```python
import torch

def _softmax(x, axis=-1):
    return torch.softmax(x, dim=axis)

def _gelu(x):
    return torch.nn.functional.gelu(x, approximate='tanh')

def _silu(x):
    return torch.nn.functional.silu(x)

def _sigmoid(x):
    return torch.sigmoid(x)

def _layernorm(x, axis=-1, eps=1e-05):
    m = x.mean(dim=axis, keepdim=True)
    v = x.var(dim=axis, keepdim=True, unbiased=False)
    return (x - m) / torch.sqrt(v + eps)

def _scatter_add(tgt, idx, src, axis=0):
    return tgt.clone().index_add_(axis, idx, src)

def _segment_sum(src, seg, n):
    out = torch.zeros((n,) + src.shape[1:], dtype=src.dtype)
    return out.index_add_(0, seg, src)

def _pad(x, pw):
    flat = tuple((v for pair in reversed(pw) for v in pair))
    return torch.nn.functional.pad(x, flat)
kernel_name = 'interleave_layers__memory_aug_recurrent_mem_tr__glu_gated_geglu__prompt'

def setup_inputs():

    _w = lambda a: (lambda t: t.to(torch.bfloat16) if t.is_floating_point() else t)(torch.as_tensor(a))

    def _A_setup():
        B, S, Dm = (1, 2048, 1024)
        H, Dh = (32, 128)
        M, seg = (8, 32)
        seg = min(seg, S)
        S = S // seg * seg
        return {'x': _w((lambda *s: torch.randn(*s, dtype=torch.bfloat16) * 0.05)(B, S, Dm)), 'mem0': _w((lambda *s: torch.randn(*s, dtype=torch.bfloat16) * 0.2)(B, M, Dm)), 'Wq': _w((lambda *s: torch.randn(*s, dtype=torch.bfloat16) * 1.6)(Dm, H, Dh) * Dm ** (-0.5)), 'Wk': _w((lambda *s: torch.randn(*s, dtype=torch.bfloat16) * 1.6)(Dm, H, Dh) * Dm ** (-0.5)), 'Wv': _w((lambda *s: torch.randn(*s, dtype=torch.bfloat16) * 0.2)(Dm, H, Dh) * Dm ** (-0.5)), 'Wo': _w((lambda *s: torch.randn(*s, dtype=torch.bfloat16) * 0.2)(H, Dh, Dm) * (H * Dh) ** (-0.5)), 'seg_len': seg}
    _A_in = _A_setup()

    def _B_setup():
        B, S, Dm, Df = (1, 2048, 1024, 3584)
        return {'x': _w((lambda *s: torch.randn(*s, dtype=torch.bfloat16) * 0.05)(B, S, Dm)), 'w_gate': _w((lambda *s: torch.randn(*s, dtype=torch.bfloat16) * 0.4)(Dm, Df) * Dm ** (-0.5)), 'w_up': _w((lambda *s: torch.randn(*s, dtype=torch.bfloat16) * 0.4)(Dm, Df) * Dm ** (-0.5)), 'w_down': _w((lambda *s: torch.randn(*s, dtype=torch.bfloat16) * 0.4)(Df, Dm) * Df ** (-0.5))}
    _B_in = _B_setup()
    return {'A_x': _A_in['x'], 'A_mem0': _A_in['mem0'], 'A_Wq': _A_in['Wq'], 'A_Wk': _A_in['Wk'], 'A_Wv': _A_in['Wv'], 'A_Wo': _A_in['Wo'], 'A_seg_len': _A_in['seg_len'], 'B_x': _B_in['x'], 'B_w_gate': _B_in['w_gate'], 'B_w_up': _B_in['w_up'], 'B_w_down': _B_in['w_down']}

def reference(A_x, A_mem0, A_Wq, A_Wk, A_Wv, A_Wo, A_seg_len, B_x, B_w_gate, B_w_up, B_w_down):

    def _A_ref(x, mem0, Wq, Wk, Wv, Wo, seg_len):
        B, S, Dm = x.shape
        H, Dh = (Wq.shape[1], Wq.shape[2])
        M = mem0.shape[1]
        scale = Dh ** (-0.5)
        n_seg = S // seg_len
        L = M + seg_len
        idx = torch.arange(L)
        mask = (idx[:, None] < M) | (idx[:, None] >= idx[None, :])
        mem = mem0
        outs = []
        for s in range(n_seg):
            xs = x[:, s * seg_len:(s + 1) * seg_len, :].clone()
            h = torch.concatenate([mem, xs], axis=1)
            q = torch.einsum('btd,dhe->bhte', h, Wq)
            k = torch.einsum('btd,dhe->bhte', h, Wk)
            v = torch.einsum('btd,dhe->bhte', h, Wv)
            scores = torch.einsum('bhqe,bhke->bhqk', q, k) * scale
            scores = torch.where(mask[None, None], scores, -1000000000.0)
            p = _softmax(scores, axis=-1)
            o = torch.einsum('bhqk,bhke->bhqe', p, v)
            o = torch.einsum('bhte,hed->btd', o, Wo)
            mem = o[:, :M, :].clone()
            outs.append(o[:, M:, :])
        return torch.concatenate(outs, axis=1)

    def _B_ref(x, w_gate, w_up, w_down):
        g = torch.einsum('bsd,df->bsf', x, w_gate)
        u = torch.einsum('bsd,df->bsf', x, w_up)
        h = _gelu(g) * u
        return torch.einsum('bsf,fd->bsd', h, w_down)
    x = A_x
    x = x + _A_ref(_layernorm(x, axis=-1), A_mem0, A_Wq, A_Wk, A_Wv, A_Wo, A_seg_len)
    x = x + _B_ref(_layernorm(x, axis=-1), B_w_gate, B_w_up, B_w_down)
    x = x + _A_ref(_layernorm(x, axis=-1), A_mem0, A_Wq, A_Wk, A_Wv, A_Wo, A_seg_len)
    x = x + _B_ref(_layernorm(x, axis=-1), B_w_gate, B_w_up, B_w_down)
    return x
```

```cpp
#include <cuda_runtime.h>
#include <cuda_bf16.h>
#include <cuda.h>
#include <stdint.h>

#define DEVI __device__ __forceinline__
typedef __nv_bfloat16 bf16;

#define LAG 16
constexpr int SEQ = 2048, DM = 1024, NH = 32, DH = 128, DF = 3584, NSEG = 64, NSTEP = NSEG + LAG;
static_assert(NSTEP % 2 == 0, "tags and slots of the exchange buffers return to their initial state");

__device__ __align__(1024) bf16 g_xn[2][NSTEP * 32 * DM];
__device__ __align__(1024) bf16 g_o[2][SEQ * NH * DH];
__device__ __align__(1024) bf16 g_x1[2][SEQ * DM];
__device__ __align__(1024) bf16 g_xm[2][SEQ * DM];
__device__ __align__(1024) bf16 g_x2[SEQ * DM];
__device__ __align__(1024) bf16 g_h[2][SEQ * DF];
__device__ __align__(1024) uint4 g_part[256 * 32 * 8];
__device__ __align__(1024) uint32_t g_ann[2][32][64];
__device__ __align__(1024) uint4 g_mem[2][2048];
struct Flags {
  int xn[2][16][32];
  int o[2][16][32];
  int x1[2][16][32];
  int xm[2][16][32];
  int h[2][16][32];
  int x2[16][32];
  int ticket[64];
};
__device__ __align__(128) Flags g_fl;

DEVI uint32_t smem_u32(const void* p) { return (uint32_t)__cvta_generic_to_shared(p); }
DEVI void mbar_init(uint32_t bar, uint32_t cnt) { asm volatile("mbarrier.init.shared::cta.b64 [%0], %1;" :: "r"(bar), "r"(cnt) : "memory"); }
DEVI void mbar_expect_tx(uint32_t bar, uint32_t bytes) { asm volatile("mbarrier.arrive.expect_tx.shared::cta.b64 _, [%0], %1;" :: "r"(bar), "r"(bytes) : "memory"); }
DEVI void mbar_arrive(uint32_t bar) { asm volatile("mbarrier.arrive.shared::cta.b64 _, [%0];" :: "r"(bar) : "memory"); }
DEVI bool mbar_try(uint32_t bar, uint32_t parity) {
  uint32_t p;
  asm volatile("{.reg .pred p; mbarrier.try_wait.parity.shared::cta.b64 p, [%1], %2; selp.u32 %0, 1, 0, p;}" : "=r"(p) : "r"(bar), "r"(parity) : "memory");
  return p;
}
constexpr int SPIN_BUDGET = 1 << 20;
DEVI void mbar_wait(uint32_t bar, uint32_t parity, int& budget) {
  while (!mbar_try(bar, parity)) { if (--budget < 0) break; }
}
DEVI uint32_t mapa(uint32_t addr, uint32_t rank) { uint32_t r; asm("mapa.shared::cluster.u32 %0, %1, %2;" : "=r"(r) : "r"(addr), "r"(rank)); return r; }
DEVI void cluster_arrive() { asm volatile("barrier.cluster.arrive.release.aligned;" ::: "memory"); }
DEVI void cluster_wait() { asm volatile("barrier.cluster.wait.acquire.aligned;" ::: "memory"); }
DEVI void fence_mbar_init() { asm volatile("fence.mbarrier_init.release.cluster;" ::: "memory"); }
DEVI void fence_proxy_async() { asm volatile("fence.proxy.async.shared::cta;" ::: "memory"); }
DEVI void tma_load_2d(uint32_t dst, const CUtensorMap* m, int c0, int c1, uint32_t bar) {
  asm volatile("cp.async.bulk.tensor.2d.shared::cluster.global.mbarrier::complete_tx::bytes [%0], [%1, {%3, %4}], [%2];"
    :: "r"(dst), "l"(m), "r"(bar), "r"(c0), "r"(c1) : "memory");
}
DEVI void tma_load_5d(uint32_t dst, const CUtensorMap* m, int c0, int c4, uint32_t bar) {
  asm volatile("cp.async.bulk.tensor.5d.shared::cluster.global.mbarrier::complete_tx::bytes [%0], [%1, {%3, %5, %5, %5, %4}], [%2];"
    :: "r"(dst), "l"(m), "r"(bar), "r"(c0), "r"(c4), "r"(0) : "memory");
}
DEVI void tma_prefetch_2d(const CUtensorMap* m, int c0, int c1) {
  asm volatile("cp.async.bulk.prefetch.tensor.2d.L2.global [%0, {%1, %2}];" :: "l"(m), "r"(c0), "r"(c1) : "memory");
}
DEVI void tma_prefetch_5d(const CUtensorMap* m, int c0, int c4) {
  asm volatile("cp.async.bulk.prefetch.tensor.5d.L2.global [%0, {%1, %3, %3, %3, %2}];" :: "l"(m), "r"(c0), "r"(c4), "r"(0) : "memory");
}
#define ELECT "{.reg .pred p; elect.sync _|p, 0xffffffff;\n @p "
DEVI void e_expect_tx(uint32_t bar, uint32_t bytes) { asm volatile(ELECT "mbarrier.arrive.expect_tx.shared::cta.b64 _, [%0], %1;}" :: "r"(bar), "r"(bytes) : "memory"); }
DEVI void e_arrive(uint32_t bar) { asm volatile(ELECT "mbarrier.arrive.shared::cta.b64 _, [%0];}" :: "r"(bar) : "memory"); }
DEVI void e_arrive_cl(uint32_t bar) { asm volatile(ELECT "mbarrier.arrive.shared::cluster.b64 _, [%0];}" :: "r"(bar) : "memory"); }
DEVI void e_tma_2d(uint32_t dst, const CUtensorMap* m, int c0, int c1, uint32_t bar) {
  asm volatile(ELECT "cp.async.bulk.tensor.2d.shared::cluster.global.mbarrier::complete_tx::bytes [%0], [%1, {%3, %4}], [%2];}"
    :: "r"(dst), "l"(m), "r"(bar), "r"(c0), "r"(c1) : "memory");
}
DEVI void e_tma_store_2d(const CUtensorMap* m, uint32_t src, int c0, int c1) {
  asm volatile(ELECT "cp.async.bulk.tensor.2d.global.shared::cta.bulk_group [%0, {%2, %3}], [%1];}" :: "l"(m), "r"(src), "r"(c0), "r"(c1) : "memory");
}
DEVI void e_flag_add(int* p, int v = 1) {
  asm volatile("{.reg .pred p; elect.sync _|p, 0xffffffff;\n fence.proxy.async.global; @p red.release.gpu.global.add.s32 [%0], %1;}" :: "l"(p), "r"(v) : "memory");
}
DEVI int e_ticket(int* p) { int v = 0; asm volatile(ELECT "atom.relaxed.gpu.global.add.s32 %0, [%1], 1;}" : "+r"(v) : "l"(p) : "memory"); return v; }
DEVI int bcast(int v) { return __reduce_max_sync(0xffffffffu, v); }
DEVI int ld_acquire(const int* p) { int v; asm volatile("ld.acquire.gpu.global.s32 %0, [%1];" : "=r"(v) : "l"(p) : "memory"); return __shfl_sync(0xffffffffu, v, 0); }
DEVI void e_tma_3d(uint32_t dst, const CUtensorMap* m, int c0, int c1, uint32_t bar) {
  asm volatile(ELECT "cp.async.bulk.tensor.3d.shared::cluster.global.mbarrier::complete_tx::bytes [%0], [%1, {%3, %4, %5}], [%2];}"
    :: "r"(dst), "l"(m), "r"(bar), "r"(c0), "r"(c1), "r"(0) : "memory");
}
DEVI void e_tma_5d(uint32_t dst, const CUtensorMap* m, int c0, int c4, uint32_t bar) {
  asm volatile(ELECT "cp.async.bulk.tensor.5d.shared::cluster.global.mbarrier::complete_tx::bytes [%0], [%1, {%3, %5, %5, %5, %4}], [%2];}"
    :: "r"(dst), "l"(m), "r"(bar), "r"(c0), "r"(c4), "r"(0) : "memory");
}
DEVI void e_bulk_g2s(uint32_t dst, const void* src, uint32_t bytes, uint32_t bar) {
  asm volatile(ELECT "cp.async.bulk.shared::cluster.global.mbarrier::complete_tx::bytes [%0], [%1], %2, [%3];}" :: "r"(dst), "l"(src), "r"(bytes), "r"(bar) : "memory");
}
DEVI void e_prefetch(const void* src, uint32_t bytes) {
  asm volatile(ELECT "cp.async.bulk.prefetch.L2.global [%0], %1;}" :: "l"(src), "r"(bytes) : "memory");
}
DEVI void bulk_commit() { asm volatile("cp.async.bulk.commit_group;" ::: "memory"); }
template<int N> DEVI void bulk_wait_read() { asm volatile("cp.async.bulk.wait_group.read %0;" :: "n"(N) : "memory"); }
template<int N> DEVI void bulk_wait() { asm volatile("cp.async.bulk.wait_group %0;" :: "n"(N) : "memory"); }
template<int ID, int N> DEVI void nbar_sync() { asm volatile("bar.sync %0, %1;" :: "n"(ID), "n"(N) : "memory"); }
template<int ID, int N> DEVI void nbar_arrive() { asm volatile("bar.arrive %0, %1;" :: "n"(ID), "n"(N) : "memory"); }
DEVI void nbar_sync_r(int id, int n) { asm volatile("bar.sync %0, %1;" :: "r"(id), "r"(n) : "memory"); }
DEVI void nbar_arrive_r(int id, int n) { asm volatile("bar.arrive %0, %1;" :: "r"(id), "r"(n) : "memory"); }
template<int R> DEVI void reg_inc() { asm volatile("setmaxnreg.inc.sync.aligned.u32 %0;" :: "n"(R)); }
template<int R> DEVI void reg_dec() { asm volatile("setmaxnreg.dec.sync.aligned.u32 %0;" :: "n"(R)); }
DEVI void wg_fence() { asm volatile("wgmma.fence.sync.aligned;" ::: "memory"); }
DEVI void wg_commit() { asm volatile("wgmma.commit_group.sync.aligned;" ::: "memory"); }
template<int N> DEVI void wg_wait() { asm volatile("wgmma.wait_group.sync.aligned %0;" :: "n"(N) : "memory"); }
DEVI uint32_t pack_bf16(float lo, float hi) { uint32_t r; asm("cvt.rn.bf16x2.f32 %0, %1, %2;" : "=r"(r) : "f"(hi), "f"(lo)); return r; }
DEVI float bf_lo(uint32_t v) { return __uint_as_float(v << 16); }
DEVI float bf_hi(uint32_t v) { return __uint_as_float(v & 0xffff0000u); }
DEVI uint32_t movmat(uint32_t a) { uint32_t r; asm volatile("movmatrix.sync.aligned.m8n8.trans.b16 %0, %1;" : "=r"(r) : "r"(a)); return r; }
DEVI void ldsm4(uint32_t addr, uint32_t& r0, uint32_t& r1, uint32_t& r2, uint32_t& r3) {
  asm volatile("ldmatrix.sync.aligned.m8n8.x4.shared.b16 {%0,%1,%2,%3}, [%4];" : "=r"(r0), "=r"(r1), "=r"(r2), "=r"(r3) : "r"(addr) : "memory");
}
DEVI void ldsm4t(uint32_t addr, uint32_t& r0, uint32_t& r1, uint32_t& r2, uint32_t& r3) {
  asm volatile("ldmatrix.sync.aligned.m8n8.x4.trans.shared.b16 {%0,%1,%2,%3}, [%4];" : "=r"(r0), "=r"(r1), "=r"(r2), "=r"(r3) : "r"(addr) : "memory");
}
DEVI void stsm4(uint32_t addr, uint32_t r0, uint32_t r1, uint32_t r2, uint32_t r3) {
  asm volatile("stmatrix.sync.aligned.m8n8.x4.shared.b16 [%0], {%1,%2,%3,%4};" :: "r"(addr), "r"(r0), "r"(r1), "r"(r2), "r"(r3) : "memory");
}
DEVI uint32_t lds32v(uint32_t a) { uint32_t v; asm volatile("ld.volatile.shared.u32 %0, [%1];" : "=r"(v) : "r"(a) : "memory"); return v; }
DEVI void sts32v(uint32_t a, uint32_t v) { asm volatile("st.volatile.shared.u32 [%0], %1;" :: "r"(a), "r"(v) : "memory"); }
DEVI void st_async128(uint32_t a, uint32_t x, uint32_t y, uint32_t z, uint32_t w, uint32_t bar) {
  asm volatile("st.async.weak.shared::cluster.mbarrier::complete_tx::bytes.v4.b32 [%0], {%1,%2,%3,%4}, [%5];" :: "r"(a), "r"(x), "r"(y), "r"(z), "r"(w), "r"(bar) : "memory");
}
DEVI void st_async32(uint32_t a, uint32_t x, uint32_t bar) {
  asm volatile("st.async.weak.shared::cluster.mbarrier::complete_tx::bytes.b32 [%0], %1, [%2];" :: "r"(a), "r"(x), "r"(bar) : "memory");
}
DEVI uint4 ldg_rlx128(const void* p) {
  uint4 v;
  asm volatile("ld.relaxed.gpu.global.v4.b32 {%0,%1,%2,%3}, [%4];" : "=r"(v.x), "=r"(v.y), "=r"(v.z), "=r"(v.w) : "l"(p) : "memory");
  return v;
}
DEVI void stg_rlx128(void* p, uint32_t x, uint32_t y, uint32_t z, uint32_t w) {
  asm volatile("st.relaxed.gpu.global.v4.b32 [%0], {%1,%2,%3,%4};" :: "l"(p), "r"(x), "r"(y), "r"(z), "r"(w) : "memory");
}
DEVI void stg128(void* p, uint32_t x, uint32_t y, uint32_t z, uint32_t w) {
  asm volatile("st.global.v4.b32 [%0], {%1,%2,%3,%4};" :: "l"(p), "r"(x), "r"(y), "r"(z), "r"(w) : "memory");
}
DEVI void stg_rlx32(void* p, uint32_t x) { asm volatile("st.relaxed.gpu.global.b32 [%0], %1;" :: "l"(p), "r"(x) : "memory"); }
DEVI uint32_t clock32() { uint32_t c; asm volatile("mov.u32 %0, %%clock;" : "=r"(c) :: "memory"); return c; }
DEVI uint32_t gtime() { uint32_t c; asm volatile("mov.u32 %0, %%globaltimer_lo;" : "=r"(c) :: "memory"); return c; }
DEVI void wait_time(uint32_t t, int& budget) { while ((int)(gtime() - t) < 0 && --budget > 0) {} }
DEVI uint2 ldg_rlx64(const void* p) { uint2 v; asm volatile("ld.relaxed.gpu.global.v2.b32 {%0,%1}, [%2];" : "=r"(v.x), "=r"(v.y) : "l"(p) : "memory"); return v; }
DEVI void sts16(uint32_t a, float x) { asm volatile("{.reg .b16 t; cvt.rn.bf16.f32 t, %1; st.shared.b16 [%0], t;}" :: "r"(a), "f"(x) : "memory"); }
DEVI void sts128(uint32_t a, uint32_t x) { asm volatile("st.shared.v4.b32 [%0], {%1,%1,%1,%1};" :: "r"(a), "r"(x) : "memory"); }
DEVI void arrive_if_eq(uint32_t bar, int a, int b) { asm volatile("{.reg .pred p; setp.eq.s32 p, %1, %2; @p mbarrier.arrive.shared::cta.b64 _, [%0];}" :: "r"(bar), "r"(a), "r"(b) : "memory"); }
template<int ID, int N> DEVI bool nbar_or(bool x) {
  uint32_t r;
  asm volatile("{.reg .pred p, q; setp.ne.u32 p, %1, 0; bar.red.or.pred q, %2, %3, p; selp.u32 %0, 1, 0, q;}" : "=r"(r) : "r"((uint32_t)x), "n"(ID), "n"(N) : "memory");
  return r;
}
DEVI void spin_until(uint32_t t0, int d) { while ((int)(clock32() - t0) < d) {} }
DEVI void flag_wait(const int* p, int n, int& budget) {
  while (ld_acquire(p) < n && --budget > 0) __nanosleep(32);
  asm volatile("fence.proxy.async.global;" ::: "memory");
}

#define F4(C, o)  C(d[o+0]), C(d[o+1]), C(d[o+2]), C(d[o+3])
#define F8(C, o)  F4(C, o), F4(C, o+4)
#define F32(C, o) F8(C, o), F8(C, o+8), F8(C, o+16), F8(C, o+24)
#define R4  "{%0,%1,%2,%3}"
#define R8  "{%0,%1,%2,%3,%4,%5,%6,%7}"
#define R20 "{%0,%1,%2,%3,%4,%5,%6,%7,%8,%9,%10,%11,%12,%13,%14,%15,%16,%17,%18,%19}"
#define R32 "{%0,%1,%2,%3,%4,%5,%6,%7,%8,%9,%10,%11,%12,%13,%14,%15,%16,%17,%18,%19,%20,%21,%22,%23,%24,%25,%26,%27,%28,%29,%30,%31}"
#define R64 "{%0,%1,%2,%3,%4,%5,%6,%7,%8,%9,%10,%11,%12,%13,%14,%15,%16,%17,%18,%19,%20,%21,%22,%23,%24,%25,%26,%27,%28,%29,%30,%31," \
  "%32,%33,%34,%35,%36,%37,%38,%39,%40,%41,%42,%43,%44,%45,%46,%47,%48,%49,%50,%51,%52,%53,%54,%55,%56,%57,%58,%59,%60,%61,%62,%63}"
template<uint32_t OFF, uint32_t LBO, uint32_t SBO, uint32_t SW, int T> struct Op {
  static constexpr uint32_t lo = (OFF >> 4) | ((LBO >> 4) << 16), hi = (SBO >> 4) | (SW << 30);
  static constexpr int t = T;
};
DEVI uint32_t desc_base(uint32_t addr) { return (addr & 0x3FFFF) >> 4; }
#define RS_ASM(SHAPE, REGS, A0, A1, A2, A3, B, LO, HI, T, SD) \
  "{.reg .b64 tb; .reg .b32 lb; add.u32 lb, " B ", " LO "; mov.b64 tb, {lb, " HI "};\n" \
  "wgmma.mma_async.sync.aligned." SHAPE ".f32.bf16.bf16 " REGS ", {" A0 "," A1 "," A2 "," A3 "}, tb, " SD ", 1, 1, " T ";}"
#define WG_RS(NAME, SHAPE, REGS, LIST, ...) \
  template<int ACC, class OB> DEVI void NAME(float* d, const uint32_t* a, uint32_t b) { \
    if (ACC) asm volatile(RS_ASM(SHAPE, REGS, __VA_ARGS__) \
      : LIST("+f") : "r"(a[0]), "r"(a[1]), "r"(a[2]), "r"(a[3]), "r"(b), "n"(OB::lo), "n"(OB::hi), "n"(OB::t), "n"(ACC & 1)); \
    else asm volatile(RS_ASM(SHAPE, REGS, __VA_ARGS__) \
      : LIST("=f") : "r"(a[0]), "r"(a[1]), "r"(a[2]), "r"(a[3]), "r"(b), "n"(OB::lo), "n"(OB::hi), "n"(OB::t), "n"(0)); \
  }
#define SS_ASM(SHAPE, REGS, A, B, LA, HA, TA, LB, HB, TB, SD) \
  "{.reg .b64 ta, tb; .reg .b32 la, lb; add.u32 la, " A ", " LA "; mov.b64 ta, {la, " HA "}; add.u32 lb, " B ", " LB "; mov.b64 tb, {lb, " HB "};\n" \
  "wgmma.mma_async.sync.aligned." SHAPE ".f32.bf16.bf16 " REGS ", ta, tb, " SD ", 1, 1, " TA ", " TB ";}"
#define WG_SS(NAME, SHAPE, REGS, LIST, ...) \
  template<int ACC, class OA, class OB> DEVI void NAME(float* d, uint32_t a, uint32_t b) { \
    if (ACC) asm volatile(SS_ASM(SHAPE, REGS, __VA_ARGS__) \
      : LIST("+f") : "r"(a), "r"(b), "n"(OA::lo), "n"(OA::hi), "n"(OA::t), "n"(OB::lo), "n"(OB::hi), "n"(OB::t), "n"(ACC & 1)); \
    else asm volatile(SS_ASM(SHAPE, REGS, __VA_ARGS__) \
      : LIST("=f") : "r"(a), "r"(b), "n"(OA::lo), "n"(OA::hi), "n"(OA::t), "n"(OB::lo), "n"(OB::hi), "n"(OB::t), "n"(0)); \
  }
#define L4(C)  F4(C, 0)
#define L8(C)  F8(C, 0)
#define L20(C) F8(C, 0), F8(C, 8), F4(C, 16)
#define L32(C) F32(C, 0)
WG_RS(wg_rs8, "m64n8k16", R4, L4, "%4", "%5", "%6", "%7", "%8", "%9", "%10", "%11", "%12")
WG_RS(wg_rs16, "m64n16k16", R8, L8, "%8", "%9", "%10", "%11", "%12", "%13", "%14", "%15", "%16")
WG_RS(wg_rs64, "m64n64k16", R32, L32, "%32", "%33", "%34", "%35", "%36", "%37", "%38", "%39", "%40")
WG_SS(wg_ss8, "m64n8k16", R4, L4, "%4", "%5", "%6", "%7", "%8", "%9", "%10", "%11", "%12")
WG_SS(wg_ss16, "m64n16k16", R8, L8, "%8", "%9", "%10", "%11", "%12", "%13", "%14", "%15", "%16")
WG_SS(wg_ss40, "m64n40k16", R20, L20, "%20", "%21", "%22", "%23", "%24", "%25", "%26", "%27", "%28")
WG_SS(wg_ss64, "m64n64k16", R32, L32, "%32", "%33", "%34", "%35", "%36", "%37", "%38", "%39", "%40")
#define L64(C) F32(C, 0), F32(C, 32)
WG_SS(wg_ss128, "m64n128k16", R64, L64, "%64", "%65", "%66", "%67", "%68", "%69", "%70", "%71", "%72")
template<int I> struct IC { __host__ __device__ constexpr operator int() const { return I; } };
template<int I, int N, class F> DEVI void sfor(F&& f) {
  if constexpr (I < N) { f(IC<I>{}); sfor<I + 1, N>(f); }
}

namespace rec {
constexpr int NHI = 36, NLO = 5, NRS = NHI + NLO, NSS = 64 - NRS;
constexpr uint32_t WS = 0;
constexpr uint32_t WO = 2 * NSS * 2048;
constexpr uint32_t RING = WO + 65536;
constexpr uint32_t QB = RING + 40960, RG = 2080, POSQ = 0x64210, POSK = 0xB9753, POSV = 0xEDCA8;
constexpr uint32_t WA = QB;
constexpr uint32_t OM = QB + 9 * RG, OMS = 2 * RG;
constexpr uint32_t OM2 = QB + 16384, OM2S = 2048;
constexpr uint32_t WH = QB + 20480;
constexpr uint32_t B_PART = QB + 15 * RG - 32;
constexpr uint32_t PM0 = QB + 16384, PM1 = QB + 15 * RG, PM2 = PM1 + 256;
constexpr uint32_t BARS = PM2 + 128;
constexpr uint32_t B_FULL = BARS, B_EMPTY = BARS + 40, B_MLAND = BARS + 80, B_QK = BARS + 112, B_V = BARS + 120, B_OM = BARS + 128,
                   B_WA = BARS + 136, B_SDONE = BARS + 144, B_BFREE = BARS + 152, B_W1 = PM1, B_W2 = PM1 + 8, B_WO = PM1 + 16;
constexpr uint32_t SMEM = BARS + 160;
static_assert(SMEM <= 232448 && QB % 1024 == 0, "smem map");
constexpr int R1 = (PM1 - WO) / 4096;
constexpr int NB_WO = 1, NB_ST = 2, NB_P = 3, NB_TR = 4, NB_X = 5, NB_G = 6;
__host__ __device__ constexpr bool is_lo(int j) { return j % 12 == 8; }
__host__ __device__ constexpr int lo_before(int j) { return (j + 3) / 12; }
__host__ __device__ constexpr int ss_before(int j) { return (j - lo_before(j)) * NSS / (64 - NLO); }
__host__ __device__ constexpr bool is_ss(int j) { return ss_before(j + 1) != ss_before(j); }
__host__ __device__ constexpr int reg_idx(int j) { return is_lo(j) ? NHI + lo_before(j) : j - ss_before(j) - lo_before(j); }
#define LOQ(i) ((0x12010 >> (4 * (i))) & 3)
template<int j> using OpW = Op<WS + ss_before(j) * 2048, 16, 1024, 1, 1>;
#define P_NA 4
#define P_M1 3
#define P_M2 3
#define TUN(i, v) (v)
}
#define PROFW(wq, i)
template<int N> DEVI void pin(float* d) {
#pragma unroll
  for (int i = 0; i < N; i++) asm volatile("" : "+f"(d[i]) :: "memory");
}
DEVI void sched_fence(int budget) { asm volatile("{.reg .pred p; setp.eq.s32 p, %0, 0x7fffff00; @p exit;}" :: "r"(budget) : "memory"); }
DEVI int lane_reg() { return __shfl_sync(0xffffffffu, threadIdx.x & 31, threadIdx.x & 31); }
#define LANE_NOW [[maybe_unused]] const int lane = lane0 + ((uint32_t)budget >> 30), g = lane >> 2, c = lane & 3

DEVI void rec_proj(const uint32_t sb, const int h, const int rank, const int w, const CUtensorMap* mW, const CUtensorMap* mWo, const uint32_t zero) {
  using namespace rec;
  const int lane0 = lane_reg(), wg = w >> 2, ww = w & 3;
  int budget = SPIN_BUDGET;
  uint32_t wr[NRS * 4];
  {
    LANE_NOW;
    const uint32_t wsw = ((lane & 7) + (lane >> 4) * 8) * 128 + (((ww * 2 + ((lane >> 3) & 1)) ^ (lane & 7)) << 4);
    mbar_wait(sb + B_W1, 0, budget);
#pragma unroll
    for (int r = 0; r < R1; r++) ldsm4t(sb + WO + (wg * R1 + r) * 2048 + wsw, wr[4*r], wr[4*r+1], wr[4*r+2], wr[4*r+3]);
    fence_proxy_async();
    nbar_sync<NB_ST, 256>();
    if (w == 0) {
      if (lane == 0) { mbar_expect_tx(sb + B_W2, (NRS - R1) * 4096); mbar_expect_tx(sb + B_WO, rank == 2 ? 65536 + 16384 + 8192 : 65536); }
      __syncwarp();
      for (int i = lane; i < 128; i += 32) {
        const int j = i & 63, t = i >> 6, r = reg_idx(j);
        if (!is_ss(j) && r >= R1) tma_load_2d(sb + RING + (t * (NRS - R1) + r - R1) * 2048, mW, h * DH + t * 64, j * 16, sb + B_W2);
      }
      const int t0 = (rank + 1) % 3;
      if (lane < 8) tma_load_5d(sb + WO + lane * 8192, mWo, (3 * (lane >> 1) + 3 + t0) * 64, h * 4 + (lane & 1) * 2, sb + B_WO);
      else if (rank == 2 && lane < 11) tma_load_5d(lane < 10 ? sb + WA + (lane - 8) * 8192 : sb + WH, mWo, lane < 10 ? 0 : 15 * 64, h * 4 + (lane > 8) * 2, sb + B_WO);
    }
    mbar_wait(sb + B_W2, 0, budget);
#pragma unroll
    for (int r = R1; r < NRS; r++) ldsm4t(sb + RING + (wg * (NRS - R1) + r - R1) * 2048 + wsw, wr[4*r], wr[4*r+1], wr[4*r+2], wr[4*r+3]);
    fence_proxy_async();
    cluster_arrive(); cluster_wait();
  }
  const uint32_t d0 = desc_base(sb), da = d0 + wg * (NSS * 128);
  const uint32_t pos = rank == 0 ? POSQ : rank == 1 ? POSK : POSV, bar = rank == 2 ? B_V : B_QK;
  uint32_t stg[3][4] = {}, pk[16] = {};
  auto stage = [&](uint32_t* t, int r) {
#pragma unroll
    for (int i = 0; i < 4; i++) asm volatile("xor.b32 %0, %1, %2;" : "+r"(t[i]) : "r"(wr[4 * r + i]), "r"(zero));
  };
#pragma unroll 1
  for (int s = -1; s < NSTEP; s++) {
    if (s >= 0) {
      float d[8];
      sfor<0, 4>([&](auto Q) {
        constexpr int q = Q;
        sfor<lo_before(16 * q), lo_before(16 * q + 16)>([&](auto I) { constexpr int i = I; stage(stg[LOQ(i)], NHI + i); });
        mbar_wait(sb + B_FULL + 8 * q, 0, budget);
        if (q == 0) PROFW(0, 16);
        wg_fence();
        sfor<16 * q, 16 * q + 16>([&](auto J) {
          constexpr int j = J;
          typedef Op<RING + j * 512, 256, 128, 0, 1> OB;
          if constexpr (is_ss(j)) wg_ss16<j != 0, OpW<j>, OB>(d, da, d0);
          else wg_rs16<j != 0, OB>(d, is_lo(j) ? stg[LOQ(lo_before(j))] : wr + 4 * reg_idx(j), d0);
        });
        wg_commit();
        if (q == 0 && s > 0) mbar_wait(sb + B_BFREE, (s & 1) ^ 1, budget);
        sfor<q ? q + 1 : 0, q < 3 ? q + 2 : 0>([&](auto N) {
          constexpr int n = N;
          LANE_NOW;
          const uint32_t r = mapa(sb, n >> 1);
          uint32_t t[4];
#pragma unroll
          for (int i = 0; i < 4; i++) { if (n == 0) t[i] = pk[i]; else asm volatile("xor.b32 %0, %1, %2;" : "=r"(t[i]) : "r"(pk[4*n+i]), "r"(zero)); }
          st_async128(r + QB + ((pos >> (4 + 4 * c)) & 15) * RG + w * 256 + (n & 1) * 128 + g * 16, t[0], t[1], t[2], t[3], r + bar);
        });
        if constexpr (q > 0) {
          wg_wait<1>();
          arrive_if_eq(sb + B_EMPTY + 8 * (q - 1), lane0, ww * 32);
        }
      });
      LANE_NOW;
      const uint32_t dst = QB + (pos & 15) * RG + w * 256 + lane * 4;
      wg_wait<0>();
      pin<8>(d);
#pragma unroll
      for (int l = 0; l < 2; l++) {
        const uint32_t r = mapa(sb, l);
        st_async32(r + dst, pack_bf16(d[4*l], d[4*l+1]), r + bar);
        st_async32(r + dst + 128, pack_bf16(d[4*l+2], d[4*l+3]), r + bar);
      }
      PROFW(0, 17);
      if (s == NSTEP - 1) break;
      arrive_if_eq(sb + B_EMPTY + 24, lane0, ww * 32);
    } else e_arrive(sb + B_EMPTY + 8 * ww);
    float d[32];
    sfor<0, 16>([&](auto C) {
      constexpr int cc = C, sl = (cc + 4) % 5, mode = cc < P_NA ? P_M1 : P_M2;
      constexpr bool last = cc == P_NA - 1 || cc == 15, first = cc == 0 || cc == P_NA;
      if constexpr (is_lo(cc * 4) && (mode != 3 || first)) stage(stg[0], reg_idx(cc * 4));
      if constexpr (mode != 3 || first) mbar_wait(sb + B_FULL + 8 * sl, ((cc + 4) / 5) & 1, budget);
      if constexpr (cc == P_NA) {
        PROFW(0, 18);
        nbar_sync<NB_WO, 384>();
      }
      sfor<0, 4>([&](auto I) {
        constexpr int i = I, j = cc * 4 + i;
        typedef Op<RING + sl * 8192 + i * 32, 16, 1024, 1, 0> OB;
        if constexpr (i == 0 || mode == 2) wg_fence();
        if constexpr (is_ss(j)) wg_ss64<j != 0, OpW<j>, OB>(d, da, d0);
        else wg_rs64<j != 0, OB>(d, is_lo(j) ? stg[0] : wr + 4 * reg_idx(j), d0);
        if constexpr (i == 3 || mode == 2) wg_commit();
        if constexpr (mode == 2 || (mode == 0 && i == 3)) {
          wg_wait<1>();
          if constexpr ((i == 0 || mode == 0) && !first) arrive_if_eq(sb + B_EMPTY + 8 * ((sl + 4) % 5), lane0, ww * 32);
        }
      });
      if constexpr (cc == P_NA) PROFW(0, 19);
      if constexpr (mode == 3 && !last) {
        if constexpr (is_lo(cc * 4 + 4)) stage(stg[0], reg_idx(cc * 4 + 4));
        mbar_wait(sb + B_FULL + 8 * ((sl + 1) % 5), ((cc + 5) / 5) & 1, budget);
      }
      if constexpr (mode == 1 || mode == 3 || last) {
        wg_wait<0>();
        arrive_if_eq(sb + B_EMPTY + 8 * sl, lane0, ww * 32);
      }
    });
    pin<32>(d);
    PROFW(0, 20);
#pragma unroll
    for (int i = 0; i < 16; i++) pk[i] = pack_bf16(d[16 * (i >> 3) + 4 * (i & 3) + ((i >> 1) & 2)], d[16 * (i >> 3) + 4 * (i & 3) + ((i >> 1) & 2) + 1]);
  }
}

DEVI float softmax_row(float* v, int lim, uint32_t* p) {
  constexpr float SC = 0.08838834764831845f * 1.4426950408889634f;
#pragma unroll
  for (int i = 0; i < 8; i++) v[2+i] = i <= lim ? v[2+i] : -INFINITY;
  float m = fmaxf(fmaxf(fmaxf(fmaxf(v[0], v[1]), fmaxf(v[2], v[3])), fmaxf(fmaxf(v[4], v[5]), fmaxf(v[6], v[7]))), fmaxf(v[8], v[9]));
  m = fmaxf(m, __shfl_xor_sync(0xffffffffu, m, 1));
  m = fmaxf(m, __shfl_xor_sync(0xffffffffu, m, 2));
  const float ms = -m * SC, mh = ms - 1.f;
#pragma unroll
  for (int i = 0; i < 10; i++) asm("ex2.approx.ftz.f32 %0, %1;" : "=f"(v[i]) : "f"(fmaf(v[i], SC, i < 8 ? ms : mh)));
#pragma unroll
  for (int n = 0; n < 5; n++) p[n] = pack_bf16(v[2*n], v[2*n+1]);
  return fmaf(v[8] + v[9], 2.f, ((v[0] + v[1]) + (v[2] + v[3])) + ((v[4] + v[5]) + (v[6] + v[7])));
}

template<bool ATT>
DEVI void rec_attn(const uint32_t sb, int h, int rank, int w, const CUtensorMap* mWo,
                   const bf16* __restrict__ Wo, const bf16* __restrict__ mem0) {
  using namespace rec;
  const int lane0 = lane_reg();
  int budget = SPIN_BUDGET;
  constexpr int NT = ATT ? 5 : 6;
  uint32_t wl[16];
  if (!ATT) {
    LANE_NOW;
#pragma unroll
    for (int i = 0; i < 16; i++) {
      const int kk = i >> 2, dh = 32 * (kk >> 1) + 8 * c + 2 * ((kk & 1) * 2 + ((i >> 1) & 1));
      const unsigned short* p = (const unsigned short*)Wo + (size_t)(h * DH + dh) * DM + 15 * 64 + 16 * w + 8 * (i & 1) + g;
      wl[i] = p[0] | (uint32_t)p[DM] << 16;
    }
  }
  mbar_wait(sb + B_WO, 0, budget);
  cluster_arrive(); cluster_wait();
  const uint32_t d0 = desc_base(sb);
  uint32_t pph = 0;
#pragma unroll 1
  for (int s = -1; s < NSTEP; s++) {
    asm volatile("" : "+r"(h), "+r"(rank), "+r"(w));
    const uint32_t sp = s & 1;
    const int t0 = ATT ? rank + 1 : 0;
    const bool more = s + 1 < NSTEP;
    float hold[10] = {0, 0, 0, 0, 0, 0, 0, 0, 0, 0};
    if (ATT && s >= 0) {
      float sc[20];
      LANE_NOW;
      const int lim = 8 * (g >> 1) + (g & 1) + 2 * w - 8 * c;
      mbar_wait(sb + B_QK, sp, budget);
      PROFW(0, 1);
      fence_proxy_async();
      wg_fence();
      sfor<0, 8>([&](auto K) { constexpr int k = K; wg_ss40<k != 0, Op<QB + k * 256, 128, RG, 0, 1>, Op<QB + 3 * RG + k * 256, 128, 2 * RG, 0, 1>>(sc, d0, d0); });
      wg_commit();
      if (w == 3) e_expect_tx(sb + B_QK, 20480);
      if (w == 2 && more) stg_rlx32(&g_ann[sp][lane][h * 2 + rank], (gtime() & ~31u) | ((s + 1) & 31));
      wg_wait<0>();
      pin<20>(sc);
      PROFW(0, 2);
      if (w == 3 && more) {
        e_arrive_cl(mapa(sb + B_SDONE, rank ^ 1));
        e_expect_tx(sb + B_WA, 16384);
        e_tma_5d(sb + WA, mWo, t0 * 64, h * 4, sb + B_WA);
        e_tma_5d(sb + WA + 8192, mWo, t0 * 64, h * 4 + 2, sb + B_WA);
      }
      uint32_t p[5];
      float v[10];
#pragma unroll
      for (int i = 0; i < 10; i++) v[i] = sc[4 * (i >> 1) + (i & 1)];
      const float psum = softmax_row(v, w ? lim : 64, p);
      if (w == 0) {
        const uint32_t a = sb + lane * 4;
        sts32v(a + PM0, p[0]); sts32v(a + PM0 + 128, p[1]); sts32v(a + PM1, p[2]); sts32v(a + PM1 + 128, p[3]); sts32v(a + PM2, p[4]);
      }
      mbar_wait(sb + B_V, sp, budget);
      if (more) {
        float rs[4], ot[2][4];
        uint32_t one[4];
#pragma unroll
        for (int i = 0; i < 4; i++) one[i] = 0x3F803F80u + ((uint32_t)budget >> (31 - i));
        typedef Op<PM0, 128, 128, 0, 0> P0; typedef Op<PM1, 128, 128, 0, 0> P1; typedef Op<PM2, 0, 128, 0, 0> P2;
        fence_proxy_async();
        nbar_sync<NB_P, 128>();
        PROFW(0, 3);
        wg_fence();
        wg_rs8<0, P0>(rs, one, d0); wg_rs8<1, P1>(rs, one, d0); wg_rs8<1, P2>(rs, one, d0);
        wg_commit();
        sfor<0, 2>([&](auto T) {
          constexpr int t = T;
          wg_ss8<0, Op<QB + 8 * RG + t * 128, 2 * RG, 256, 0, 0>, P0>(ot[t], d0, d0);
          wg_ss8<1, Op<QB + 12 * RG + t * 128, RG, 256, 0, 0>, P1>(ot[t], d0, d0);
          wg_ss8<1, Op<QB + 14 * RG + t * 128, 0, 256, 0, 0>, P2>(ot[t], d0, d0);
        });
        wg_commit();
        const uint32_t oa = (w * 4 + c) * 128 + g * 16;
        mbar_wait(sb + B_SDONE, sp, budget);
        wg_wait<1>();
        pin<4>(rs);
        float i0, i1;
        asm("rcp.approx.ftz.f32 %0, %1;" : "=f"(i0) : "f"(rs[0]));
        asm("rcp.approx.ftz.f32 %0, %1;" : "=f"(i1) : "f"(rs[1]));
        wg_wait<0>();
        pin<4>(ot[0]); pin<4>(ot[1]);
        uint32_t x[4];
#pragma unroll
        for (int j = 0; j < 4; j++) x[j] = movmat(pack_bf16(ot[j & 1][j & 2] * i0, ot[j & 1][(j & 2) + 1] * i1));
#pragma unroll
        for (int i = 0; i < 3; i++) {
          const uint32_t rb = mapa(sb, 2 - i);
          st_async128(rb + oa + (i ? OM + rank * OMS : OM2 + rank * OM2S), x[0], x[1], x[2], x[3], rb + B_OM);
        }
        PROFW(0, 4);
      }
#pragma unroll
      for (int i = 0; i < 10; i++) hold[i] = (w == 0 || i > 5) ? sc[4 * (i >> 1) + 2 + (i & 1)] : i < 5 ? __uint_as_float(p[i]) : psum;
      if (w == 3) e_expect_tx(sb + B_V, 10240);
    }
    if (more && s >= 0) {
      LANE_NOW;
      char* const pw = (char*)g_part + (size_t)(t0 * 16 + w * 4 + (lane >> 3)) * 4096 + h * 128 + ((lane ^ h) & 7) * 16;
      if (ATT) mbar_wait(sb + B_WA, sp, budget);
      mbar_wait(sb + B_OM, sp, budget);
      if (w == 0) nbar_arrive<NB_G, 128>();
      PROFW(1, 5);
      fence_proxy_async();
      float acc[3][8];
      sfor<0, NT + 1>([&](auto J) {
        constexpr int j = J;
        if constexpr (j < NT) {
          wg_fence();
          sfor<0, 8>([&](auto K) {
            constexpr int k = K;
            typedef Op<(ATT ? OM : OM2) + k * 256, 128, ATT ? OMS : OM2S, 0, 0> OB;
            if constexpr (j == 5 && k < 4) wg_rs16<k ? 1 : 2, OB>(acc[j % 3], wl + 4 * k, d0);
            else wg_ss16<k ? 1 : j < 3 ? 0 : 2, Op<(j == 0 ? WA : j < 5 ? WO + (j - 1) * 16384 : WH - 8192) + k * 2048, 16, 1024, 1, 1>, OB>(acc[j % 3], d0, d0);
          });
          wg_commit();
          if constexpr (j == 0) { if (w == 3) e_expect_tx(sb + B_OM, 4096); }
          if constexpr (j == NT - 1) nbar_arrive<NB_WO, 384>();
        }
        if constexpr (j > 0) {
          if constexpr (j < NT) wg_wait<1>(); else wg_wait<0>();
          float* d = acc[(j - 1) % 3];
          pin<8>(d);
          stg_rlx128(pw + (j - 1) * (48 * 4096), (pack_bf16(d[0], d[1]) & ~1u) | (sp ^ 1), pack_bf16(d[2], d[3]), pack_bf16(d[4], d[5]), pack_bf16(d[6], d[7]));
          if constexpr (ATT && j == 1) nbar_arrive<NB_TR, 160>();
        }
      });
    } else if (more) nbar_arrive<NB_WO, 384>();
    PROFW(0, 6);
    asm volatile("" : "+r"(h), "+r"(rank), "+r"(w));
    if (ATT && more) {
      LANE_NOW;
      const int blk = rank * 32 + h;
      char* const mw = (char*)g_mem + blk * 512 + w * 128 + lane * 4;
      uint32_t v = 0;
      if (s >= 0) {
        if (w == 3 && lane < 14) sts128(sb + PM1 + lane * 16, (lane >> 1) == 3 ? 0x3F803F80u : 0);
        fence_proxy_async();
        nbar_sync<NB_P, 128>();
        const uint32_t ca = sb + WA + w * 4096 + lane * 32 + (g & 1) * 16;
        const uint32_t sa = sb + OM + (((g >> 1) & 1) * 2 + (g >> 2)) * 128 + (2 * c + (w >> 1)) * 16 + (w & 1) * 8 + (g & 1) * 2;
        while (true) {
          float r[4];
          mbar_wait(sb + B_PART, pph, budget);
          PROFW(0, 11);
          pph ^= 1;
          wg_fence();
          sfor<0, 8>([&](auto K) { constexpr int k = K; wg_ss8<k != 0, Op<WA + k * 2048, 16, 1024, 1, 1>, Op<PM1 + (6 - (k & 6)) * 16, 0, 128, 0, 0>>(r, d0, d0); });
          wg_commit();
          sched_fence(budget);
          const uint32_t x0 = lds32v(ca), x1 = lds32v(ca + 1024), x2 = lds32v(ca + 2048), x3 = lds32v(ca + 3072);
          const bool bad = ((sp ? x0 | x1 | x2 | x3 : ~(x0 & x1 & x2 & x3)) & 1) && budget > 0;
          wg_wait<0>();
          pin<4>(r);
          sts16(sa, r[0]); sts16(sa + 4, r[2]);
          if (!nbar_or<NB_P, 128>(bad)) break;
          budget--;
          if (w == 0) { e_expect_tx(sb + B_PART, 16384); e_bulk_g2s(sb + WA, (const char*)g_part + blk * 16384, 16384, sb + B_PART); }
        }
        v = lds32v(sb + OM + w * 128 + lane * 4);
      }
      if (s == -1 || (s == LAG - 1 && (w & 1))) {
        const unsigned short* q = (const unsigned short*)mem0 + c * 2 * DM + blk * 16 + (w >> 1) * 8 + g;
        v = q[0] | (uint32_t)q[DM] << 16;
      }
      if (v == 0) v = 0x8000u;
      stg_rlx32(mw + sp * 32768, v);
      stg_rlx32(mw + (sp ^ 1) * 32768, 0);
      PROFW(1, 8);
    }
    if (ATT && w == 0) {
      LANE_NOW;
      uint32_t p[5];
      const float psum = softmax_row(hold, 8 * (g >> 1) + (g & 1) - 8 * c, p);
#pragma unroll
      for (int i = 0; i < 5; i++) hold[i] = __uint_as_float(p[i]);
      hold[5] = psum;
    }
    if (ATT && s >= 0) {
      const int seg = s - (rank ? LAG : 0);
      const bool act = (unsigned)seg < NSEG;
      LANE_NOW;
      uint32_t a[12];
#pragma unroll
      for (int i = 0; i < 12; i++) a[i] = __float_as_uint(hold[i < 10 ? i >> 1 : 4]) + ((uint32_t)budget >> (31 - (i & 3)));
      float o[32], inv, psum = hold[5];
      char* const ob = (char*)g_o[rank] + ((size_t)(seg * 32 + 8 * (g >> 1) + (g & 1) + 2 * w) * (NH * DH) + h * DH + c * 8) * 2;
      sfor<0, 2>([&](auto HF) {
        constexpr int hf = HF;
        wg_fence();
        wg_rs64<hf * 2, Op<QB + 8 * RG + hf * 1024, 2 * RG, 128, 0, 0>>(o, a, d0);
        wg_rs64<1, Op<QB + 12 * RG + hf * 1024, RG, 128, 0, 0>>(o, a + 4, d0);
        wg_rs64<1, Op<QB + 14 * RG + hf * 1024, 0, 128, 0, 0>>(o, a + 8, d0);
        wg_commit();
        if constexpr (hf == 0) {
          psum += __shfl_xor_sync(0xffffffffu, psum, 1);
          psum += __shfl_xor_sync(0xffffffffu, psum, 2);
          asm("rcp.approx.ftz.f32 %0, %1;" : "=f"(inv) : "f"(psum));
        }
        wg_wait<0>();
        pin<32>(o);
        if constexpr (hf == 1) { if (w < 3 && more) e_arrive_cl(mapa(sb + B_BFREE, w)); }
        if (act) {
#pragma unroll
          for (int i = 0; i < 2; i++)
            stg128(ob + (hf * 2 + i) * 64, pack_bf16(o[16*i] * inv, o[16*i+1] * inv), pack_bf16(o[16*i+4] * inv, o[16*i+5] * inv),
                   pack_bf16(o[16*i+8] * inv, o[16*i+9] * inv), pack_bf16(o[16*i+12] * inv, o[16*i+13] * inv));
        }
      });
      PROFW(0, 7);
      if (act && (seg & 3) == 3) {
        __syncwarp();
        e_flag_add(g_fl.o[rank][seg >> 2]);
      }
    } else if (!ATT && w == 3) {
      if (s + 4 < NSEG) e_prefetch(g_xn[0] + (size_t)((s + 4) * 32 + h) * DM, 2048);
    }
  }
  cluster_arrive(); cluster_wait();
  char* const pw = (char*)g_part + (size_t)((ATT ? rank + 1 : 0) * 16 + w * 4 + (lane0 >> 3)) * 4096 + h * 128 + (lane0 & 7) * 16;
#pragma unroll
  for (int j = 0; j < NT; j++) stg_rlx128(pw + j * (48 * 4096), 0, 0, 0, 0);
}

DEVI void rec_load(const uint32_t sb, const int h, const int rank, const int w, const CUtensorMap* mX) {
  using namespace rec;
  static_assert(((NSTEP - 1) & 31) != 1 && ((NSTEP - 2) & 31) != 2, "stale time stamps of the previous launch never match");
  const int lane0 = lane_reg(), mq = (w + 3) & 3;
  int budget = SPIN_BUDGET;
  cluster_arrive(); cluster_wait();
  if (w == 0) { if (lane0 < 4) mbar_arrive(sb + B_FULL + 8 * lane0); __syncwarp(); }
  uint32_t lph = 0;
#pragma unroll 1
  for (int s = -1; s < NSTEP - 1; s++) {
    if (w == 0) {
      const int sa = s + 1, sn = sa - LAG;
      if ((sa & 3) == 0 && sa < NSEG) flag_wait(g_fl.xn[0][sa >> 2], 32, budget);
      if ((sn & 3) == 0 && (unsigned)sn < NSEG) flag_wait(g_fl.xn[1][sn >> 2], 32, budget);
      int sl = 4, ph = 1;
#pragma unroll 1
      for (int i = 0; i < 16; i++) {
        mbar_wait(sb + B_EMPTY + 8 * sl, ph, budget);
        e_expect_tx(sb + B_FULL + 8 * sl, 8192);
        e_tma_3d(sb + RING + sl * 8192, mX, i * 64, (s + 1) * 32, sb + B_FULL + 8 * sl);
        if (++sl == 5) { sl = 0; ph ^= 1; }
      }
      nbar_arrive<NB_X, 128>();
    }
    uint32_t t = gtime();
    if (s >= 0) {
      uint2 a;
      if (w) nbar_sync<NB_G, 128>();
      do { a = ldg_rlx64(&g_ann[s & 1][h][lane0 * 2]); } while (__any_sync(0xffffffffu, ((a.x ^ (s + 1)) | (a.y ^ (s + 1))) & 31) && --budget > 0);
      t += __reduce_max_sync(0xffffffffu, max((int)(a.x - t), (int)(a.y - t)));
      t &= ~31u;
      PROFW(1, 12);
      if (w == 1 && rank < 2) {
        nbar_sync<NB_TR, 160>();
        wait_time(t + (rank ? TUN(1, 1800) : TUN(0, 1600)), budget);
        e_expect_tx(sb + B_PART, 16384);
        e_bulk_g2s(sb + WA, (const char*)g_part + (rank * 32 + h) * 16384, 16384, sb + B_PART);
        PROFW(1, 21);
      }
      t += mq == 0 ? TUN(2, 2750) : mq == 1 ? TUN(3, 2750) : mq == 2 ? TUN(4, 2950) : TUN(5, 2950);
    }
    if (w) nbar_sync<NB_X, 128>();
    mbar_wait(sb + B_EMPTY + 8 * mq, 1, budget);
    PROFW(1, 9);
    wait_time(t, budget);
    PROFW(1, 22); PROFW(3, 23);
    while (true) {
      e_expect_tx(sb + B_MLAND + 8 * mq, 8192);
      e_bulk_g2s(sb + RING + mq * 8192, (const char*)g_mem + (s & 1) * 32768 + mq * 8192, 8192, sb + B_MLAND + 8 * mq);
      const uint32_t a = sb + RING + mq * 8192 + lane0 * 32 + (lane0 >> 2) * 4;
      mbar_wait(sb + B_MLAND + 8 * mq, lph, budget);
      lph ^= 1;
      PROFW(1, 24);
      uint32_t mn = 0xffffffffu;
#pragma unroll
      for (int i = 0; i < 8; i++) mn = min(mn, lds32v(a + i * 1024));
      if (!__any_sync(0xffffffffu, mn == 0) || --budget <= 0) break;
    }
    e_arrive(sb + B_FULL + 8 * mq);
    PROFW(1, 10); PROFW(2, 13); PROFW(3, 14); PROFW(0, 15);
  }
}

struct RecMaps { CUtensorMap w[3], wo, x; };
__global__ void __cluster_dims__(3, 1, 1) __launch_bounds__(512, 1)
rec_kernel(const __grid_constant__ RecMaps M, const bf16* __restrict__ Wo, const bf16* __restrict__ mem0, uint32_t zero) {
  using namespace rec;
  extern __shared__ __align__(1024) uint8_t smem[];
  const uint32_t sb = smem_u32(smem);
  const int tid = threadIdx.x, warp = __shfl_sync(0xffffffffu, tid >> 5, 0), wg = warp >> 2, lane = tid & 31;
  const int h = blockIdx.x / 3, rank = blockIdx.x % 3;
  if (warp == 0) {
    if (lane < 20) mbar_init(sb + BARS + 8 * lane, (lane >= 5 && lane < 10) || lane == 19 ? 2 : 1);
    else if (lane < 23) mbar_init(sb + B_W1 + 8 * (lane - 20), 1);
    else if (lane == 23) mbar_init(sb + B_PART, 1);
    fence_mbar_init();
    __syncwarp();
    if (lane == 0) { mbar_expect_tx(sb + B_W1, (NSS + R1) * 4096); mbar_expect_tx(sb + B_QK, 20480); mbar_expect_tx(sb + B_V, 10240); mbar_expect_tx(sb + B_OM, 4096); }
    __syncwarp();
    for (int i = lane; i < 128; i += 32) {
      const int j = i >> 1, t = i & 1, r = reg_idx(j);
      if (is_ss(j)) tma_load_2d(sb + WS + (t * NSS + ss_before(j)) * 2048, &M.w[rank], h * DH + t * 64, j * 16, sb + B_W1);
      else if (r < R1) tma_load_2d(sb + WO + (t * R1 + r) * 2048, &M.w[rank], h * DH + t * 64, j * 16, sb + B_W1);
      else tma_prefetch_2d(&M.w[rank], h * DH + t * 64, j * 16);
    }
    const int t = 3 * (lane >> 1) + (rank + 1) % 3;
    if (t < 16) tma_prefetch_5d(&M.wo, t * 64, h * 4 + (lane & 1) * 2);
  } else if (warp == 1) {
    constexpr int N = (sizeof(Flags) - sizeof(g_fl.xn)) / 16;
    const int i = blockIdx.x * 16 + lane;
    if (lane < 16 && i < N) ((uint4*)g_fl.o)[i] = make_uint4(0, 0, 0, 0);
    static_assert(N <= 96 * 16, "flag reset");
    __threadfence();
    __syncwarp();
    asm volatile("griddepcontrol.launch_dependents;" ::: "memory");
  }
  __syncthreads();
  if (wg == 3) {
    reg_dec<24>();
    rec_load(sb, h, rank, warp & 3, &M.x);
    cluster_arrive(); cluster_wait();
  } else if (wg == 2) {
    reg_dec<72>();
    if (rank < 2) rec_attn<true>(sb, h, rank, warp & 3, &M.wo, Wo, mem0);
    else rec_attn<false>(sb, h, rank, warp & 3, &M.wo, Wo, mem0);
  } else {
    reg_inc<208>();
    rec_proj(sb, h, rank, warp, &M.w[rank], &M.wo, zero);
    cluster_arrive(); cluster_wait();
  }
}

namespace gm {
constexpr int STAGES = 6, STAGE_BYTES = 32768;
constexpr uint32_t SO = STAGES * STAGE_BYTES, B_FULL = SO + 32768, B_EMPTY = B_FULL + 64, B_JOB = B_FULL + 128, JOB = B_FULL + 144, SMEM = B_FULL + 192;
constexpr int T_O = 0, T_GU = 1, T_D = 2, T_END = 3, NJOB = 2 * 16 * 72;
#define G_FILL 3
struct JobList { uint16_t j[NJOB]; };
constexpr JobList make_jobs() {
  JobList L{};
  int n = 0, f = 0;
  auto add = [&](int t, int l, int c, int j0, int j1) { for (int j = j0; j < j1; j++) L.j[n++] = (uint16_t)(t << 11 | l << 10 | c << 6 | j); };
  for (int c = 0; c <= 16; c++) {
    if (c < 16) add(T_O, 0, c, 0, 8);
    if (c > 0) { add(T_GU, 0, c - 1, 0, 56); add(T_D, 0, c - 1, 0, 8); }
    for (int i = 0; i < G_FILL && f / 8 + (LAG + 3) / 4 + 1 <= c; i++, f++) add(T_O, 1, f / 8, f % 8, f % 8 + 1);
  }
  for (; f < 128; f++) add(T_O, 1, f / 8, f % 8, f % 8 + 1);
  for (int c = 0; c < 16; c++) add(T_GU, 1, c, 0, 56);
  for (int c = 0; c < 16; c++) add(T_D, 1, c, 0, 8);
  return L;
}
__device__ const JobList g_jobs = make_jobs();
struct Pipe { int s, ph; DEVI void next() { if (++s == STAGES) { s = 0; ph ^= 1; } } };
}
struct GemmMaps { CUtensorMap o, wo, x, x1, xm, wg, wu, h, wd, x2, out; };

DEVI float geglu(float g, float u) {
  const float z = g * (0.7978845608028654f + 0.035677408136300125f * g * g);
  float t; asm("tanh.approx.f32 %0, %1;" : "=f"(t) : "f"(z));
  const float hg = 0.5f * g;
  return fmaf(hg, t, hg) * u;
}
DEVI int h_wait(const int* p, int i, int& budget) {
  int n = 64;
  while ((n = (__ffs(~ld_acquire(p) & 0x88888888) >> 2) * 8 - 8) <= i && --budget > 0) __nanosleep(32);
  asm volatile("fence.proxy.async.global;" ::: "memory");
  return n;
}
DEVI void ln_rows(const bf16* src, bf16* dst, int lane) {
  uint4 u[2][4];
#pragma unroll
  for (int r = 0; r < 2; r++)
#pragma unroll
    for (int i = 0; i < 4; i++) u[r][i] = __ldcg((const uint4*)(src + r * DM) + i * 32 + lane);
#pragma unroll
  for (int r = 0; r < 2; r++) {
    uint32_t* x = (uint32_t*)u[r];
    float sum = 0;
#pragma unroll
    for (int i = 0; i < 16; i++) sum += bf_lo(x[i]) + bf_hi(x[i]);
#pragma unroll
    for (int o = 16; o; o >>= 1) sum += __shfl_xor_sync(0xffffffffu, sum, o);
    const float mean = sum * (1.f / DM);
    float q = 0;
#pragma unroll
    for (int i = 0; i < 16; i++) asm volatile("" : "+r"(x[i]));
#pragma unroll
    for (int i = 0; i < 16; i++) { const float a = bf_lo(x[i]) - mean, b = bf_hi(x[i]) - mean; q = fmaf(a, a, fmaf(b, b, q)); }
#pragma unroll
    for (int o = 16; o; o >>= 1) q += __shfl_xor_sync(0xffffffffu, q, o);
    const float rs = rsqrtf(q * (1.f / DM) + 1e-5f), mr = -mean * rs;
#pragma unroll
    for (int i = 0; i < 16; i++) asm volatile("" : "+r"(x[i]));
#pragma unroll
    for (int i = 0; i < 16; i++) x[i] = pack_bf16(fmaf(bf_lo(x[i]), rs, mr), fmaf(bf_hi(x[i]), rs, mr));
#pragma unroll
    for (int i = 0; i < 4; i++) ((uint4*)(dst + r * DM))[i * 32 + lane] = u[r][i];
  }
}
DEVI void ln_stream(int* ticket, const int* dep, const bf16* src, bf16* dst, int* done) {
  const int lane = threadIdx.x & 31;
  int budget = SPIN_BUDGET;
  while (true) {
    const int t = bcast(e_ticket(ticket));
    if (t >= 512) break;
    if (dep) flag_wait(dep + (t >> 5) * 32, 8, budget);
#pragma unroll 1
    for (int r = 0; r < 4; r += 2) ln_rows(src + (size_t)(t * 4 + r) * DM, dst + (size_t)(t * 4 + r) * DM, lane);
    __syncwarp();
    e_flag_add(done + (t >> 5) * 32);
  }
}

__global__ void __launch_bounds__(384, 1) gemm_kernel(const __grid_constant__ GemmMaps M, const bf16* __restrict__ x) {
  using namespace gm;
  extern __shared__ __align__(1024) uint8_t smem[];
  const uint32_t sb = smem_u32(smem);
  const int tid = threadIdx.x, wid = __shfl_sync(0xffffffffu, tid >> 5, 0), wg = wid >> 2, warp = wid & 3;
  int budget = SPIN_BUDGET;
  if (tid < 18) mbar_init(sb + B_FULL + 8 * tid, 1);
  fence_mbar_init();
  __syncthreads();
  if (wg == 2) {
    reg_dec<72>();
    if (warp == 0) {
      Pipe p; p.s = 0; p.ph = 1;
      int tk = e_ticket(g_fl.ticket);
      for (int n = 0; ; n++) {
        tk = bcast(tk);
        const int job = __shfl_sync(0xffffffffu, tk < NJOB ? g_jobs.j[tk] : T_END << 11, 0);
        const int ty = job >> 11, l = (job >> 10) & 1, cb = (job >> 6) & 15, j = job & 63, row = l * SEQ + cb * 128;
        mbar_wait(sb + B_EMPTY + 8 * p.s, p.ph, budget);
        if (budget <= 0) __trap();
        sts32v(sb + JOB + 4 * (n & 1), job | p.s << 16 | (p.ph ^ 1) << 20);
        e_arrive(sb + B_JOB + 8 * (n & 1));
        if (ty == T_END) break;
        const int nk = ty == T_O ? 64 : ty == T_GU ? 16 : 56;
        int rdy = 64;
        if (ty == T_D) rdy = h_wait(g_fl.h[l][cb], 0, budget);
        else flag_wait(ty == T_O ? g_fl.o[l][cb] : g_fl.xm[l][cb], ty == T_O ? 128 : 32, budget);
        if (ty != T_GU) {
          const uint32_t fb = sb + B_FULL + 8 * p.s, a = sb + p.s * STAGE_BYTES;
          const CUtensorMap* m = ty == T_D ? &M.x1 : l ? &M.x2 : &M.x;
          const int r = ty == T_D ? row : cb * 128;
          e_expect_tx(fb, STAGE_BYTES);
          e_tma_2d(a, m, j * 128, r, fb); e_tma_2d(a + 16384, m, j * 128 + 64, r, fb);
          p.next();
        }
        const CUtensorMap* const ma = ty == T_O ? &M.o : ty == T_GU ? &M.xm : &M.h;
        for (int i = 0; i < nk; i++) {
          if (i == nk - 4) tk = e_ticket(g_fl.ticket);
          const uint32_t fb = sb + B_FULL + 8 * p.s, a = sb + p.s * STAGE_BYTES, b = a + 16384;
          mbar_wait(sb + B_EMPTY + 8 * p.s, p.ph, budget);
          e_expect_tx(fb, STAGE_BYTES);
          if (ty == T_O) { e_tma_5d(b, &M.wo, j * 128, i * 2, fb); e_tma_5d(b + 8192, &M.wo, j * 128 + 64, i * 2, fb); }
          else if (ty == T_GU) { e_tma_2d(b, &M.wg, j * 64, i * 64, fb); e_tma_2d(b + 8192, &M.wu, j * 64, i * 64, fb); }
          else {
            e_tma_2d(b, &M.wd, j * 128, i * 64, fb); e_tma_2d(b + 8192, &M.wd, j * 128 + 64, i * 64, fb);
            if (i >= rdy) rdy = h_wait(g_fl.h[l][cb], i, budget);
          }
          e_tma_2d(a, ma, i * 64, row, fb);
          p.next();
        }
      }
    } else {
      const int ws = warp - 1;
#pragma unroll 1
      for (int i = ws; i < 3; i = i < 2 ? 2 : 3)
        ln_stream(g_fl.ticket + 32 + 8 * i, i == 1 ? g_fl.x2[0] : g_fl.x1[i >> 1][0], i == 1 ? g_x2 : g_x1[i >> 1],
                  i == 1 ? g_xn[1] + LAG * 32 * DM : g_xm[i >> 1], i == 1 ? g_fl.xn[1][0] : g_fl.xm[i >> 1][0]);
      if (blockIdx.x == 0 && ws == 2) {
        asm volatile("griddepcontrol.wait;" ::: "memory");
        g_fl.xn[(tid >> 4) & 1][tid & 15][0] = 0;
      }
    }
  } else {
    reg_inc<216>();
    ln_stream(g_fl.ticket + 56, nullptr, x, g_xn[0], g_fl.xn[0][0]);
    const int lane = lane_reg();
    const bool lead = warp == 0;
    const uint32_t so = sb + SO + wg * 16384;
    const int r0 = warp * 16 + (lane & 7) + ((lane >> 3) & 1) * 8;
    const uint32_t sw = r0 * 128 + (((lane >> 4) ^ (r0 & 7)) << 4);
    for (int n = wg; ; n += 2) {
      float d0[64], d1[64];
      mbar_wait(sb + B_JOB + 8 * wg, (n >> 1) & 1, budget);
      if (budget < 0) __trap();
      const int job = __shfl_sync(0xffffffffu, lds32v(sb + JOB + 4 * wg), 0);
      const int ty = (job >> 11) & 3, l = (job >> 10) & 1, cb = (job >> 6) & 15, j = job & 63;
      if (ty == T_END) {
        if (n > 0) nbar_sync_r(1 + wg, 256);
        if (lead && !(job & 1)) { sts32v(sb + JOB + 4 * (wg ^ 1), job | 1); e_arrive(sb + B_JOB + 8 * (wg ^ 1)); }
        if (!(job & 1)) nbar_arrive_r(1 + (wg ^ 1), 256);
        break;
      }
      Pipe q; q.s = (job >> 16) & 15; q.ph = job >> 20;
      if (ty != T_GU) {
        mbar_wait(sb + B_FULL + 8 * q.s, q.ph, budget);
#pragma unroll
        for (int m = 0; m < 2; m++)
#pragma unroll
          for (int c = 0; c < 8; c++) {
            float* d = (m ? d1 : d0) + 8 * c;
            uint32_t r[4];
            ldsm4(sb + q.s * STAGE_BYTES + (c >> 2) * 16384 + m * 8192 + (sw ^ ((c & 3) << 5)), r[0], r[1], r[2], r[3]);
#pragma unroll
            for (int i = 0; i < 4; i++) { d[2*i] = bf_lo(r[i]); d[2*i+1] = bf_hi(r[i]); }
          }
        fence_proxy_async();
        nbar_sync_r(3 + wg, 128);
        if (lead) e_arrive(sb + B_EMPTY + 8 * q.s);
        q.next();
      } else {
#pragma unroll
        for (int i = 0; i < 64; i++) d0[i] = d1[i] = 0.f;
      }
      pin<64>(d0); pin<64>(d1);
      if (n > 0) nbar_sync_r(1 + wg, 256);
      const int nk = ty == T_O ? 64 : ty == T_GU ? 16 : 56;
      int prev = 0;
      for (int i = 0; i < nk; i++) {
        mbar_wait(sb + B_FULL + 8 * q.s, q.ph, budget);
        const uint32_t da = desc_base(sb) + q.s * (STAGE_BYTES / 16);
        wg_fence();
        sfor<0, 4>([&](auto K) {
          constexpr int k = K;
          typedef Op<16384 + k * 2048, 8192, 1024, 1, 1> OB;
          wg_ss128<1, Op<k * 32, 16, 1024, 1, 0>, OB>(d0, da, da);
          wg_ss128<1, Op<8192 + k * 32, 16, 1024, 1, 0>, OB>(d1, da, da);
        });
        wg_commit();
        wg_wait<1>();
        arrive_if_eq(sb + B_EMPTY + 8 * prev, lane, i ? warp * 32 : -1);
        prev = q.s;
        q.next();
      }
      nbar_arrive_r(1 + (wg ^ 1), 256);
      wg_wait<0>();
      pin<64>(d0); pin<64>(d1);
      if (lead) e_arrive(sb + B_EMPTY + 8 * prev);
      if (ty == T_GU) {
#pragma unroll
        for (int m = 0; m < 2; m++)
#pragma unroll
          for (int c = 0; c < 4; c++) {
            const float* d = (m ? d1 : d0) + 8 * c;
            uint32_t r[4];
#pragma unroll
            for (int i = 0; i < 4; i++) r[i] = pack_bf16(geglu(d[2*i], d[32+2*i]), geglu(d[2*i+1], d[32+2*i+1]));
            stsm4(so + m * 8192 + (sw ^ (c << 5)), r[0], r[1], r[2], r[3]);
          }
        fence_proxy_async();
        nbar_sync_r(3 + wg, 128);
        if (lead) {
          e_tma_store_2d(&M.h, so, j * 64, l * SEQ + cb * 128);
          bulk_commit(); bulk_wait<0>();
          e_flag_add(g_fl.h[l][cb], 1 << ((j >> 3) * 4));
        }
      } else {
        const CUtensorMap* const mo = ty == T_O ? &M.x1 : l ? &M.out : &M.x2;
        const int row = (ty == T_O ? l * SEQ : 0) + cb * 128;
#pragma unroll
        for (int hf = 0; hf < 2; hf++) {
          if (hf) nbar_sync_r(3 + wg, 128);
#pragma unroll
          for (int m = 0; m < 2; m++)
#pragma unroll
            for (int c = 0; c < 4; c++) {
              const float* d = (m ? d1 : d0) + 32 * hf + 8 * c;
              stsm4(so + m * 8192 + (sw ^ (c << 5)), pack_bf16(d[0], d[1]), pack_bf16(d[2], d[3]), pack_bf16(d[4], d[5]), pack_bf16(d[6], d[7]));
            }
          fence_proxy_async();
          nbar_sync_r(3 + wg, 128);
          if (lead) {
            e_tma_store_2d(mo, so, j * 128 + hf * 64, row);
            bulk_commit();
            if (hf == 0) bulk_wait_read<0>();
            else {
              bulk_wait<0>();
              if (ty == T_O) e_flag_add(g_fl.x1[l][cb]); else if (l == 0) e_flag_add(g_fl.x2[cb]);
            }
          }
        }
      }
    }
  }
}

typedef CUresult (*PFN_encodeTiled)(CUtensorMap*, CUtensorMapDataType, cuuint32_t, void*, const cuuint64_t*, const cuuint64_t*,
                                    const cuuint32_t*, const cuuint32_t*, CUtensorMapInterleave, CUtensorMapSwizzle,
                                    CUtensorMapL2promotion, CUtensorMapFloatOOBfill);
static PFN_encodeTiled g_encode = nullptr;
static CUtensorMap encode(const void* ptr, int rank, const cuuint64_t* dims, const cuuint64_t* strides, const cuuint32_t* box) {
  CUtensorMap m;
  const cuuint32_t es[5] = {1, 1, 1, 1, 1};
  g_encode(&m, CU_TENSOR_MAP_DATA_TYPE_BFLOAT16, rank, (void*)ptr, dims, strides, box, es, CU_TENSOR_MAP_INTERLEAVE_NONE,
           CU_TENSOR_MAP_SWIZZLE_128B, CU_TENSOR_MAP_L2_PROMOTION_L2_256B, CU_TENSOR_MAP_FLOAT_OOB_FILL_NONE);
  return m;
}
static CUtensorMap make_map(const void* ptr, uint64_t rows, uint64_t cols, uint32_t box_rows) {
  const cuuint64_t dims[2] = {cols, rows}, strides[1] = {cols * 2};
  const cuuint32_t box[2] = {64, box_rows};
  return encode(ptr, 2, dims, strides, box);
}
static CUtensorMap make_map_x(const void* ptr) {
  const cuuint64_t dims[3] = {DM, NSTEP * 32, 2}, strides[2] = {DM * 2, (cuuint64_t)NSTEP * 32 * DM * 2};
  const cuuint32_t box[3] = {64, 32, 2};
  return encode(ptr, 3, dims, strides, box);
}
static CUtensorMap make_map_wo(const void* ptr) {
  const cuuint64_t dims[5] = {DM, 2, 4, 4, NH * DH / 32}, strides[4] = {DM * 2, 8 * DM * 2, 2 * DM * 2, 32 * DM * 2};
  const cuuint32_t box[5] = {64, 2, 4, 4, 2};
  return encode(ptr, 5, dims, strides, box);
}

extern "C" void kernel_launch(void* const* d_in, const int* in_sizes, int n_in, void* d_out, int out_size) {
  const bf16 *x = (const bf16*)d_in[0], *mem0 = (const bf16*)d_in[1], *Wo = (const bf16*)d_in[5];
  if (!g_encode) {
    void* p = nullptr; cudaDriverEntryPointQueryResult q;
    cudaGetDriverEntryPoint("cuTensorMapEncodeTiled", &p, cudaEnableDefault, &q);
    g_encode = (PFN_encodeTiled)p;
    cudaFuncSetAttribute(rec_kernel, cudaFuncAttributeMaxDynamicSharedMemorySize, rec::SMEM);
    cudaFuncSetAttribute(gemm_kernel, cudaFuncAttributeMaxDynamicSharedMemorySize, gm::SMEM);
  }
  void *xn, *o, *x1, *xm, *x2, *hh;
  cudaGetSymbolAddress(&xn, g_xn); cudaGetSymbolAddress(&o, g_o); cudaGetSymbolAddress(&x1, g_x1);
  cudaGetSymbolAddress(&xm, g_xm); cudaGetSymbolAddress(&x2, g_x2); cudaGetSymbolAddress(&hh, g_h);
  RecMaps R;
  for (int i = 0; i < 3; i++) R.w[i] = make_map(d_in[2 + i], DM, NH * DH, 16);
  R.wo = make_map_wo(Wo); R.x = make_map_x(xn);
  rec_kernel<<<96, 512, rec::SMEM>>>(R, Wo, mem0, 0);
  GemmMaps G;
  G.o = make_map(o, 2 * SEQ, NH * DH, 128); G.wo = R.wo; G.x = make_map(x, SEQ, DM, 128);
  G.x1 = make_map(x1, 2 * SEQ, DM, 128); G.xm = make_map(xm, 2 * SEQ, DM, 128);
  G.wg = make_map(d_in[8], DM, DF, 64); G.wu = make_map(d_in[9], DM, DF, 64); G.wd = make_map(d_in[10], DF, DM, 64);
  G.h = make_map(hh, 2 * SEQ, DF, 128); G.x2 = make_map(x2, SEQ, DM, 128); G.out = make_map(d_out, SEQ, DM, 128);
  cudaLaunchConfig_t cfg = {};
  cfg.gridDim = dim3(132); cfg.blockDim = dim3(384); cfg.dynamicSmemBytes = gm::SMEM; cfg.stream = cudaStreamPerThread;
  cudaLaunchAttribute at;
  at.id = cudaLaunchAttributeProgrammaticStreamSerialization; at.val.programmaticStreamSerializationAllowed = 1;
  cfg.attrs = &at; cfg.numAttrs = 1;
  cudaLaunchKernelEx(&cfg, gemm_kernel, G, x);
}
```

```cpp
#include <cuda_runtime.h>
#include <cuda_bf16.h>
#include <cuda.h>
#include <stdint.h>

#define DEVI __device__ __forceinline__
typedef __nv_bfloat16 bf16;

#define LAG 16
constexpr int SEQ = 2048, DM = 1024, NH = 32, DH = 128, DF = 3584, NSEG = 64, NSTEP = NSEG + LAG;
static_assert(NSTEP % 2 == 0, "tags and slots of the exchange buffers return to their initial state");

__device__ __align__(1024) bf16 g_xn[2][NSTEP * 32 * DM];
__device__ __align__(1024) bf16 g_o[2][SEQ * NH * DH];
__device__ __align__(1024) bf16 g_x1[2][SEQ * DM];
__device__ __align__(1024) bf16 g_xm[2][SEQ * DM];
__device__ __align__(1024) bf16 g_x2[SEQ * DM];
__device__ __align__(1024) bf16 g_h[2][SEQ * DF];
__device__ __align__(1024) uint4 g_part[256 * 32 * 8];
__device__ __align__(1024) uint32_t g_ann[2][32][64];
__device__ __align__(1024) uint4 g_mem[2][2048];
struct Flags {
  int xn[2][16][32];
  int o[2][16][32];
  int x1[2][16][32];
  int xm[2][16][32];
  int h[2][16][32];
  int x2[16][32];
  int ticket[64];
};
__device__ __align__(128) Flags g_fl;

DEVI uint32_t smem_u32(const void* p) { return (uint32_t)__cvta_generic_to_shared(p); }
DEVI void mbar_init(uint32_t bar, uint32_t cnt) { asm volatile("mbarrier.init.shared::cta.b64 [%0], %1;" :: "r"(bar), "r"(cnt) : "memory"); }
DEVI void mbar_expect_tx(uint32_t bar, uint32_t bytes) { asm volatile("mbarrier.arrive.expect_tx.shared::cta.b64 _, [%0], %1;" :: "r"(bar), "r"(bytes) : "memory"); }
DEVI void mbar_arrive(uint32_t bar) { asm volatile("mbarrier.arrive.shared::cta.b64 _, [%0];" :: "r"(bar) : "memory"); }
DEVI bool mbar_try(uint32_t bar, uint32_t parity) {
  uint32_t p;
  asm volatile("{.reg .pred p; mbarrier.try_wait.parity.shared::cta.b64 p, [%1], %2; selp.u32 %0, 1, 0, p;}" : "=r"(p) : "r"(bar), "r"(parity) : "memory");
  return p;
}
constexpr int SPIN_BUDGET = 1 << 20;
DEVI void mbar_wait(uint32_t bar, uint32_t parity, int& budget) {
  while (!mbar_try(bar, parity)) { if (--budget < 0) break; }
}
DEVI uint32_t mapa(uint32_t addr, uint32_t rank) { uint32_t r; asm("mapa.shared::cluster.u32 %0, %1, %2;" : "=r"(r) : "r"(addr), "r"(rank)); return r; }
DEVI void cluster_arrive() { asm volatile("barrier.cluster.arrive.release.aligned;" ::: "memory"); }
DEVI void cluster_wait() { asm volatile("barrier.cluster.wait.acquire.aligned;" ::: "memory"); }
DEVI void fence_mbar_init() { asm volatile("fence.mbarrier_init.release.cluster;" ::: "memory"); }
DEVI void fence_proxy_async() { asm volatile("fence.proxy.async.shared::cta;" ::: "memory"); }
DEVI void tma_load_2d(uint32_t dst, const CUtensorMap* m, int c0, int c1, uint32_t bar) {
  asm volatile("cp.async.bulk.tensor.2d.shared::cluster.global.mbarrier::complete_tx::bytes [%0], [%1, {%3, %4}], [%2];"
    :: "r"(dst), "l"(m), "r"(bar), "r"(c0), "r"(c1) : "memory");
}
DEVI void tma_load_5d(uint32_t dst, const CUtensorMap* m, int c0, int c4, uint32_t bar) {
  asm volatile("cp.async.bulk.tensor.5d.shared::cluster.global.mbarrier::complete_tx::bytes [%0], [%1, {%3, %5, %5, %5, %4}], [%2];"
    :: "r"(dst), "l"(m), "r"(bar), "r"(c0), "r"(c4), "r"(0) : "memory");
}
DEVI void tma_prefetch_2d(const CUtensorMap* m, int c0, int c1) {
  asm volatile("cp.async.bulk.prefetch.tensor.2d.L2.global [%0, {%1, %2}];" :: "l"(m), "r"(c0), "r"(c1) : "memory");
}
DEVI void tma_prefetch_5d(const CUtensorMap* m, int c0, int c4) {
  asm volatile("cp.async.bulk.prefetch.tensor.5d.L2.global [%0, {%1, %3, %3, %3, %2}];" :: "l"(m), "r"(c0), "r"(c4), "r"(0) : "memory");
}
#define ELECT "{.reg .pred p; elect.sync _|p, 0xffffffff;\n @p "
DEVI void e_expect_tx(uint32_t bar, uint32_t bytes) { asm volatile(ELECT "mbarrier.arrive.expect_tx.shared::cta.b64 _, [%0], %1;}" :: "r"(bar), "r"(bytes) : "memory"); }
DEVI void e_arrive(uint32_t bar) { asm volatile(ELECT "mbarrier.arrive.shared::cta.b64 _, [%0];}" :: "r"(bar) : "memory"); }
DEVI void e_arrive_cl(uint32_t bar) { asm volatile(ELECT "mbarrier.arrive.shared::cluster.b64 _, [%0];}" :: "r"(bar) : "memory"); }
DEVI void e_tma_2d(uint32_t dst, const CUtensorMap* m, int c0, int c1, uint32_t bar) {
  asm volatile(ELECT "cp.async.bulk.tensor.2d.shared::cluster.global.mbarrier::complete_tx::bytes [%0], [%1, {%3, %4}], [%2];}"
    :: "r"(dst), "l"(m), "r"(bar), "r"(c0), "r"(c1) : "memory");
}
DEVI void e_tma_store_2d(const CUtensorMap* m, uint32_t src, int c0, int c1) {
  asm volatile(ELECT "cp.async.bulk.tensor.2d.global.shared::cta.bulk_group [%0, {%2, %3}], [%1];}" :: "l"(m), "r"(src), "r"(c0), "r"(c1) : "memory");
}
DEVI void e_flag_add(int* p, int v = 1) {
  asm volatile("{.reg .pred p; elect.sync _|p, 0xffffffff;\n fence.proxy.async.global; @p red.release.gpu.global.add.s32 [%0], %1;}" :: "l"(p), "r"(v) : "memory");
}
DEVI int e_ticket(int* p) { int v = 0; asm volatile(ELECT "atom.relaxed.gpu.global.add.s32 %0, [%1], 1;}" : "+r"(v) : "l"(p) : "memory"); return v; }
DEVI int bcast(int v) { return __reduce_max_sync(0xffffffffu, v); }
DEVI int ld_acquire(const int* p) { int v; asm volatile("ld.acquire.gpu.global.s32 %0, [%1];" : "=r"(v) : "l"(p) : "memory"); return __shfl_sync(0xffffffffu, v, 0); }
DEVI void e_tma_3d(uint32_t dst, const CUtensorMap* m, int c0, int c1, uint32_t bar) {
  asm volatile(ELECT "cp.async.bulk.tensor.3d.shared::cluster.global.mbarrier::complete_tx::bytes [%0], [%1, {%3, %4, %5}], [%2];}"
    :: "r"(dst), "l"(m), "r"(bar), "r"(c0), "r"(c1), "r"(0) : "memory");
}
DEVI void e_tma_5d(uint32_t dst, const CUtensorMap* m, int c0, int c4, uint32_t bar) {
  asm volatile(ELECT "cp.async.bulk.tensor.5d.shared::cluster.global.mbarrier::complete_tx::bytes [%0], [%1, {%3, %5, %5, %5, %4}], [%2];}"
    :: "r"(dst), "l"(m), "r"(bar), "r"(c0), "r"(c4), "r"(0) : "memory");
}
DEVI void e_bulk_g2s(uint32_t dst, const void* src, uint32_t bytes, uint32_t bar) {
  asm volatile(ELECT "cp.async.bulk.shared::cluster.global.mbarrier::complete_tx::bytes [%0], [%1], %2, [%3];}" :: "r"(dst), "l"(src), "r"(bytes), "r"(bar) : "memory");
}
DEVI void e_prefetch(const void* src, uint32_t bytes) {
  asm volatile(ELECT "cp.async.bulk.prefetch.L2.global [%0], %1;}" :: "l"(src), "r"(bytes) : "memory");
}
DEVI void bulk_commit() { asm volatile("cp.async.bulk.commit_group;" ::: "memory"); }
template<int N> DEVI void bulk_wait_read() { asm volatile("cp.async.bulk.wait_group.read %0;" :: "n"(N) : "memory"); }
template<int N> DEVI void bulk_wait() { asm volatile("cp.async.bulk.wait_group %0;" :: "n"(N) : "memory"); }
template<int ID, int N> DEVI void nbar_sync() { asm volatile("bar.sync %0, %1;" :: "n"(ID), "n"(N) : "memory"); }
template<int ID, int N> DEVI void nbar_arrive() { asm volatile("bar.arrive %0, %1;" :: "n"(ID), "n"(N) : "memory"); }
DEVI void nbar_sync_r(int id, int n) { asm volatile("bar.sync %0, %1;" :: "r"(id), "r"(n) : "memory"); }
DEVI void nbar_arrive_r(int id, int n) { asm volatile("bar.arrive %0, %1;" :: "r"(id), "r"(n) : "memory"); }
template<int R> DEVI void reg_inc() { asm volatile("setmaxnreg.inc.sync.aligned.u32 %0;" :: "n"(R)); }
template<int R> DEVI void reg_dec() { asm volatile("setmaxnreg.dec.sync.aligned.u32 %0;" :: "n"(R)); }
DEVI void wg_fence() { asm volatile("wgmma.fence.sync.aligned;" ::: "memory"); }
DEVI void wg_commit() { asm volatile("wgmma.commit_group.sync.aligned;" ::: "memory"); }
template<int N> DEVI void wg_wait() { asm volatile("wgmma.wait_group.sync.aligned %0;" :: "n"(N) : "memory"); }
DEVI uint32_t pack_bf16(float lo, float hi) { uint32_t r; asm("cvt.rn.bf16x2.f32 %0, %1, %2;" : "=r"(r) : "f"(hi), "f"(lo)); return r; }
DEVI float bf_lo(uint32_t v) { return __uint_as_float(v << 16); }
DEVI float bf_hi(uint32_t v) { return __uint_as_float(v & 0xffff0000u); }
DEVI uint32_t movmat(uint32_t a) { uint32_t r; asm volatile("movmatrix.sync.aligned.m8n8.trans.b16 %0, %1;" : "=r"(r) : "r"(a)); return r; }
DEVI void ldsm4(uint32_t addr, uint32_t& r0, uint32_t& r1, uint32_t& r2, uint32_t& r3) {
  asm volatile("ldmatrix.sync.aligned.m8n8.x4.shared.b16 {%0,%1,%2,%3}, [%4];" : "=r"(r0), "=r"(r1), "=r"(r2), "=r"(r3) : "r"(addr) : "memory");
}
DEVI void ldsm4t(uint32_t addr, uint32_t& r0, uint32_t& r1, uint32_t& r2, uint32_t& r3) {
  asm volatile("ldmatrix.sync.aligned.m8n8.x4.trans.shared.b16 {%0,%1,%2,%3}, [%4];" : "=r"(r0), "=r"(r1), "=r"(r2), "=r"(r3) : "r"(addr) : "memory");
}
DEVI void stsm4(uint32_t addr, uint32_t r0, uint32_t r1, uint32_t r2, uint32_t r3) {
  asm volatile("stmatrix.sync.aligned.m8n8.x4.shared.b16 [%0], {%1,%2,%3,%4};" :: "r"(addr), "r"(r0), "r"(r1), "r"(r2), "r"(r3) : "memory");
}
DEVI uint32_t lds32v(uint32_t a) { uint32_t v; asm volatile("ld.volatile.shared.u32 %0, [%1];" : "=r"(v) : "r"(a) : "memory"); return v; }
DEVI void sts32v(uint32_t a, uint32_t v) { asm volatile("st.volatile.shared.u32 [%0], %1;" :: "r"(a), "r"(v) : "memory"); }
DEVI void st_async128(uint32_t a, uint32_t x, uint32_t y, uint32_t z, uint32_t w, uint32_t bar) {
  asm volatile("st.async.weak.shared::cluster.mbarrier::complete_tx::bytes.v4.b32 [%0], {%1,%2,%3,%4}, [%5];" :: "r"(a), "r"(x), "r"(y), "r"(z), "r"(w), "r"(bar) : "memory");
}
DEVI void st_async32(uint32_t a, uint32_t x, uint32_t bar) {
  asm volatile("st.async.weak.shared::cluster.mbarrier::complete_tx::bytes.b32 [%0], %1, [%2];" :: "r"(a), "r"(x), "r"(bar) : "memory");
}
DEVI void st_cl128(bool own, uint32_t a, uint32_t x, uint32_t y, uint32_t z, uint32_t w, uint32_t bar) {
  asm volatile("{.reg .pred p; setp.ne.u32 p, %6, 0; @p st.shared.v4.b32 [%0], {%1,%2,%3,%4};\n"
               "@!p st.async.weak.shared::cluster.mbarrier::complete_tx::bytes.v4.b32 [%0], {%1,%2,%3,%4}, [%5];}"
               :: "r"(a), "r"(x), "r"(y), "r"(z), "r"(w), "r"(bar), "r"((uint32_t)own) : "memory");
}
DEVI void st_cl32(bool own, uint32_t a, uint32_t x, uint32_t bar) {
  asm volatile("{.reg .pred p; setp.ne.u32 p, %3, 0; @p st.shared.b32 [%0], %1;\n"
               "@!p st.async.weak.shared::cluster.mbarrier::complete_tx::bytes.b32 [%0], %1, [%2];}" :: "r"(a), "r"(x), "r"(bar), "r"((uint32_t)own) : "memory");
}
DEVI uint4 ldg_rlx128(const void* p) {
  uint4 v;
  asm volatile("ld.relaxed.gpu.global.v4.b32 {%0,%1,%2,%3}, [%4];" : "=r"(v.x), "=r"(v.y), "=r"(v.z), "=r"(v.w) : "l"(p) : "memory");
  return v;
}
DEVI void stg_rlx128(void* p, uint32_t x, uint32_t y, uint32_t z, uint32_t w) {
  asm volatile("st.relaxed.gpu.global.v4.b32 [%0], {%1,%2,%3,%4};" :: "l"(p), "r"(x), "r"(y), "r"(z), "r"(w) : "memory");
}
DEVI void stg128(void* p, uint32_t x, uint32_t y, uint32_t z, uint32_t w) {
  asm volatile("st.global.v4.b32 [%0], {%1,%2,%3,%4};" :: "l"(p), "r"(x), "r"(y), "r"(z), "r"(w) : "memory");
}
DEVI void stg_rlx32(void* p, uint32_t x) { asm volatile("st.relaxed.gpu.global.b32 [%0], %1;" :: "l"(p), "r"(x) : "memory"); }
DEVI uint32_t clock32() { uint32_t c; asm volatile("mov.u32 %0, %%clock;" : "=r"(c) :: "memory"); return c; }
DEVI uint32_t gtime() { uint32_t c; asm volatile("mov.u32 %0, %%globaltimer_lo;" : "=r"(c) :: "memory"); return c; }
DEVI void wait_time(uint32_t t, int& budget) { while ((int)(gtime() - t) < 0 && --budget > 0) {} }
DEVI uint2 ldg_rlx64(const void* p) { uint2 v; asm volatile("ld.relaxed.gpu.global.v2.b32 {%0,%1}, [%2];" : "=r"(v.x), "=r"(v.y) : "l"(p) : "memory"); return v; }
DEVI void sts16(uint32_t a, uint32_t x) { asm volatile("st.shared.b16 [%0], %1;" :: "r"(a), "h"((unsigned short)x) : "memory"); }
DEVI void sts128(uint32_t a, uint32_t x) { asm volatile("st.shared.v4.b32 [%0], {%1,%1,%1,%1};" :: "r"(a), "r"(x) : "memory"); }
DEVI void arrive_if_eq(uint32_t bar, int a, int b) { asm volatile("{.reg .pred p; setp.eq.s32 p, %1, %2; @p mbarrier.arrive.shared::cta.b64 _, [%0];}" :: "r"(bar), "r"(a), "r"(b) : "memory"); }
template<int ID, int N> DEVI bool nbar_or(bool x) {
  uint32_t r;
  asm volatile("{.reg .pred p, q; setp.ne.u32 p, %1, 0; bar.red.or.pred q, %2, %3, p; selp.u32 %0, 1, 0, q;}" : "=r"(r) : "r"((uint32_t)x), "n"(ID), "n"(N) : "memory");
  return __any_sync(0xffffffffu, r);
}
DEVI void spin_until(uint32_t t0, int d) { while ((int)(clock32() - t0) < d) {} }
DEVI void flag_wait(const int* p, int n, int& budget) {
  while (ld_acquire(p) < n && --budget > 0) __nanosleep(32);
  asm volatile("fence.proxy.async.global;" ::: "memory");
}

#define F4(C, o)  C(d[o+0]), C(d[o+1]), C(d[o+2]), C(d[o+3])
#define F8(C, o)  F4(C, o), F4(C, o+4)
#define F32(C, o) F8(C, o), F8(C, o+8), F8(C, o+16), F8(C, o+24)
#define R4  "{%0,%1,%2,%3}"
#define R8  "{%0,%1,%2,%3,%4,%5,%6,%7}"
#define R20 "{%0,%1,%2,%3,%4,%5,%6,%7,%8,%9,%10,%11,%12,%13,%14,%15,%16,%17,%18,%19}"
#define R32 "{%0,%1,%2,%3,%4,%5,%6,%7,%8,%9,%10,%11,%12,%13,%14,%15,%16,%17,%18,%19,%20,%21,%22,%23,%24,%25,%26,%27,%28,%29,%30,%31}"
#define R64 "{%0,%1,%2,%3,%4,%5,%6,%7,%8,%9,%10,%11,%12,%13,%14,%15,%16,%17,%18,%19,%20,%21,%22,%23,%24,%25,%26,%27,%28,%29,%30,%31," \
  "%32,%33,%34,%35,%36,%37,%38,%39,%40,%41,%42,%43,%44,%45,%46,%47,%48,%49,%50,%51,%52,%53,%54,%55,%56,%57,%58,%59,%60,%61,%62,%63}"
template<uint32_t OFF, uint32_t LBO, uint32_t SBO, uint32_t SW, int T> struct Op {
  static constexpr uint32_t lo = (OFF >> 4) | ((LBO >> 4) << 16), hi = (SBO >> 4) | (SW << 30);
  static constexpr int t = T;
};
DEVI uint32_t desc_base(uint32_t addr) { return (addr & 0x3FFFF) >> 4; }
#define RS_ASM(SHAPE, REGS, A0, A1, A2, A3, B, LO, HI, T, SD) \
  "{.reg .b64 tb; .reg .b32 lb; add.u32 lb, " B ", " LO "; mov.b64 tb, {lb, " HI "};\n" \
  "wgmma.mma_async.sync.aligned." SHAPE ".f32.bf16.bf16 " REGS ", {" A0 "," A1 "," A2 "," A3 "}, tb, " SD ", 1, 1, " T ";}"
#define WG_RS(NAME, SHAPE, REGS, LIST, ...) \
  template<int ACC, class OB> DEVI void NAME(float* d, const uint32_t* a, uint32_t b) { \
    if (ACC) asm volatile(RS_ASM(SHAPE, REGS, __VA_ARGS__) \
      : LIST("+f") : "r"(a[0]), "r"(a[1]), "r"(a[2]), "r"(a[3]), "r"(b), "n"(OB::lo), "n"(OB::hi), "n"(OB::t), "n"(ACC & 1)); \
    else asm volatile(RS_ASM(SHAPE, REGS, __VA_ARGS__) \
      : LIST("=f") : "r"(a[0]), "r"(a[1]), "r"(a[2]), "r"(a[3]), "r"(b), "n"(OB::lo), "n"(OB::hi), "n"(OB::t), "n"(0)); \
  }
#define SS_ASM(SHAPE, REGS, A, B, LA, HA, TA, LB, HB, TB, SD) \
  "{.reg .b64 ta, tb; .reg .b32 la, lb; add.u32 la, " A ", " LA "; mov.b64 ta, {la, " HA "}; add.u32 lb, " B ", " LB "; mov.b64 tb, {lb, " HB "};\n" \
  "wgmma.mma_async.sync.aligned." SHAPE ".f32.bf16.bf16 " REGS ", ta, tb, " SD ", 1, 1, " TA ", " TB ";}"
#define WG_SS(NAME, SHAPE, REGS, LIST, ...) \
  template<int ACC, class OA, class OB> DEVI void NAME(float* d, uint32_t a, uint32_t b) { \
    if (ACC) asm volatile(SS_ASM(SHAPE, REGS, __VA_ARGS__) \
      : LIST("+f") : "r"(a), "r"(b), "n"(OA::lo), "n"(OA::hi), "n"(OA::t), "n"(OB::lo), "n"(OB::hi), "n"(OB::t), "n"(ACC & 1)); \
    else asm volatile(SS_ASM(SHAPE, REGS, __VA_ARGS__) \
      : LIST("=f") : "r"(a), "r"(b), "n"(OA::lo), "n"(OA::hi), "n"(OA::t), "n"(OB::lo), "n"(OB::hi), "n"(OB::t), "n"(0)); \
  }
#define L4(C)  F4(C, 0)
#define L8(C)  F8(C, 0)
#define L20(C) F8(C, 0), F8(C, 8), F4(C, 16)
#define L32(C) F32(C, 0)
WG_RS(wg_rs8, "m64n8k16", R4, L4, "%4", "%5", "%6", "%7", "%8", "%9", "%10", "%11", "%12")
WG_RS(wg_rs16, "m64n16k16", R8, L8, "%8", "%9", "%10", "%11", "%12", "%13", "%14", "%15", "%16")
WG_RS(wg_rs64, "m64n64k16", R32, L32, "%32", "%33", "%34", "%35", "%36", "%37", "%38", "%39", "%40")
WG_SS(wg_ss8, "m64n8k16", R4, L4, "%4", "%5", "%6", "%7", "%8", "%9", "%10", "%11", "%12")
WG_SS(wg_ss16, "m64n16k16", R8, L8, "%8", "%9", "%10", "%11", "%12", "%13", "%14", "%15", "%16")
WG_SS(wg_ss40, "m64n40k16", R20, L20, "%20", "%21", "%22", "%23", "%24", "%25", "%26", "%27", "%28")
WG_SS(wg_ss64, "m64n64k16", R32, L32, "%32", "%33", "%34", "%35", "%36", "%37", "%38", "%39", "%40")
#define L64(C) F32(C, 0), F32(C, 32)
WG_SS(wg_ss128, "m64n128k16", R64, L64, "%64", "%65", "%66", "%67", "%68", "%69", "%70", "%71", "%72")
template<int I> struct IC { __host__ __device__ constexpr operator int() const { return I; } };
template<int I, int N, class F> DEVI void sfor(F&& f) {
  if constexpr (I < N) { f(IC<I>{}); sfor<I + 1, N>(f); }
}

namespace rec {
constexpr int NHI = 36, NLO = 5, NRS = NHI + NLO, NSS = 64 - NRS;
constexpr uint32_t WS = 0;
constexpr uint32_t WO = 2 * NSS * 2048;
constexpr uint32_t RING = WO + 65536;
constexpr uint32_t QB = RING + 40960, RG = 2080, POSQ = 0x64210, POSK = 0xB9753, POSV = 0xEDCA8;
#define JA 2
constexpr uint32_t WA = QB;
constexpr uint32_t OM = QB + 9 * RG, OMS = 2 * RG;
constexpr uint32_t OM2 = QB + 16384, OM2S = 2048;
constexpr uint32_t WH = QB + 20480;
constexpr uint32_t B_PART = QB + 15 * RG - 32;
constexpr uint32_t PM0 = QB + 16384, PM1 = QB + 15 * RG, PM2 = PM1 + 256;
constexpr uint32_t BARS = PM2 + 128;
constexpr uint32_t B_FULL = BARS, B_EMPTY = BARS + 40, B_MLAND = BARS + 80, B_QK = BARS + 112, B_V = BARS + 120, B_OM = BARS + 128,
                   B_WA = BARS + 136, B_SDONE = BARS + 144, B_BFREE = BARS + 152, B_W1 = PM1, B_W2 = PM1 + 8, B_WO = PM1 + 16;
constexpr uint32_t SMEM = BARS + 160;
static_assert(SMEM <= 232448 && QB % 1024 == 0, "smem map");
constexpr int R1 = (PM1 - WO) / 4096;
constexpr int NB_WO = 1, NB_ST = 2, NB_P = 3, NB_TR = 4, NB_X = 5, NB_G = 6, NB_G1 = 7, NB_G2 = 8, NB_G4 = 9, NB_S = 10;
__host__ __device__ constexpr bool is_lo(int j) { return j % 12 == 8; }
__host__ __device__ constexpr int lo_before(int j) { return (j + 3) / 12; }
__host__ __device__ constexpr int ss_before(int j) { return (j - lo_before(j)) * NSS / (64 - NLO); }
__host__ __device__ constexpr bool is_ss(int j) { return ss_before(j + 1) != ss_before(j); }
__host__ __device__ constexpr int reg_idx(int j) { return is_lo(j) ? NHI + lo_before(j) : j - ss_before(j) - lo_before(j); }
#define LOQ(i) ((0x12010 >> (4 * (i))) & 3)
template<int j> using OpW = Op<WS + ss_before(j) * 2048, 16, 1024, 1, 1>;
#define P_G1 1
#define P_G2 2
#define P_G2L 0
#define P_OS 1
#define P_NA 4
#define P_G4 10
#define P_G5 11
#define TUN(i, v) (v)
}
#define PROFW(wq, i)
template<int N> DEVI void pin(float* d) {
#pragma unroll
  for (int i = 0; i < N; i++) asm volatile("" : "+f"(d[i]) :: "memory");
}
DEVI void keep(const void* a) { asm volatile("{.reg .pred p; setp.eq.u64 p, %0, 0; vote.sync.any.pred p, p, 0xffffffff; @p exit;}" :: "l"(a) : "memory"); }
DEVI int lane_reg() { return __shfl_sync(0xffffffffu, threadIdx.x & 31, threadIdx.x & 31); }
#define LANE_NOW [[maybe_unused]] const int lane = lane0 + ((uint32_t)budget >> 30), g = lane >> 2, c = lane & 3

DEVI void rec_proj(const uint32_t sb, const int h, const int rank, const int w, const CUtensorMap* mW, const CUtensorMap* mWo, const uint32_t zero) {
  using namespace rec;
  const int lane0 = lane_reg(), wg = w >> 2, ww = w & 3;
  int budget = SPIN_BUDGET;
  uint32_t wr[NRS * 4];
  {
    LANE_NOW;
    const uint32_t wsw = ((lane & 7) + (lane >> 4) * 8) * 128 + (((ww * 2 + ((lane >> 3) & 1)) ^ (lane & 7)) << 4);
    mbar_wait(sb + B_W1, 0, budget);
#pragma unroll
    for (int r = 0; r < R1; r++) ldsm4t(sb + WO + (wg * R1 + r) * 2048 + wsw, wr[4*r], wr[4*r+1], wr[4*r+2], wr[4*r+3]);
    fence_proxy_async();
    nbar_sync<NB_ST, 256>();
    if (w == 0) {
      if (lane == 0) { mbar_expect_tx(sb + B_W2, (NRS - R1) * 4096); mbar_expect_tx(sb + B_WO, rank == 2 ? 65536 + 16384 + 8192 : 65536); }
      __syncwarp();
      for (int i = lane; i < 128; i += 32) {
        const int j = i & 63, t = i >> 6, r = reg_idx(j);
        if (!is_ss(j) && r >= R1) tma_load_2d(sb + RING + (t * (NRS - R1) + r - R1) * 2048, mW, h * DH + t * 64, j * 16, sb + B_W2);
      }
      const int t0 = (rank + 1) % 3;
      if (lane < 8) tma_load_2d(sb + WO + lane * 8192, mWo, (3 * ((lane >> 1) + (lane >> 1 >= JA)) + t0) * 64, h * DH + (lane & 1) * 64, sb + B_WO);
      else if (rank == 2 && lane < 11) tma_load_2d(lane < 10 ? sb + WA + (lane - 8) * 8192 : sb + WH, mWo, lane < 10 ? 3 * JA * 64 : 15 * 64, h * DH + (lane > 8) * 64, sb + B_WO);
    }
    mbar_wait(sb + B_W2, 0, budget);
#pragma unroll
    for (int r = R1; r < NRS; r++) ldsm4t(sb + RING + (wg * (NRS - R1) + r - R1) * 2048 + wsw, wr[4*r], wr[4*r+1], wr[4*r+2], wr[4*r+3]);
    fence_proxy_async();
    cluster_arrive(); cluster_wait();
  }
  const uint32_t d0 = desc_base(sb), da = d0 + wg * (NSS * 128);
  const uint32_t pos = rank == 0 ? POSQ : rank == 1 ? POSK : POSV, bar = rank == 2 ? B_V : B_QK;
  uint32_t stg[3][4] = {}, pk[16] = {};
  auto stage = [&](uint32_t* t, int r) {
#pragma unroll
    for (int i = 0; i < 4; i++) asm volatile("xor.b32 %0, %1, %2;" : "+r"(t[i]) : "r"(wr[4 * r + i]), "r"(zero));
  };
#pragma unroll 1
  for (int s = -1; s < NSTEP; s++) {
    if (s >= 0) {
      float d[8];
      sfor<0, 4>([&](auto Q) {
        constexpr int q = Q;
        sfor<lo_before(16 * q), lo_before(16 * q + 16)>([&](auto I) { constexpr int i = I; stage(stg[LOQ(i)], NHI + i); });
        mbar_wait(sb + B_FULL + 8 * q, 0, budget);
        if (q == 0) PROFW(0, 16);
        wg_fence();
        sfor<16 * q, 16 * q + 16>([&](auto J) {
          constexpr int j = J;
          typedef Op<RING + j * 512, 256, 128, 0, 1> OB;
          if constexpr (is_ss(j)) wg_ss16<j != 0, OpW<j>, OB>(d, da, d0);
          else wg_rs16<j != 0, OB>(d, is_lo(j) ? stg[LOQ(lo_before(j))] : wr + 4 * reg_idx(j), d0);
        });
        wg_commit();
        if (q == 0 && s > 0) mbar_wait(sb + B_BFREE, (s & 1) ^ 1, budget);
        sfor<q ? q + 1 : 0, q < 3 ? q + 2 : 0>([&](auto N) {
          constexpr int n = N;
          LANE_NOW;
          const uint32_t r = mapa(sb, n >> 1);
          uint32_t t[4];
#pragma unroll
          for (int i = 0; i < 4; i++) { if (n == 0) t[i] = pk[i]; else asm volatile("xor.b32 %0, %1, %2;" : "=r"(t[i]) : "r"(pk[4*n+i]), "r"(zero)); }
          st_cl128(rank == n >> 1, r + QB + ((pos >> (4 + 4 * c)) & 15) * RG + w * 256 + (n & 1) * 128 + g * 16, t[0], t[1], t[2], t[3], r + bar);
        });
        if constexpr (q > 0) {
          wg_wait<1>();
          arrive_if_eq(sb + B_EMPTY + 8 * (q - 1), lane0, ww * 32);
        }
      });
      LANE_NOW;
      const uint32_t dst = QB + (pos & 15) * RG + w * 256 + lane * 4;
      wg_wait<0>();
      pin<8>(d);
      {
        const uint32_t x0 = pack_bf16(d[0], d[1]), x1 = pack_bf16(d[2], d[3]), y0 = pack_bf16(d[4], d[5]), y1 = pack_bf16(d[6], d[7]);
        const uint32_t r = mapa(sb, rank == 0);
        if (rank < 2) { sts32v(sb + dst, rank ? y0 : x0); sts32v(sb + dst + 128, rank ? y1 : x1); fence_proxy_async(); }
        st_async32(r + dst, rank ? x0 : y0, r + bar); st_async32(r + dst + 128, rank ? x1 : y1, r + bar);
        if (rank < 2) e_arrive(sb + B_QK);
        else { const uint32_t r1 = mapa(sb, 1); st_async32(r1 + dst, y0, r1 + bar); st_async32(r1 + dst + 128, y1, r1 + bar); }
      }
      PROFW(0, 17);
      if (s == NSTEP - 1) break;
      arrive_if_eq(sb + B_EMPTY + 24, lane0, ww * 32);
    } else e_arrive(sb + B_EMPTY + 8 * ww);
    float d[32];
    const bool gate = rank < 2 && s >= 0;
    sfor<0, 16>([&](auto C) {
      constexpr int cc = C, sl = (cc + 4) % 5;
      if constexpr (cc == 0) mbar_wait(sb + B_FULL + 8 * sl, 0, budget);
      if constexpr (cc == P_G1) { if (gate) nbar_sync<NB_G1, 384>(); }
      if constexpr (cc == P_G2) { if (gate) nbar_sync<NB_G2, 384>(); }
      if constexpr (cc == P_NA) {
        PROFW(0, 18);
        nbar_sync<NB_WO, 384>();
      }
      if constexpr (cc == P_G4 || cc == P_G5) { if (gate && cc == (rank ? P_G5 : P_G4)) nbar_sync<NB_G4, 384>(); }
      wg_fence();
      sfor<0, 4>([&](auto I) {
        constexpr int i = I, j = cc * 4 + i;
        typedef Op<RING + sl * 8192 + i * 32, 16, 1024, 1, 0> OB;
        if constexpr (is_ss(j)) wg_ss64<j != 0, OpW<j>, OB>(d, da, d0);
        else wg_rs64<j != 0, OB>(d, is_lo(j) ? stg[0] : wr + 4 * reg_idx(j), d0);
      });
      wg_commit();
      if constexpr (cc == P_NA) PROFW(0, 19);
      if constexpr (cc < 15) {
        if constexpr (is_lo(cc * 4 + 4)) stage(stg[0], reg_idx(cc * 4 + 4));
        mbar_wait(sb + B_FULL + 8 * ((sl + 1) % 5), ((cc + 5) / 5) & 1, budget);
      }
      wg_wait<0>();
      arrive_if_eq(sb + B_EMPTY + 8 * sl, lane0, ww * 32);
    });
    pin<32>(d);
    PROFW(0, 20);
#pragma unroll
    for (int i = 0; i < 16; i++) pk[i] = pack_bf16(d[16 * (i >> 3) + 4 * (i & 3) + ((i >> 1) & 2)], d[16 * (i >> 3) + 4 * (i & 3) + ((i >> 1) & 2) + 1]);
  }
}

DEVI float softmax_row(float* v, uint32_t* p) {
  constexpr float SC = 0.08838834764831845f * 1.4426950408889634f;
  float m = fmaxf(fmaxf(fmaxf(fmaxf(v[0], v[1]), fmaxf(v[2], v[3])), fmaxf(fmaxf(v[4], v[5]), fmaxf(v[6], v[7]))), fmaxf(v[8], v[9]));
  m = fmaxf(m, __shfl_xor_sync(0xffffffffu, m, 1));
  m = fmaxf(m, __shfl_xor_sync(0xffffffffu, m, 2));
  const float ms = -m * SC, mh = fmaf(m, -SC, -1.f);
#pragma unroll
  for (int i = 0; i < 10; i++) asm("ex2.approx.ftz.f32 %0, %1;" : "=f"(v[i]) : "f"(fmaf(v[i], SC, i < 8 ? ms : mh)));
#pragma unroll
  for (int n = 0; n < 5; n++) p[n] = pack_bf16(v[2*n], v[2*n+1]);
  return fmaf(v[8] + v[9], 2.f, ((v[0] + v[1]) + (v[2] + v[3])) + ((v[4] + v[5]) + (v[6] + v[7])));
}

template<bool ATT>
DEVI void rec_attn(const uint32_t sb, int h, int rank, int w, const bf16* __restrict__ Wo, const bf16* __restrict__ mem0) {
  using namespace rec;
  const int lane0 = lane_reg();
  int budget = SPIN_BUDGET;
  constexpr int NT = ATT ? 5 : 6;
  uint32_t wl[16];
  if (!ATT) {
    LANE_NOW;
#pragma unroll
    for (int i = 0; i < 16; i++) {
      const int dh = 8 * (i >> 1) + 2 * c;
      const unsigned short* p = (const unsigned short*)Wo + (size_t)(h * DH + dh) * DM + 15 * 64 + 16 * w + 8 * (i & 1) + g;
      wl[i] = p[0] | (uint32_t)p[DM] << 16;
    }
  }
  mbar_wait(sb + B_WO, 0, budget);
  cluster_arrive(); cluster_wait();
  const uint32_t d0 = desc_base(sb);
  uint32_t pph = 0;
#pragma unroll 1
  for (int s = -1; s < NSTEP; s++) {
    asm volatile("" : "+r"(h), "+r"(rank), "+r"(w));
    const uint32_t sp = s & 1;
    const int t0 = ATT ? rank + 1 : 0;
    const bool more = s + 1 < NSTEP;
    float hold[10] = {0, 0, 0, 0, 0, 0, 0, 0, 0, 0};
    if (ATT && s >= 0) {
      float sc[20];
      LANE_NOW;
      mbar_wait(sb + B_QK, sp, budget);
      PROFW(0, 1);
      fence_proxy_async();
      wg_fence();
      sfor<0, 8>([&](auto K) { constexpr int k = K; wg_ss40<k != 0, Op<QB + k * 256, 128, RG, 0, 1>, Op<QB + 3 * RG + k * 256, 128, 2 * RG, 0, 1>>(sc, d0, d0); });
      wg_commit();
      if (P_G1 < 16 && more) nbar_arrive<NB_G1, 384>();
      mbar_wait(sb + B_V, sp, budget);
      wg_wait<0>();
      pin<20>(sc);
      if (w == 3 && more) nbar_arrive<NB_S, 64>();
      PROFW(1, 2);
      if (w == 0) {
        uint32_t p[5];
        float v[10];
#pragma unroll
        for (int i = 0; i < 10; i++) v[i] = sc[4 * (i >> 1) + (i & 1)];
        softmax_row(v, p);
        const uint32_t a = sb + lane * 4;
        sts32v(a + PM0, p[0]); sts32v(a + PM0 + 128, p[1]); sts32v(a + PM1, p[2]); sts32v(a + PM1 + 128, p[3]); sts32v(a + PM2, p[4]);
      }
      if (more) {
        float rs[4], ot[2][4];
        uint32_t one[4];
#pragma unroll
        for (int i = 0; i < 4; i++) one[i] = 0x3F803F80u + ((uint32_t)budget >> (31 - i));
        typedef Op<PM0, 128, 128, 0, 0> P0; typedef Op<PM1, 128, 128, 0, 0> P1; typedef Op<PM2, 0, 128, 0, 0> P2;
        fence_proxy_async();
        nbar_sync<NB_P, 128>();
        PROFW(0, 3);
        wg_fence();
        wg_rs8<0, P0>(rs, one, d0); wg_rs8<1, P1>(rs, one, d0); wg_rs8<1, P2>(rs, one, d0);
        wg_commit();
        sfor<0, 2>([&](auto T) {
          constexpr int t = T;
          wg_ss8<0, Op<QB + 8 * RG + t * 1024, 2 * RG, 128, 0, 0>, P0>(ot[t], d0, d0);
          wg_ss8<1, Op<QB + 12 * RG + t * 1024, RG, 128, 0, 0>, P1>(ot[t], d0, d0);
          wg_ss8<1, Op<QB + 14 * RG + t * 1024, 0, 128, 0, 0>, P2>(ot[t], d0, d0);
        });
        wg_commit();
        if (P_G2 < 16 && !P_G2L) nbar_arrive<NB_G2, 384>();
        const uint32_t oa = w * 256 + lane * 4, r1 = mapa(sb, rank ^ 1), r2 = mapa(sb, 2);
        mbar_wait(sb + B_SDONE, sp, budget);
        wg_wait<1>();
        pin<4>(rs);
        float i0, i1;
        asm volatile("rcp.approx.ftz.f32 %0, %1;" : "=f"(i0) : "f"(rs[0]));
        asm volatile("rcp.approx.ftz.f32 %0, %1;" : "=f"(i1) : "f"(rs[1]));
        wg_wait<0>();
        pin<4>(ot[0]); pin<4>(ot[1]);
        uint32_t x[4];
#pragma unroll
        for (int j = 0; j < 4; j++) {
          x[j] = pack_bf16(ot[j >> 1][2 * (j & 1)] * i0, ot[j >> 1][2 * (j & 1) + 1] * i1);
          sts32v(sb + OM + rank * OMS + oa + (j >> 1) * 1024 + (j & 1) * 128, x[j]);
        }
        fence_proxy_async();
#pragma unroll
        for (int j = 0; j < 8; j++) {
          const int i = P_OS ? j >> 1 : j & 3;
          if (P_OS ? j & 1 : j >> 2) st_async32(r1 + OM + rank * OMS + oa + (i >> 1) * 1024 + (i & 1) * 128, x[i], r1 + B_OM);
          else st_async32(r2 + OM2 + rank * OM2S + oa + (i >> 1) * 1024 + (i & 1) * 128, x[i], r2 + B_OM);
        }
        e_arrive(sb + B_OM);
        if (P_G2 < 16 && P_G2L) nbar_arrive<NB_G2, 384>();
        PROFW(0, 4);
      }
#pragma unroll
      for (int i = 0; i < 10; i++) hold[i] = w ? sc[4 * (i >> 1) + (i & 1)] : sc[4 * (i >> 1) + 2 + (i & 1)];
    }
    if (more && s >= 0) {
      LANE_NOW;
      char* const pw = (char*)g_part + (uint32_t)((t0 * 16 + w * 4 + (lane >> 3)) * 4096 + h * 128 + ((lane ^ h) & 7) * 16);
      mbar_wait(sb + B_OM, sp, budget);
      if (w == 0) nbar_arrive<NB_G, 128>();
      PROFW(1, 5);
      if (!ATT) fence_proxy_async();
      float acc[3][8];
      sfor<0, NT + 1>([&](auto J) {
        constexpr int j = J;
        if constexpr (j < NT) {
          if constexpr (ATT && j == JA) { mbar_wait(sb + B_WA, sp, budget); PROFW(2, 0); }
          wg_fence();
          sfor<0, 8>([&](auto K) {
            constexpr int k = K;
            typedef Op<(ATT ? OM : OM2) + k * 256, 128, ATT ? OMS : OM2S, 0, 1> OB;
            if constexpr (j == 5 && k < 4) wg_rs16<k ? 1 : 2, OB>(acc[j % 3], wl + 4 * k, d0);
            else wg_ss16<k ? 1 : j < 3 ? 0 : 2, Op<(j == JA ? WA : j < 5 ? WO + (j - (j > JA)) * 16384 : WH - 8192) + k * 2048, 16, 1024, 1, 1>, OB>(acc[j % 3], d0, d0);
          });
          wg_commit();
          if constexpr (j == 0) { if (w == 3) e_expect_tx(sb + B_OM, ATT ? 2048 : 4096); }
          if constexpr (j == NT - 1) nbar_arrive<NB_WO, 384>();
        }
        if constexpr (j > 0) {
          if constexpr (j < NT) wg_wait<1>(); else wg_wait<0>();
          float* d = acc[(j - 1) % 3];
          pin<8>(d);
          uint32_t x[4];
#pragma unroll
          for (int i = 0; i < 4; i++) { const uint32_t m = (h >> 3) == i; x[i] = (pack_bf16(d[2*i], d[2*i+1]) & ~m) | (m & ~sp); }
          stg_rlx128(pw + (j - 1) * (48 * 4096), x[0], x[1], x[2], x[3]);
          if constexpr (ATT && j == JA + 1) nbar_arrive<NB_TR, 160>();
          if constexpr (j == 3) PROFW(3, 26);
        }
      });
    } else if (more) nbar_arrive<NB_WO, 384>();
    PROFW(0, 6);
    asm volatile("" : "+r"(h), "+r"(rank), "+r"(w));
    if (ATT) {
      LANE_NOW;
      const int lim = 8 * (g >> 1) + (g & 1) + 2 * w - 8 * c;
      uint32_t p[5];
#pragma unroll
      for (int i = 0; i < 8; i++) hold[2+i] = i <= lim ? hold[2+i] : -INFINITY;
      if (w == 3 && lane < 14) sts128(sb + PM1 + lane * 16, (lane >> 1) == 3 ? 0x3F803F80u : 0);
      const float psum = softmax_row(hold, p);
#pragma unroll
      for (int i = 0; i < 5; i++) hold[i] = __uint_as_float(p[i]);
      hold[5] = psum;
      pin<6>(hold);
    }
    if (ATT && more) {
      LANE_NOW;
      const int blk = rank * 32 + h;
      char* const mw = (char*)g_mem + (uint32_t)(sp * 32768 + blk * 512 + w * 128 + lane * 4);
      const bool start = s == -1 || (s == LAG - 1 && (w & 1));
      uint32_t v = 0;
      if (start) {
        const unsigned short* q = (const unsigned short*)mem0 + c * 2 * DM + blk * 16 + (w >> 1) * 8 + g;
        v = q[0] | (uint32_t)q[DM] << 16;
        if (v == 0) v = 0x8000u;
      }
      keep(mw);
      if (s >= 0) {
        fence_proxy_async();
        nbar_sync<NB_P, 128>();
        const uint32_t ca = sb + WA + lane * 128 + (((2 * w) ^ lane) & 7) * 16 + (lane >> 3) * 4;
        const uint32_t sa = sb + OM + (((g >> 1) & 1) * 2 + (g >> 2)) * 128 + (2 * c + (w >> 1)) * 16 + (w & 1) * 8 + (g & 1) * 2;
        for (bool first = true; ; first = false) {
          float r[4];
          mbar_wait(sb + B_PART, pph, budget);
          PROFW(0, 11);
          pph ^= 1;
          wg_fence();
          sfor<0, 8>([&](auto K) { constexpr int k = K; wg_ss8<k != 0, Op<WA + k * 2048, 16, 1024, 1, 1>, Op<PM1 + (6 - (k & 6)) * 16, 0, 128, 0, 0>>(r, d0, d0); });
          wg_commit();
          if (P_G4 < 16 && first) nbar_arrive<NB_G4, 384>();
          const uint32_t x0 = lds32v(ca), x1 = lds32v(ca + 4096), x2 = lds32v(ca + 8192), x3 = lds32v(ca + 12288);
          const bool bad = __any_sync(0xffffffffu, (sp ? x0 | x1 | x2 | x3 : ~(x0 & x1 & x2 & x3)) & 1) && budget > 0;
          wg_wait<0>();
          pin<4>(r);
          uint32_t y = pack_bf16(r[0], r[2]);
          y |= (y & 0xffffu) ? 0 : 0x8000u;
          y |= (y >> 16) ? 0 : 0x80000000u;
          if (bad) y = 0;
          sts16(sa, y); sts16(sa + 4, y >> 16);
          nbar_sync<NB_P, 128>();
          y = lds32v(sb + OM + w * 128 + lane * 4);
          if (!__any_sync(0xffffffffu, y == 0)) { if (!start) v = y; break; }
          nbar_sync<NB_P, 128>();
          budget--;
          if (w == 0) { e_expect_tx(sb + B_PART, 16384); e_bulk_g2s(sb + WA, (const char*)g_part + blk * 16384, 16384, sb + B_PART); }
          __syncwarp();
        }
      }
      stg_rlx32(mw, v);
      stg_rlx32(mw + (sp ? -32768 : 32768), 0);
      PROFW(1, 8);
    }
    if (ATT && s >= 0) {
      const int seg = s - (rank ? LAG : 0);
      const bool act = (unsigned)seg < NSEG;
      LANE_NOW;
      uint32_t a[12];
#pragma unroll
      for (int i = 0; i < 12; i++) a[i] = __float_as_uint(hold[i < 10 ? i >> 1 : 4]) + ((uint32_t)budget >> (31 - (i & 3)));
      float o[32], inv, psum = hold[5];
      char* const ob = (char*)g_o[rank] + ((size_t)(seg * 32 + 8 * (g >> 1) + (g & 1) + 2 * w) * (NH * DH) + h * DH + c * 8) * 2;
      sfor<0, 2>([&](auto HF) {
        constexpr int hf = HF;
        wg_fence();
        wg_rs64<hf * 2, Op<QB + 8 * RG + hf * 1024, 2 * RG, 128, 0, 0>>(o, a, d0);
        wg_rs64<1, Op<QB + 12 * RG + hf * 1024, RG, 128, 0, 0>>(o, a + 4, d0);
        wg_rs64<1, Op<QB + 14 * RG + hf * 1024, 0, 128, 0, 0>>(o, a + 8, d0);
        wg_commit();
        if constexpr (hf == 0) {
          psum += __shfl_xor_sync(0xffffffffu, psum, 1);
          psum += __shfl_xor_sync(0xffffffffu, psum, 2);
          asm("rcp.approx.ftz.f32 %0, %1;" : "=f"(inv) : "f"(psum));
        }
        wg_wait<0>();
        pin<32>(o);
        if constexpr (hf == 1) { if (w < 3 && more) e_arrive_cl(mapa(sb + B_BFREE, w)); }
        if (act) {
#pragma unroll
          for (int i = 0; i < 2; i++)
            stg128(ob + (hf * 2 + i) * 64, pack_bf16(o[16*i] * inv, o[16*i+1] * inv), pack_bf16(o[16*i+4] * inv, o[16*i+5] * inv),
                   pack_bf16(o[16*i+8] * inv, o[16*i+9] * inv), pack_bf16(o[16*i+12] * inv, o[16*i+13] * inv));
        }
      });
      PROFW(0, 7);
      if (act && (seg & 3) == 3) {
        __syncwarp();
        e_flag_add(g_fl.o[rank][seg >> 2]);
      }
    } else if (!ATT && w == 3) {
      if (s + 4 < NSEG) e_prefetch(g_xn[0] + (size_t)((s + 4) * 32 + h) * DM, 2048);
    }
  }
  cluster_arrive(); cluster_wait();
  char* const pw = (char*)g_part + (size_t)((ATT ? rank + 1 : 0) * 16 + w * 4 + (lane0 >> 3)) * 4096 + h * 128 + (lane0 & 7) * 16;
#pragma unroll
  for (int j = 0; j < NT; j++) stg_rlx128(pw + j * (48 * 4096), 0, 0, 0, 0);
}

DEVI void rec_load(const uint32_t sb, const int h, const int rank, const int w, const CUtensorMap* mX, const CUtensorMap* mWo) {
  using namespace rec;
  static_assert(((NSTEP - 1) & 31) != 1 && ((NSTEP - 2) & 31) != 2, "stale time stamps of the previous launch never match");
  const int lane0 = lane_reg(), mq = (w + 3) & 3;
  int budget = SPIN_BUDGET;
  cluster_arrive(); cluster_wait();
  if (w == 0) { if (lane0 < 4) mbar_arrive(sb + B_FULL + 8 * lane0); __syncwarp(); }
  uint32_t lph = 0;
#pragma unroll 1
  for (int s = -1; s < NSTEP - 1; s++) {
    if (w == 0) {
      const int sa = s + 1, sn = sa - LAG;
      if ((sa & 3) == 0 && sa < NSEG) flag_wait(g_fl.xn[0][sa >> 2], 32, budget);
      if ((sn & 3) == 0 && (unsigned)sn < NSEG) flag_wait(g_fl.xn[1][sn >> 2], 32, budget);
      int sl = 4, ph = 1;
#pragma unroll 1
      for (int i = 0; i < 16; i++) {
        mbar_wait(sb + B_EMPTY + 8 * sl, ph, budget);
        e_expect_tx(sb + B_FULL + 8 * sl, 8192);
        e_tma_3d(sb + RING + sl * 8192, mX, i * 64, (s + 1) * 32, sb + B_FULL + 8 * sl);
        if (++sl == 5) { sl = 0; ph ^= 1; }
      }
      nbar_arrive<NB_X, 128>();
    }
    uint32_t t = gtime();
    if (s >= 0) {
      uint2 a;
      if (w == 2 && rank < 2) {
        nbar_sync<NB_S, 64>();
        e_expect_tx(sb + B_WA, 16384);
        e_tma_2d(sb + WA, mWo, (3 * JA + 1 + rank) * 64, h * DH, sb + B_WA);
        e_tma_2d(sb + WA + 8192, mWo, (3 * JA + 1 + rank) * 64, h * DH + 64, sb + B_WA);
        e_arrive_cl(mapa(sb + B_SDONE, rank ^ 1));
        stg_rlx32(&g_ann[s & 1][lane0][h * 2 + rank], (gtime() & ~31u) | ((s + 1) & 31));
        e_expect_tx(sb + B_QK, 10240);
        e_expect_tx(sb + B_V, 10240);
      }
      if (w) nbar_sync<NB_G, 128>();
      do { a = ldg_rlx64(&g_ann[s & 1][h][lane0 * 2]); } while (__any_sync(0xffffffffu, ((a.x ^ (s + 1)) | (a.y ^ (s + 1))) & 31) && --budget > 0);
      t += __reduce_max_sync(0xffffffffu, max((int)(a.x - t), (int)(a.y - t)));
      t &= ~31u;
      PROFW(1, 12);
      if (w == 1 && rank < 2) {
        nbar_sync<NB_TR, 160>();
        wait_time(t + (rank ? TUN(1, 1750) : TUN(0, 1500)), budget);
        e_expect_tx(sb + B_PART, 16384);
        e_bulk_g2s(sb + WA, (const char*)g_part + (rank * 32 + h) * 16384, 16384, sb + B_PART);
        PROFW(1, 21);
      }
      t += mq == 0 ? TUN(2, 2500) : mq == 1 ? TUN(3, 2550) : mq == 2 ? TUN(4, 2800) : TUN(5, 2800);
    }
    if (w) nbar_sync<NB_X, 128>();
    mbar_wait(sb + B_EMPTY + 8 * mq, 1, budget);
    PROFW(1, 9);
    wait_time(t, budget);
    PROFW(1, 22); PROFW(3, 23);
    while (true) {
      e_expect_tx(sb + B_MLAND + 8 * mq, 8192);
      e_bulk_g2s(sb + RING + mq * 8192, (const char*)g_mem + (s & 1) * 32768 + mq * 8192, 8192, sb + B_MLAND + 8 * mq);
      const uint32_t a = sb + RING + mq * 8192 + lane0 * 32 + (lane0 >> 2) * 4;
      mbar_wait(sb + B_MLAND + 8 * mq, lph, budget);
      lph ^= 1;
      PROFW(1, 24);
      uint32_t mn = 0xffffffffu;
#pragma unroll
      for (int i = 0; i < 8; i++) mn = min(mn, lds32v(a + i * 1024));
      if (!__any_sync(0xffffffffu, mn == 0) || --budget <= 0) break;
    }
    e_arrive(sb + B_FULL + 8 * mq);
    PROFW(1, 10); PROFW(2, 13); PROFW(3, 14); PROFW(0, 15);
  }
}

struct RecMaps { CUtensorMap w[3], wo, x; };
__global__ void __cluster_dims__(3, 1, 1) __launch_bounds__(512, 1)
rec_kernel(const __grid_constant__ RecMaps M, const bf16* __restrict__ Wo, const bf16* __restrict__ mem0, uint32_t zero) {
  using namespace rec;
  extern __shared__ __align__(1024) uint8_t smem[];
  const uint32_t sb = smem_u32(smem);
  const int tid = threadIdx.x, warp = __shfl_sync(0xffffffffu, tid >> 5, 0), wg = warp >> 2, lane = tid & 31;
  const int h = blockIdx.x / 3, rank = blockIdx.x % 3;
  if (warp == 0) {
    if (lane < 20) mbar_init(sb + BARS + 8 * lane, (lane >= 5 && lane < 10) || lane == 19 ? 2 : lane == 14 ? 9 : lane == 16 && rank < 2 ? 5 : 1);
    else if (lane < 23) mbar_init(sb + B_W1 + 8 * (lane - 20), 1);
    else if (lane == 23) mbar_init(sb + B_PART, 1);
    fence_mbar_init();
    __syncwarp();
    if (lane == 0) { mbar_expect_tx(sb + B_W1, (NSS + R1) * 4096); mbar_expect_tx(sb + B_QK, 10240); mbar_expect_tx(sb + B_V, 10240); mbar_expect_tx(sb + B_OM, rank < 2 ? 2048 : 4096); }
    __syncwarp();
    for (int i = lane; i < 128; i += 32) {
      const int j = i >> 1, t = i & 1, r = reg_idx(j);
      if (is_ss(j)) tma_load_2d(sb + WS + (t * NSS + ss_before(j)) * 2048, &M.w[rank], h * DH + t * 64, j * 16, sb + B_W1);
      else if (r < R1) tma_load_2d(sb + WO + (t * R1 + r) * 2048, &M.w[rank], h * DH + t * 64, j * 16, sb + B_W1);
      else tma_prefetch_2d(&M.w[rank], h * DH + t * 64, j * 16);
    }
    const int t = 3 * (lane >> 1) + (rank + 1) % 3;
    if (t < 16) tma_prefetch_2d(&M.wo, t * 64, h * DH + (lane & 1) * 64);
  } else if (warp == 1) {
    constexpr int N = (sizeof(Flags) - sizeof(g_fl.xn)) / 16;
    const int i = blockIdx.x * 16 + lane;
    if (lane < 16 && i < N) ((uint4*)g_fl.o)[i] = make_uint4(0, 0, 0, 0);
    static_assert(N <= 96 * 16, "flag reset");
    __threadfence();
    __syncwarp();
    asm volatile("griddepcontrol.launch_dependents;" ::: "memory");
  }
  __syncthreads();
  if (wg == 3) {
    reg_dec<24>();
    rec_load(sb, h, rank, warp & 3, &M.x, &M.wo);
    cluster_arrive(); cluster_wait();
  } else if (wg == 2) {
    reg_dec<72>();
    if (rank < 2) rec_attn<true>(sb, h, rank, warp & 3, Wo, mem0);
    else rec_attn<false>(sb, h, rank, warp & 3, Wo, mem0);
  } else {
    reg_inc<208>();
    rec_proj(sb, h, rank, warp, &M.w[rank], &M.wo, zero);
    cluster_arrive(); cluster_wait();
  }
}

namespace gm {
constexpr int STAGES = 6, STAGE_BYTES = 32768;
constexpr uint32_t SO = STAGES * STAGE_BYTES, B_FULL = SO + 32768, B_EMPTY = B_FULL + 64, B_JOB = B_FULL + 128, JOB = B_FULL + 144, SMEM = B_FULL + 192;
constexpr int T_O = 0, T_GU = 1, T_D = 2, T_END = 3, NJOB = 2 * 16 * 72;
#define G_FILL 3
struct JobList { uint16_t j[NJOB]; };
constexpr JobList make_jobs() {
  JobList L{};
  int n = 0, f = 0;
  auto add = [&](int t, int l, int c, int j0, int j1) { for (int j = j0; j < j1; j++) L.j[n++] = (uint16_t)(t << 11 | l << 10 | c << 6 | j); };
  for (int c = 0; c <= 16; c++) {
    if (c < 16) add(T_O, 0, c, 0, 8);
    if (c > 0) { add(T_GU, 0, c - 1, 0, 56); add(T_D, 0, c - 1, 0, 8); }
    for (int i = 0; i < G_FILL && f / 8 + (LAG + 3) / 4 + 1 <= c; i++, f++) add(T_O, 1, f / 8, f % 8, f % 8 + 1);
  }
  for (; f < 128; f++) add(T_O, 1, f / 8, f % 8, f % 8 + 1);
  for (int c = 0; c < 16; c++) add(T_GU, 1, c, 0, 56);
  for (int c = 0; c < 16; c++) add(T_D, 1, c, 0, 8);
  return L;
}
__device__ const JobList g_jobs = make_jobs();
struct Pipe { int s, ph; DEVI void next() { if (++s == STAGES) { s = 0; ph ^= 1; } } };
}
struct GemmMaps { CUtensorMap o, wo, x, x1, xm, wg, wu, h, wd, x2, out; };

DEVI float geglu(float g, float u) {
  const float z = g * (0.7978845608028654f + 0.035677408136300125f * g * g);
  float t; asm("tanh.approx.f32 %0, %1;" : "=f"(t) : "f"(z));
  const float hg = 0.5f * g;
  return fmaf(hg, t, hg) * u;
}
DEVI int h_wait(const int* p, int i, int& budget) {
  int n = 64;
  while ((n = (__ffs(~ld_acquire(p) & 0x88888888) >> 2) * 8 - 8) <= i && --budget > 0) __nanosleep(32);
  asm volatile("fence.proxy.async.global;" ::: "memory");
  return n;
}
DEVI void ln_rows(const bf16* src, bf16* dst, int lane) {
  uint4 u[2][4];
#pragma unroll
  for (int r = 0; r < 2; r++)
#pragma unroll
    for (int i = 0; i < 4; i++) u[r][i] = __ldcg((const uint4*)(src + r * DM) + i * 32 + lane);
#pragma unroll
  for (int r = 0; r < 2; r++) {
    uint32_t* x = (uint32_t*)u[r];
    float sum = 0;
#pragma unroll
    for (int i = 0; i < 16; i++) sum += bf_lo(x[i]) + bf_hi(x[i]);
#pragma unroll
    for (int o = 16; o; o >>= 1) sum += __shfl_xor_sync(0xffffffffu, sum, o);
    const float mean = sum * (1.f / DM);
    float q = 0;
#pragma unroll
    for (int i = 0; i < 16; i++) asm volatile("" : "+r"(x[i]));
#pragma unroll
    for (int i = 0; i < 16; i++) { const float a = bf_lo(x[i]) - mean, b = bf_hi(x[i]) - mean; q = fmaf(a, a, fmaf(b, b, q)); }
#pragma unroll
    for (int o = 16; o; o >>= 1) q += __shfl_xor_sync(0xffffffffu, q, o);
    const float rs = rsqrtf(q * (1.f / DM) + 1e-5f), mr = -mean * rs;
#pragma unroll
    for (int i = 0; i < 16; i++) asm volatile("" : "+r"(x[i]));
#pragma unroll
    for (int i = 0; i < 16; i++) x[i] = pack_bf16(fmaf(bf_lo(x[i]), rs, mr), fmaf(bf_hi(x[i]), rs, mr));
#pragma unroll
    for (int i = 0; i < 4; i++) ((uint4*)(dst + r * DM))[i * 32 + lane] = u[r][i];
  }
}
DEVI void ln_stream(int* ticket, const int* dep, const bf16* src, bf16* dst, int* done) {
  const int lane = threadIdx.x & 31;
  int budget = SPIN_BUDGET;
  while (true) {
    const int t = bcast(e_ticket(ticket));
    if (t >= 512) break;
    if (dep) flag_wait(dep + (t >> 5) * 32, 8, budget);
#pragma unroll 1
    for (int r = 0; r < 4; r += 2) ln_rows(src + (size_t)(t * 4 + r) * DM, dst + (size_t)(t * 4 + r) * DM, lane);
    __syncwarp();
    e_flag_add(done + (t >> 5) * 32);
  }
}

__global__ void __launch_bounds__(384, 1) gemm_kernel(const __grid_constant__ GemmMaps M, const bf16* __restrict__ x) {
  using namespace gm;
  extern __shared__ __align__(1024) uint8_t smem[];
  const uint32_t sb = smem_u32(smem);
  const int tid = threadIdx.x, wid = __shfl_sync(0xffffffffu, tid >> 5, 0), wg = wid >> 2, warp = wid & 3;
  int budget = SPIN_BUDGET;
  if (tid < 18) mbar_init(sb + B_FULL + 8 * tid, 1);
  fence_mbar_init();
  __syncthreads();
  if (wg == 2) {
    reg_dec<72>();
    if (warp == 0) {
      Pipe p; p.s = 0; p.ph = 1;
      int tk = e_ticket(g_fl.ticket);
      for (int n = 0; ; n++) {
        tk = bcast(tk);
        const int job = __shfl_sync(0xffffffffu, tk < NJOB ? g_jobs.j[tk] : T_END << 11, 0);
        const int ty = job >> 11, l = (job >> 10) & 1, cb = (job >> 6) & 15, j = job & 63, row = l * SEQ + cb * 128;
        mbar_wait(sb + B_EMPTY + 8 * p.s, p.ph, budget);
        if (budget <= 0) __trap();
        sts32v(sb + JOB + 4 * (n & 1), job | p.s << 16 | (p.ph ^ 1) << 20);
        e_arrive(sb + B_JOB + 8 * (n & 1));
        if (ty == T_END) break;
        const int nk = ty == T_O ? 64 : ty == T_GU ? 16 : 56;
        int rdy = 64;
        if (ty == T_D) rdy = h_wait(g_fl.h[l][cb], 0, budget);
        else flag_wait(ty == T_O ? g_fl.o[l][cb] : g_fl.xm[l][cb], ty == T_O ? 128 : 32, budget);
        if (ty != T_GU) {
          const uint32_t fb = sb + B_FULL + 8 * p.s, a = sb + p.s * STAGE_BYTES;
          const CUtensorMap* m = ty == T_D ? &M.x1 : l ? &M.x2 : &M.x;
          const int r = ty == T_D ? row : cb * 128;
          e_expect_tx(fb, STAGE_BYTES);
          e_tma_2d(a, m, j * 128, r, fb); e_tma_2d(a + 16384, m, j * 128 + 64, r, fb);
          p.next();
        }
        const CUtensorMap* const ma = ty == T_O ? &M.o : ty == T_GU ? &M.xm : &M.h;
        for (int i = 0; i < nk; i++) {
          if (i == nk - 4) tk = e_ticket(g_fl.ticket);
          const uint32_t fb = sb + B_FULL + 8 * p.s, a = sb + p.s * STAGE_BYTES, b = a + 16384;
          mbar_wait(sb + B_EMPTY + 8 * p.s, p.ph, budget);
          e_expect_tx(fb, STAGE_BYTES);
          if (ty == T_O) { e_tma_5d(b, &M.wo, j * 128, i * 2, fb); e_tma_5d(b + 8192, &M.wo, j * 128 + 64, i * 2, fb); }
          else if (ty == T_GU) { e_tma_2d(b, &M.wg, j * 64, i * 64, fb); e_tma_2d(b + 8192, &M.wu, j * 64, i * 64, fb); }
          else {
            e_tma_2d(b, &M.wd, j * 128, i * 64, fb); e_tma_2d(b + 8192, &M.wd, j * 128 + 64, i * 64, fb);
            if (i >= rdy) rdy = h_wait(g_fl.h[l][cb], i, budget);
          }
          e_tma_2d(a, ma, i * 64, row, fb);
          p.next();
        }
      }
    } else {
      const int ws = warp - 1;
#pragma unroll 1
      for (int i = ws; i < 3; i = i < 2 ? 2 : 3)
        ln_stream(g_fl.ticket + 32 + 8 * i, i == 1 ? g_fl.x2[0] : g_fl.x1[i >> 1][0], i == 1 ? g_x2 : g_x1[i >> 1],
                  i == 1 ? g_xn[1] + LAG * 32 * DM : g_xm[i >> 1], i == 1 ? g_fl.xn[1][0] : g_fl.xm[i >> 1][0]);
      if (blockIdx.x == 0 && ws == 2) {
        asm volatile("griddepcontrol.wait;" ::: "memory");
        g_fl.xn[(tid >> 4) & 1][tid & 15][0] = 0;
      }
    }
  } else {
    reg_inc<216>();
    ln_stream(g_fl.ticket + 56, nullptr, x, g_xn[0], g_fl.xn[0][0]);
    const int lane = lane_reg();
    const bool lead = warp == 0;
    const uint32_t so = sb + SO + wg * 16384;
    const int r0 = warp * 16 + (lane & 7) + ((lane >> 3) & 1) * 8;
    const uint32_t sw = r0 * 128 + (((lane >> 4) ^ (r0 & 7)) << 4);
    for (int n = wg; ; n += 2) {
      float d0[64], d1[64];
      mbar_wait(sb + B_JOB + 8 * wg, (n >> 1) & 1, budget);
      if (budget < 0) __trap();
      const int job = __shfl_sync(0xffffffffu, lds32v(sb + JOB + 4 * wg), 0);
      const int ty = (job >> 11) & 3, l = (job >> 10) & 1, cb = (job >> 6) & 15, j = job & 63;
      if (ty == T_END) {
        if (n > 0) nbar_sync_r(1 + wg, 256);
        if (lead && !(job & 1)) { sts32v(sb + JOB + 4 * (wg ^ 1), job | 1); e_arrive(sb + B_JOB + 8 * (wg ^ 1)); }
        if (!(job & 1)) nbar_arrive_r(1 + (wg ^ 1), 256);
        break;
      }
      Pipe q; q.s = (job >> 16) & 15; q.ph = job >> 20;
      if (ty != T_GU) {
        mbar_wait(sb + B_FULL + 8 * q.s, q.ph, budget);
#pragma unroll
        for (int m = 0; m < 2; m++)
#pragma unroll
          for (int c = 0; c < 8; c++) {
            float* d = (m ? d1 : d0) + 8 * c;
            uint32_t r[4];
            ldsm4(sb + q.s * STAGE_BYTES + (c >> 2) * 16384 + m * 8192 + (sw ^ ((c & 3) << 5)), r[0], r[1], r[2], r[3]);
#pragma unroll
            for (int i = 0; i < 4; i++) { d[2*i] = bf_lo(r[i]); d[2*i+1] = bf_hi(r[i]); }
          }
        fence_proxy_async();
        nbar_sync_r(3 + wg, 128);
        if (lead) e_arrive(sb + B_EMPTY + 8 * q.s);
        q.next();
      } else {
#pragma unroll
        for (int i = 0; i < 64; i++) d0[i] = d1[i] = 0.f;
      }
      pin<64>(d0); pin<64>(d1);
      if (n > 0) nbar_sync_r(1 + wg, 256);
      const int nk = ty == T_O ? 64 : ty == T_GU ? 16 : 56;
      int prev = 0;
      for (int i = 0; i < nk; i++) {
        mbar_wait(sb + B_FULL + 8 * q.s, q.ph, budget);
        const uint32_t da = desc_base(sb) + q.s * (STAGE_BYTES / 16);
        wg_fence();
        sfor<0, 4>([&](auto K) {
          constexpr int k = K;
          typedef Op<16384 + k * 2048, 8192, 1024, 1, 1> OB;
          wg_ss128<1, Op<k * 32, 16, 1024, 1, 0>, OB>(d0, da, da);
          wg_ss128<1, Op<8192 + k * 32, 16, 1024, 1, 0>, OB>(d1, da, da);
        });
        wg_commit();
        wg_wait<1>();
        arrive_if_eq(sb + B_EMPTY + 8 * prev, lane, i ? warp * 32 : -1);
        prev = q.s;
        q.next();
      }
      nbar_arrive_r(1 + (wg ^ 1), 256);
      wg_wait<0>();
      pin<64>(d0); pin<64>(d1);
      if (lead) e_arrive(sb + B_EMPTY + 8 * prev);
      if (ty == T_GU) {
#pragma unroll
        for (int m = 0; m < 2; m++)
#pragma unroll
          for (int c = 0; c < 4; c++) {
            const float* d = (m ? d1 : d0) + 8 * c;
            uint32_t r[4];
#pragma unroll
            for (int i = 0; i < 4; i++) r[i] = pack_bf16(geglu(d[2*i], d[32+2*i]), geglu(d[2*i+1], d[32+2*i+1]));
            stsm4(so + m * 8192 + (sw ^ (c << 5)), r[0], r[1], r[2], r[3]);
          }
        fence_proxy_async();
        nbar_sync_r(3 + wg, 128);
        if (lead) {
          e_tma_store_2d(&M.h, so, j * 64, l * SEQ + cb * 128);
          bulk_commit(); bulk_wait<0>();
          e_flag_add(g_fl.h[l][cb], 1 << ((j >> 3) * 4));
        }
      } else {
        const CUtensorMap* const mo = ty == T_O ? &M.x1 : l ? &M.out : &M.x2;
        const int row = (ty == T_O ? l * SEQ : 0) + cb * 128;
#pragma unroll
        for (int hf = 0; hf < 2; hf++) {
          if (hf) nbar_sync_r(3 + wg, 128);
#pragma unroll
          for (int m = 0; m < 2; m++)
#pragma unroll
            for (int c = 0; c < 4; c++) {
              const float* d = (m ? d1 : d0) + 32 * hf + 8 * c;
              stsm4(so + m * 8192 + (sw ^ (c << 5)), pack_bf16(d[0], d[1]), pack_bf16(d[2], d[3]), pack_bf16(d[4], d[5]), pack_bf16(d[6], d[7]));
            }
          fence_proxy_async();
          nbar_sync_r(3 + wg, 128);
          if (lead) {
            e_tma_store_2d(mo, so, j * 128 + hf * 64, row);
            bulk_commit();
            if (hf == 0) bulk_wait_read<0>();
            else {
              bulk_wait<0>();
              if (ty == T_O) e_flag_add(g_fl.x1[l][cb]); else if (l == 0) e_flag_add(g_fl.x2[cb]);
            }
          }
        }
      }
    }
  }
}

typedef CUresult (*PFN_encodeTiled)(CUtensorMap*, CUtensorMapDataType, cuuint32_t, void*, const cuuint64_t*, const cuuint64_t*,
                                    const cuuint32_t*, const cuuint32_t*, CUtensorMapInterleave, CUtensorMapSwizzle,
                                    CUtensorMapL2promotion, CUtensorMapFloatOOBfill);
static PFN_encodeTiled g_encode = nullptr;
static CUtensorMap encode(const void* ptr, int rank, const cuuint64_t* dims, const cuuint64_t* strides, const cuuint32_t* box) {
  CUtensorMap m;
  const cuuint32_t es[5] = {1, 1, 1, 1, 1};
  g_encode(&m, CU_TENSOR_MAP_DATA_TYPE_BFLOAT16, rank, (void*)ptr, dims, strides, box, es, CU_TENSOR_MAP_INTERLEAVE_NONE,
           CU_TENSOR_MAP_SWIZZLE_128B, CU_TENSOR_MAP_L2_PROMOTION_L2_256B, CU_TENSOR_MAP_FLOAT_OOB_FILL_NONE);
  return m;
}
static CUtensorMap make_map(const void* ptr, uint64_t rows, uint64_t cols, uint32_t box_rows) {
  const cuuint64_t dims[2] = {cols, rows}, strides[1] = {cols * 2};
  const cuuint32_t box[2] = {64, box_rows};
  return encode(ptr, 2, dims, strides, box);
}
static CUtensorMap make_map_x(const void* ptr) {
  const cuuint64_t dims[3] = {DM, NSTEP * 32, 2}, strides[2] = {DM * 2, (cuuint64_t)NSTEP * 32 * DM * 2};
  const cuuint32_t box[3] = {64, 32, 2};
  return encode(ptr, 3, dims, strides, box);
}
static CUtensorMap make_map_wo(const void* ptr) {
  const cuuint64_t dims[5] = {DM, 2, 4, 4, NH * DH / 32}, strides[4] = {DM * 2, 8 * DM * 2, 2 * DM * 2, 32 * DM * 2};
  const cuuint32_t box[5] = {64, 2, 4, 4, 2};
  return encode(ptr, 5, dims, strides, box);
}

extern "C" void kernel_launch(void* const* d_in, const int* in_sizes, int n_in, void* d_out, int out_size) {
  const bf16 *x = (const bf16*)d_in[0], *mem0 = (const bf16*)d_in[1], *Wo = (const bf16*)d_in[5];
  if (!g_encode) {
    void* p = nullptr; cudaDriverEntryPointQueryResult q;
    cudaGetDriverEntryPoint("cuTensorMapEncodeTiled", &p, cudaEnableDefault, &q);
    g_encode = (PFN_encodeTiled)p;
    cudaFuncSetAttribute(rec_kernel, cudaFuncAttributeMaxDynamicSharedMemorySize, rec::SMEM);
    cudaFuncSetAttribute(gemm_kernel, cudaFuncAttributeMaxDynamicSharedMemorySize, gm::SMEM);
  }
  void *xn, *o, *x1, *xm, *x2, *hh;
  cudaGetSymbolAddress(&xn, g_xn); cudaGetSymbolAddress(&o, g_o); cudaGetSymbolAddress(&x1, g_x1);
  cudaGetSymbolAddress(&xm, g_xm); cudaGetSymbolAddress(&x2, g_x2); cudaGetSymbolAddress(&hh, g_h);
  RecMaps R;
  for (int i = 0; i < 3; i++) R.w[i] = make_map(d_in[2 + i], DM, NH * DH, 16);
  R.wo = make_map(Wo, NH * DH, DM, 64); R.x = make_map_x(xn);
  rec_kernel<<<96, 512, rec::SMEM>>>(R, Wo, mem0, 0);
  GemmMaps G;
  G.o = make_map(o, 2 * SEQ, NH * DH, 128); G.wo = make_map_wo(Wo); G.x = make_map(x, SEQ, DM, 128);
  G.x1 = make_map(x1, 2 * SEQ, DM, 128); G.xm = make_map(xm, 2 * SEQ, DM, 128);
  G.wg = make_map(d_in[8], DM, DF, 64); G.wu = make_map(d_in[9], DM, DF, 64); G.wd = make_map(d_in[10], DF, DM, 64);
  G.h = make_map(hh, 2 * SEQ, DF, 128); G.x2 = make_map(x2, SEQ, DM, 128); G.out = make_map(d_out, SEQ, DM, 128);
  cudaLaunchConfig_t cfg = {};
  cfg.gridDim = dim3(132); cfg.blockDim = dim3(384); cfg.dynamicSmemBytes = gm::SMEM; cfg.stream = cudaStreamPerThread;
  cudaLaunchAttribute at;
  at.id = cudaLaunchAttributeProgrammaticStreamSerialization; at.val.programmaticStreamSerializationAllowed = 1;
  cfg.attrs = &at; cfg.numAttrs = 1;
  cudaLaunchKernelEx(&cfg, gemm_kernel, G, x);
}
```

```cpp
#include <cuda_runtime.h>
#include <cuda_bf16.h>
#include <cuda.h>
#include <stdint.h>

#define DEVI __device__ __forceinline__
typedef __nv_bfloat16 bf16;

#define LAG 18
constexpr int SEQ = 2048, DM = 1024, NH = 32, DH = 128, DF = 3584, NSEG = 64, NSTEP = NSEG + LAG;
static_assert(NSTEP % 2 == 0, "tags and slots of the exchange buffers return to their initial state");

__device__ __align__(1024) bf16 g_xn[2][NSTEP * 32 * DM];
__device__ __align__(1024) bf16 g_o[2][SEQ * NH * DH];
__device__ __align__(1024) bf16 g_x1[2][SEQ * DM];
__device__ __align__(1024) bf16 g_xm[2][SEQ * DM];
__device__ __align__(1024) bf16 g_x2[SEQ * DM];
__device__ __align__(1024) bf16 g_h[2][SEQ * DF];
__device__ __align__(1024) uint4 g_part[256 * 32 * 8];
__device__ __align__(1024) uint32_t g_ann[2][32][64];
__device__ __align__(1024) uint4 g_mem[2][2048];
#define NSPL 2
constexpr int KS = 4;
__device__ __align__(1024) bf16 g_pt[NSPL * KS * 128 * DM];
__host__ __device__ constexpr int grp(int type, int layer, int blk) { return (layer ? 0 : 48) + 16 * type + blk; }
struct Flags {
  int xn[2][16][32];
  int dep[96];
  int taken[64];
  int part[64];
  int ticket[32];
};
__device__ __align__(128) Flags g_fl;

DEVI uint32_t smem_u32(const void* p) { return (uint32_t)__cvta_generic_to_shared(p); }
DEVI void mbar_init(uint32_t bar, uint32_t cnt) { asm volatile("mbarrier.init.shared::cta.b64 [%0], %1;" :: "r"(bar), "r"(cnt) : "memory"); }
DEVI void mbar_expect_tx(uint32_t bar, uint32_t bytes) { asm volatile("mbarrier.arrive.expect_tx.shared::cta.b64 _, [%0], %1;" :: "r"(bar), "r"(bytes) : "memory"); }
DEVI void mbar_arrive(uint32_t bar) { asm volatile("mbarrier.arrive.shared::cta.b64 _, [%0];" :: "r"(bar) : "memory"); }
DEVI bool mbar_try(uint32_t bar, uint32_t parity) {
  uint32_t p;
  asm volatile("{.reg .pred p; mbarrier.try_wait.parity.shared::cta.b64 p, [%1], %2; selp.u32 %0, 1, 0, p;}" : "=r"(p) : "r"(bar), "r"(parity) : "memory");
  return p;
}
constexpr int SPIN_BUDGET = 1 << 20;
DEVI void mbar_wait(uint32_t bar, uint32_t parity, int& budget) {
  while (!mbar_try(bar, parity)) { if (--budget < 0) break; }
}
DEVI void trap_if_spent(int budget) { asm volatile("{.reg .pred p; setp.le.s32 p, %0, 0; @p trap;}" :: "r"(budget) : "memory"); }
DEVI void fault_if_spent(int budget) { asm volatile("{.reg .pred p; setp.le.s32 p, %0, 0; @p st.global.u32 [%1], 0;}" :: "r"(budget), "l"(0ull) : "memory"); }
DEVI uint32_t mapa(uint32_t addr, uint32_t rank) { uint32_t r; asm("mapa.shared::cluster.u32 %0, %1, %2;" : "=r"(r) : "r"(addr), "r"(rank)); return r; }
DEVI void cluster_arrive() { asm volatile("barrier.cluster.arrive.release.aligned;" ::: "memory"); }
DEVI void cluster_wait() { asm volatile("barrier.cluster.wait.acquire.aligned;" ::: "memory"); }
DEVI void fence_mbar_init() { asm volatile("fence.mbarrier_init.release.cluster;" ::: "memory"); }
DEVI void fence_proxy_async() { asm volatile("fence.proxy.async.shared::cta;" ::: "memory"); }
DEVI void tma_load_2d(uint32_t dst, const CUtensorMap* m, int c0, int c1, uint32_t bar) {
  asm volatile("cp.async.bulk.tensor.2d.shared::cluster.global.mbarrier::complete_tx::bytes [%0], [%1, {%3, %4}], [%2];"
    :: "r"(dst), "l"(m), "r"(bar), "r"(c0), "r"(c1) : "memory");
}
DEVI void tma_load_5d(uint32_t dst, const CUtensorMap* m, int c0, int c4, uint32_t bar) {
  asm volatile("cp.async.bulk.tensor.5d.shared::cluster.global.mbarrier::complete_tx::bytes [%0], [%1, {%3, %5, %5, %5, %4}], [%2];"
    :: "r"(dst), "l"(m), "r"(bar), "r"(c0), "r"(c4), "r"(0) : "memory");
}
DEVI void tma_prefetch_2d(const CUtensorMap* m, int c0, int c1) {
  asm volatile("cp.async.bulk.prefetch.tensor.2d.L2.global [%0, {%1, %2}];" :: "l"(m), "r"(c0), "r"(c1) : "memory");
}
DEVI void tma_prefetch_5d(const CUtensorMap* m, int c0, int c4) {
  asm volatile("cp.async.bulk.prefetch.tensor.5d.L2.global [%0, {%1, %3, %3, %3, %2}];" :: "l"(m), "r"(c0), "r"(c4), "r"(0) : "memory");
}
#define ELECT "{.reg .pred p; elect.sync _|p, 0xffffffff;\n @p "
DEVI void e_expect_tx(uint32_t bar, uint32_t bytes) { asm volatile(ELECT "mbarrier.arrive.expect_tx.shared::cta.b64 _, [%0], %1;}" :: "r"(bar), "r"(bytes) : "memory"); }
DEVI void e_arrive(uint32_t bar) { asm volatile(ELECT "mbarrier.arrive.shared::cta.b64 _, [%0];}" :: "r"(bar) : "memory"); }
DEVI void e_arrive_cl(uint32_t bar) { asm volatile(ELECT "mbarrier.arrive.shared::cluster.b64 _, [%0];}" :: "r"(bar) : "memory"); }
DEVI void e_tma_2d(uint32_t dst, const CUtensorMap* m, int c0, int c1, uint32_t bar) {
  asm volatile(ELECT "cp.async.bulk.tensor.2d.shared::cluster.global.mbarrier::complete_tx::bytes [%0], [%1, {%3, %4}], [%2];}"
    :: "r"(dst), "l"(m), "r"(bar), "r"(c0), "r"(c1) : "memory");
}
DEVI void e_tma_2d_mc(uint32_t dst, const CUtensorMap* m, int c0, int c1, uint32_t bar) {
  asm volatile(ELECT "cp.async.bulk.tensor.2d.shared::cluster.global.mbarrier::complete_tx::bytes.multicast::cluster [%0], [%1, {%3, %4}], [%2], %5;}"
    :: "r"(dst), "l"(m), "r"(bar), "r"(c0), "r"(c1), "h"((unsigned short)3) : "memory");
}
DEVI void e_st_async32(uint32_t a, uint32_t x, uint32_t bar) {
  asm volatile(ELECT "st.async.weak.shared::cluster.mbarrier::complete_tx::bytes.b32 [%0], %1, [%2];}" :: "r"(a), "r"(x), "r"(bar) : "memory");
}
DEVI void e_tma_store_2d(const CUtensorMap* m, uint32_t src, int c0, int c1) {
  asm volatile(ELECT "cp.async.bulk.tensor.2d.global.shared::cta.bulk_group [%0, {%2, %3}], [%1];}" :: "l"(m), "r"(src), "r"(c0), "r"(c1) : "memory");
}
DEVI void e_flag_add(int* p, int v = 1) {
  asm volatile("{.reg .pred p; elect.sync _|p, 0xffffffff;\n fence.proxy.async.global; @p red.release.gpu.global.add.s32 [%0], %1;}" :: "l"(p), "r"(v) : "memory");
}
DEVI int e_ticket(int* p) { int v = 0; asm volatile(ELECT "atom.relaxed.gpu.global.add.s32 %0, [%1], 1;}" : "+r"(v) : "l"(p) : "memory"); __syncwarp(); return v; }
DEVI int bcast(int v) { return __reduce_max_sync(0xffffffffu, v); }
DEVI int ld_relaxed(const int* p) { int v; asm volatile("ld.relaxed.gpu.global.s32 %0, [%1];" : "=r"(v) : "l"(p) : "memory"); return v; }
DEVI int ld_acquire(const int* p) { int v; asm volatile("ld.acquire.gpu.global.s32 %0, [%1];" : "=r"(v) : "l"(p) : "memory"); return __shfl_sync(0xffffffffu, v, 0); }
DEVI void e_tma_3d(uint32_t dst, const CUtensorMap* m, int c0, int c1, uint32_t bar) {
  asm volatile(ELECT "cp.async.bulk.tensor.3d.shared::cluster.global.mbarrier::complete_tx::bytes [%0], [%1, {%3, %4, %5}], [%2];}"
    :: "r"(dst), "l"(m), "r"(bar), "r"(c0), "r"(c1), "r"(0) : "memory");
}
DEVI void e_tma_5d(uint32_t dst, const CUtensorMap* m, int c0, int c4, uint32_t bar) {
  asm volatile(ELECT "cp.async.bulk.tensor.5d.shared::cluster.global.mbarrier::complete_tx::bytes [%0], [%1, {%3, %5, %5, %5, %4}], [%2];}"
    :: "r"(dst), "l"(m), "r"(bar), "r"(c0), "r"(c4), "r"(0) : "memory");
}
DEVI void e_bulk_g2s(uint32_t dst, const void* src, uint32_t bytes, uint32_t bar) {
  asm volatile(ELECT "cp.async.bulk.shared::cluster.global.mbarrier::complete_tx::bytes [%0], [%1], %2, [%3];}" :: "r"(dst), "l"(src), "r"(bytes), "r"(bar) : "memory");
}
DEVI void e_prefetch(const void* src, uint32_t bytes) {
  asm volatile(ELECT "cp.async.bulk.prefetch.L2.global [%0], %1;}" :: "l"(src), "r"(bytes) : "memory");
}
DEVI void bulk_commit() { asm volatile("cp.async.bulk.commit_group;" ::: "memory"); }
template<int N> DEVI void bulk_wait_read() { asm volatile("cp.async.bulk.wait_group.read %0;" :: "n"(N) : "memory"); }
template<int N> DEVI void bulk_wait() { asm volatile("cp.async.bulk.wait_group %0;" :: "n"(N) : "memory"); }
template<int ID, int N> DEVI void nbar_sync() { asm volatile("bar.sync %0, %1;" :: "n"(ID), "n"(N) : "memory"); }
template<int ID, int N> DEVI void nbar_arrive() { asm volatile("bar.arrive %0, %1;" :: "n"(ID), "n"(N) : "memory"); }
DEVI void nbar_sync_r(int id, int n) { asm volatile("bar.sync %0, %1;" :: "r"(id), "r"(n) : "memory"); }
DEVI void nbar_arrive_r(int id, int n) { asm volatile("bar.arrive %0, %1;" :: "r"(id), "r"(n) : "memory"); }
template<int R> DEVI void reg_inc() { asm volatile("setmaxnreg.inc.sync.aligned.u32 %0;" :: "n"(R)); }
template<int R> DEVI void reg_dec() { asm volatile("setmaxnreg.dec.sync.aligned.u32 %0;" :: "n"(R)); }
DEVI void wg_fence() { asm volatile("wgmma.fence.sync.aligned;" ::: "memory"); }
DEVI void wg_commit() { asm volatile("wgmma.commit_group.sync.aligned;" ::: "memory"); }
template<int N> DEVI void wg_wait() { asm volatile("wgmma.wait_group.sync.aligned %0;" :: "n"(N) : "memory"); }
DEVI uint32_t pack_bf16(float lo, float hi) { uint32_t r; asm("cvt.rn.bf16x2.f32 %0, %1, %2;" : "=r"(r) : "f"(hi), "f"(lo)); return r; }
DEVI float bf_lo(uint32_t v) { return __uint_as_float(v << 16); }
DEVI float bf_hi(uint32_t v) { return __uint_as_float(v & 0xffff0000u); }
DEVI uint32_t movmat(uint32_t a) { uint32_t r; asm volatile("movmatrix.sync.aligned.m8n8.trans.b16 %0, %1;" : "=r"(r) : "r"(a)); return r; }
DEVI void ldsm4(uint32_t addr, uint32_t& r0, uint32_t& r1, uint32_t& r2, uint32_t& r3) {
  asm volatile("ldmatrix.sync.aligned.m8n8.x4.shared.b16 {%0,%1,%2,%3}, [%4];" : "=r"(r0), "=r"(r1), "=r"(r2), "=r"(r3) : "r"(addr) : "memory");
}
DEVI void ldsm4t(uint32_t addr, uint32_t& r0, uint32_t& r1, uint32_t& r2, uint32_t& r3) {
  asm volatile("ldmatrix.sync.aligned.m8n8.x4.trans.shared.b16 {%0,%1,%2,%3}, [%4];" : "=r"(r0), "=r"(r1), "=r"(r2), "=r"(r3) : "r"(addr) : "memory");
}
DEVI void stsm4(uint32_t addr, uint32_t r0, uint32_t r1, uint32_t r2, uint32_t r3) {
  asm volatile("stmatrix.sync.aligned.m8n8.x4.shared.b16 [%0], {%1,%2,%3,%4};" :: "r"(addr), "r"(r0), "r"(r1), "r"(r2), "r"(r3) : "memory");
}
DEVI uint32_t lds32v(uint32_t a) { uint32_t v; asm volatile("ld.volatile.shared.u32 %0, [%1];" : "=r"(v) : "r"(a) : "memory"); return v; }
DEVI void sts32v(uint32_t a, uint32_t v) { asm volatile("st.volatile.shared.u32 [%0], %1;" :: "r"(a), "r"(v) : "memory"); }
DEVI void st_async128(uint32_t a, uint32_t x, uint32_t y, uint32_t z, uint32_t w, uint32_t bar) {
  asm volatile("st.async.weak.shared::cluster.mbarrier::complete_tx::bytes.v4.b32 [%0], {%1,%2,%3,%4}, [%5];" :: "r"(a), "r"(x), "r"(y), "r"(z), "r"(w), "r"(bar) : "memory");
}
DEVI void st_async32(uint32_t a, uint32_t x, uint32_t bar) {
  asm volatile("st.async.weak.shared::cluster.mbarrier::complete_tx::bytes.b32 [%0], %1, [%2];" :: "r"(a), "r"(x), "r"(bar) : "memory");
}
DEVI void st_cl128(bool own, uint32_t a, uint32_t x, uint32_t y, uint32_t z, uint32_t w, uint32_t bar) {
  asm volatile("{.reg .pred p; setp.ne.u32 p, %6, 0; @p st.shared.v4.b32 [%0], {%1,%2,%3,%4};\n"
               "@!p st.async.weak.shared::cluster.mbarrier::complete_tx::bytes.v4.b32 [%0], {%1,%2,%3,%4}, [%5];}"
               :: "r"(a), "r"(x), "r"(y), "r"(z), "r"(w), "r"(bar), "r"((uint32_t)own) : "memory");
}
DEVI void st_cl32(bool own, uint32_t a, uint32_t x, uint32_t bar) {
  asm volatile("{.reg .pred p; setp.ne.u32 p, %3, 0; @p st.shared.b32 [%0], %1;\n"
               "@!p st.async.weak.shared::cluster.mbarrier::complete_tx::bytes.b32 [%0], %1, [%2];}" :: "r"(a), "r"(x), "r"(bar), "r"((uint32_t)own) : "memory");
}
DEVI uint4 ldg_rlx128(const void* p) {
  uint4 v;
  asm volatile("ld.relaxed.gpu.global.v4.b32 {%0,%1,%2,%3}, [%4];" : "=r"(v.x), "=r"(v.y), "=r"(v.z), "=r"(v.w) : "l"(p) : "memory");
  return v;
}
DEVI void stg_rlx128(void* p, uint32_t x, uint32_t y, uint32_t z, uint32_t w) {
  asm volatile("st.relaxed.gpu.global.v4.b32 [%0], {%1,%2,%3,%4};" :: "l"(p), "r"(x), "r"(y), "r"(z), "r"(w) : "memory");
}
DEVI void stg128(void* p, uint32_t x, uint32_t y, uint32_t z, uint32_t w) {
  asm volatile("st.global.v4.b32 [%0], {%1,%2,%3,%4};" :: "l"(p), "r"(x), "r"(y), "r"(z), "r"(w) : "memory");
}
DEVI void stg_rlx32(void* p, uint32_t x) { asm volatile("st.relaxed.gpu.global.b32 [%0], %1;" :: "l"(p), "r"(x) : "memory"); }
DEVI uint32_t clock32() { uint32_t c; asm volatile("mov.u32 %0, %%clock;" : "=r"(c) :: "memory"); return c; }
DEVI uint32_t gtime() { uint32_t c; asm volatile("mov.u32 %0, %%globaltimer_lo;" : "=r"(c) :: "memory"); return c; }
DEVI void wait_time(uint32_t t, int& budget) { while ((int)(gtime() - t) < 0 && --budget > 0) {} }
DEVI uint2 ldg_rlx64(const void* p) { uint2 v; asm volatile("ld.relaxed.gpu.global.v2.b32 {%0,%1}, [%2];" : "=r"(v.x), "=r"(v.y) : "l"(p) : "memory"); return v; }
DEVI void sts16(uint32_t a, uint32_t x) { asm volatile("st.shared.b16 [%0], %1;" :: "r"(a), "h"((unsigned short)x) : "memory"); }
DEVI void sts128(uint32_t a, uint32_t x) { asm volatile("st.shared.v4.b32 [%0], {%1,%1,%1,%1};" :: "r"(a), "r"(x) : "memory"); }
DEVI void arrive_if_eq(uint32_t bar, int a, int b) { asm volatile("{.reg .pred p; setp.eq.s32 p, %1, %2; @p mbarrier.arrive.shared::cta.b64 _, [%0];}" :: "r"(bar), "r"(a), "r"(b) : "memory"); }
DEVI void arrive_cl_if_eq(uint32_t bar, int a, int b) { asm volatile("{.reg .pred p; setp.eq.s32 p, %1, %2; @p mbarrier.arrive.shared::cluster.b64 _, [%0];}" :: "r"(bar), "r"(a), "r"(b) : "memory"); }
template<int ID, int N> DEVI bool nbar_or(bool x) {
  uint32_t r;
  asm volatile("{.reg .pred p, q; setp.ne.u32 p, %1, 0; bar.red.or.pred q, %2, %3, p; selp.u32 %0, 1, 0, q;}" : "=r"(r) : "r"((uint32_t)x), "n"(ID), "n"(N) : "memory");
  return __any_sync(0xffffffffu, r);
}
DEVI void spin_until(uint32_t t0, int d) { while ((int)(clock32() - t0) < d) {} }
DEVI void flag_wait(const int* p, int n, int& budget) {
  while (ld_acquire(p) < n && --budget > 0) __nanosleep(32);
  asm volatile("fence.proxy.async.global;" ::: "memory");
}

#define F4(C, o)  C(d[o+0]), C(d[o+1]), C(d[o+2]), C(d[o+3])
#define F8(C, o)  F4(C, o), F4(C, o+4)
#define F32(C, o) F8(C, o), F8(C, o+8), F8(C, o+16), F8(C, o+24)
#define R4  "{%0,%1,%2,%3}"
#define R8  "{%0,%1,%2,%3,%4,%5,%6,%7}"
#define R20 "{%0,%1,%2,%3,%4,%5,%6,%7,%8,%9,%10,%11,%12,%13,%14,%15,%16,%17,%18,%19}"
#define R32 "{%0,%1,%2,%3,%4,%5,%6,%7,%8,%9,%10,%11,%12,%13,%14,%15,%16,%17,%18,%19,%20,%21,%22,%23,%24,%25,%26,%27,%28,%29,%30,%31}"
#define R64 "{%0,%1,%2,%3,%4,%5,%6,%7,%8,%9,%10,%11,%12,%13,%14,%15,%16,%17,%18,%19,%20,%21,%22,%23,%24,%25,%26,%27,%28,%29,%30,%31," \
  "%32,%33,%34,%35,%36,%37,%38,%39,%40,%41,%42,%43,%44,%45,%46,%47,%48,%49,%50,%51,%52,%53,%54,%55,%56,%57,%58,%59,%60,%61,%62,%63}"
template<uint32_t OFF, uint32_t LBO, uint32_t SBO, uint32_t SW, int T> struct Op {
  static constexpr uint32_t lo = (OFF >> 4) | ((LBO >> 4) << 16), hi = (SBO >> 4) | (SW << 30);
  static constexpr int t = T;
};
DEVI uint32_t desc_base(uint32_t addr) { return (addr & 0x3FFFF) >> 4; }
#define RS_ASM(SHAPE, REGS, A0, A1, A2, A3, B, LO, HI, T, SD) \
  "{.reg .b64 tb; .reg .b32 lb; add.u32 lb, " B ", " LO "; mov.b64 tb, {lb, " HI "};\n" \
  "wgmma.mma_async.sync.aligned." SHAPE ".f32.bf16.bf16 " REGS ", {" A0 "," A1 "," A2 "," A3 "}, tb, " SD ", 1, 1, " T ";}"
#define WG_RS(NAME, SHAPE, REGS, LIST, ...) \
  template<int ACC, class OB> DEVI void NAME(float* d, const uint32_t* a, uint32_t b) { \
    if (ACC) asm volatile(RS_ASM(SHAPE, REGS, __VA_ARGS__) \
      : LIST("+f") : "r"(a[0]), "r"(a[1]), "r"(a[2]), "r"(a[3]), "r"(b), "n"(OB::lo), "n"(OB::hi), "n"(OB::t), "n"(ACC & 1)); \
    else asm volatile(RS_ASM(SHAPE, REGS, __VA_ARGS__) \
      : LIST("=f") : "r"(a[0]), "r"(a[1]), "r"(a[2]), "r"(a[3]), "r"(b), "n"(OB::lo), "n"(OB::hi), "n"(OB::t), "n"(0)); \
  }
#define SS_ASM(SHAPE, REGS, A, B, LA, HA, TA, LB, HB, TB, SD) \
  "{.reg .b64 ta, tb; .reg .b32 la, lb; add.u32 la, " A ", " LA "; mov.b64 ta, {la, " HA "}; add.u32 lb, " B ", " LB "; mov.b64 tb, {lb, " HB "};\n" \
  "wgmma.mma_async.sync.aligned." SHAPE ".f32.bf16.bf16 " REGS ", ta, tb, " SD ", 1, 1, " TA ", " TB ";}"
#define WG_SS(NAME, SHAPE, REGS, LIST, ...) \
  template<int ACC, class OA, class OB> DEVI void NAME(float* d, uint32_t a, uint32_t b) { \
    if (ACC) asm volatile(SS_ASM(SHAPE, REGS, __VA_ARGS__) \
      : LIST("+f") : "r"(a), "r"(b), "n"(OA::lo), "n"(OA::hi), "n"(OA::t), "n"(OB::lo), "n"(OB::hi), "n"(OB::t), "n"(ACC & 1)); \
    else asm volatile(SS_ASM(SHAPE, REGS, __VA_ARGS__) \
      : LIST("=f") : "r"(a), "r"(b), "n"(OA::lo), "n"(OA::hi), "n"(OA::t), "n"(OB::lo), "n"(OB::hi), "n"(OB::t), "n"(0)); \
  }
#define L4(C)  F4(C, 0)
#define L8(C)  F8(C, 0)
#define L20(C) F8(C, 0), F8(C, 8), F4(C, 16)
#define L32(C) F32(C, 0)
WG_RS(wg_rs8, "m64n8k16", R4, L4, "%4", "%5", "%6", "%7", "%8", "%9", "%10", "%11", "%12")
WG_RS(wg_rs16, "m64n16k16", R8, L8, "%8", "%9", "%10", "%11", "%12", "%13", "%14", "%15", "%16")
WG_RS(wg_rs64, "m64n64k16", R32, L32, "%32", "%33", "%34", "%35", "%36", "%37", "%38", "%39", "%40")
WG_SS(wg_ss8, "m64n8k16", R4, L4, "%4", "%5", "%6", "%7", "%8", "%9", "%10", "%11", "%12")
WG_SS(wg_ss16, "m64n16k16", R8, L8, "%8", "%9", "%10", "%11", "%12", "%13", "%14", "%15", "%16")
WG_SS(wg_ss40, "m64n40k16", R20, L20, "%20", "%21", "%22", "%23", "%24", "%25", "%26", "%27", "%28")
WG_SS(wg_ss64, "m64n64k16", R32, L32, "%32", "%33", "%34", "%35", "%36", "%37", "%38", "%39", "%40")
#define L64(C) F32(C, 0), F32(C, 32)
WG_SS(wg_ss128, "m64n128k16", R64, L64, "%64", "%65", "%66", "%67", "%68", "%69", "%70", "%71", "%72")
template<int I> struct IC { __host__ __device__ constexpr operator int() const { return I; } };
template<int I, int N, class F> DEVI void sfor(F&& f) {
  if constexpr (I < N) { f(IC<I>{}); sfor<I + 1, N>(f); }
}

#define R_CL 6
namespace rec {
constexpr int NHI = 36, NLO = 5, NRS = NHI + NLO, NSS = 64 - NRS;
constexpr uint32_t WS = 0;
constexpr uint32_t WO = 2 * NSS * 2048;
constexpr uint32_t RING = WO + 65536;
constexpr uint32_t QB = RING + 40960, RG = 2080, POSQ = 0x64210, POSK = 0xB9753, POSV = 0xEDCA8;
#define JA 2
constexpr uint32_t WA = QB;
constexpr uint32_t OM = QB + 9 * RG, OMS = 2 * RG;
constexpr uint32_t OM2 = QB + 16384, OM2S = 2048;
constexpr uint32_t WH = QB + 20480;
constexpr uint32_t B_PART = QB + 15 * RG - 32;
constexpr uint32_t PM0 = QB + 16384, PM1 = QB + 15 * RG, PM2 = PM1 + 256;
constexpr uint32_t BARS = PM2 + 128;
constexpr uint32_t B_FULL = BARS, B_EMPTY = BARS + 40, B_MLAND = BARS + 80, B_QK = BARS + 112, B_V = BARS + 120, B_OM = BARS + 128,
                   B_WA = BARS + 136, B_SDONE = BARS + 144, B_BFREE = BARS + 152, B_W1 = PM1, B_W2 = PM1 + 8, B_WO = PM1 + 16;
constexpr uint32_t SMEM = BARS + 160;
static_assert(SMEM <= 232448 && QB % 1024 == 0, "smem map");
constexpr int R1 = (PM1 - WO) / 4096;
constexpr int NB_WO = 1, NB_ST = 2, NB_P = 3, NB_TR = 4, NB_X = 5, NB_G = 6, NB_G1 = 7, NB_G2 = 8, NB_G4 = 9, NB_S = 10;
__host__ __device__ constexpr bool is_lo(int j) { return j % 12 == 8; }
__host__ __device__ constexpr int lo_before(int j) { return (j + 3) / 12; }
__host__ __device__ constexpr int ss_before(int j) { return (j - lo_before(j)) * NSS / (64 - NLO); }
__host__ __device__ constexpr bool is_ss(int j) { return ss_before(j + 1) != ss_before(j); }
__host__ __device__ constexpr int reg_idx(int j) { return is_lo(j) ? NHI + lo_before(j) : j - ss_before(j) - lo_before(j); }
#define LOQ(i) ((0x12010 >> (4 * (i))) & 3)
template<int j> using OpW = Op<WS + ss_before(j) * 2048, 16, 1024, 1, 1>;
#define P_G1 1
#define P_G2 2
#define P_G2L 0
#define P_OS 1
#define P_NA 4
#define P_G4 10
#define P_G5 11
#define TUN(i, v) (v)
}
#define PROFW(wq, i)
DEVI uint32_t mapr(int h, uint32_t addr, int rank) { return mapa(addr, rank + (R_CL == 6 ? (h & 1) * 3 : 0)); }
template<int N> DEVI void pin(float* d) {
#pragma unroll
  for (int i = 0; i < N; i++) asm volatile("" : "+f"(d[i]) :: "memory");
}
DEVI void keep(const void* a) { asm volatile("{.reg .pred p; setp.eq.u64 p, %0, 0; vote.sync.any.pred p, p, 0xffffffff; @p exit;}" :: "l"(a) : "memory"); }
DEVI int lane_reg() { return __shfl_sync(0xffffffffu, threadIdx.x & 31, threadIdx.x & 31); }
#define LANE_NOW [[maybe_unused]] const int lane = lane0 + ((uint32_t)budget >> 30), g = lane >> 2, c = lane & 3

DEVI void rec_proj(const uint32_t sb, const int h, const int rank, const int w, const CUtensorMap* mW, const CUtensorMap* mWo, const uint32_t zero) {
  using namespace rec;
  const int lane0 = lane_reg(), wg = w >> 2, ww = w & 3;
  int budget = SPIN_BUDGET;
  uint32_t wr[NRS * 4];
  {
    LANE_NOW;
    const uint32_t wsw = ((lane & 7) + (lane >> 4) * 8) * 128 + (((ww * 2 + ((lane >> 3) & 1)) ^ (lane & 7)) << 4);
    mbar_wait(sb + B_W1, 0, budget);
#pragma unroll
    for (int r = 0; r < R1; r++) ldsm4t(sb + WO + (wg * R1 + r) * 2048 + wsw, wr[4*r], wr[4*r+1], wr[4*r+2], wr[4*r+3]);
    fence_proxy_async();
    nbar_sync<NB_ST, 256>();
    if (w == 0) {
      if (lane == 0) { mbar_expect_tx(sb + B_W2, (NRS - R1) * 4096); mbar_expect_tx(sb + B_WO, rank == 2 ? 65536 + 16384 + 8192 : 65536); }
      __syncwarp();
      for (int i = lane; i < 128; i += 32) {
        const int j = i & 63, t = i >> 6, r = reg_idx(j);
        if (!is_ss(j) && r >= R1) tma_load_2d(sb + RING + (t * (NRS - R1) + r - R1) * 2048, mW, h * DH + t * 64, j * 16, sb + B_W2);
      }
      const int t0 = (rank + 1) % 3;
      if (lane < 8) tma_load_2d(sb + WO + lane * 8192, mWo, (3 * ((lane >> 1) + (lane >> 1 >= JA)) + t0) * 64, h * DH + (lane & 1) * 64, sb + B_WO);
      else if (rank == 2 && lane < 11) tma_load_2d(lane < 10 ? sb + WA + (lane - 8) * 8192 : sb + WH, mWo, lane < 10 ? 3 * JA * 64 : 15 * 64, h * DH + (lane > 8) * 64, sb + B_WO);
    }
    mbar_wait(sb + B_W2, 0, budget);
#pragma unroll
    for (int r = R1; r < NRS; r++) ldsm4t(sb + RING + (wg * (NRS - R1) + r - R1) * 2048 + wsw, wr[4*r], wr[4*r+1], wr[4*r+2], wr[4*r+3]);
    fence_proxy_async();
    cluster_arrive(); cluster_wait();
  }
  const uint32_t d0 = desc_base(sb), da = d0 + wg * (NSS * 128);
  const uint32_t pos = rank == 0 ? POSQ : rank == 1 ? POSK : POSV, bar = rank == 2 ? B_V : B_QK;
  uint32_t stg[3][4] = {}, pk[16] = {};
  auto stage = [&](uint32_t* t, int r) {
#pragma unroll
    for (int i = 0; i < 4; i++) asm volatile("xor.b32 %0, %1, %2;" : "+r"(t[i]) : "r"(wr[4 * r + i]), "r"(zero));
  };
#pragma unroll 1
  for (int s = -1; s < NSTEP; s++) {
    if (s >= 0) {
      float d[8];
      sfor<0, 4>([&](auto Q) {
        constexpr int q = Q;
        sfor<lo_before(16 * q), lo_before(16 * q + 16)>([&](auto I) { constexpr int i = I; stage(stg[LOQ(i)], NHI + i); });
        mbar_wait(sb + B_FULL + 8 * q, 0, budget);
        if (q == 0) PROFW(0, 16);
        wg_fence();
        sfor<16 * q, 16 * q + 16>([&](auto J) {
          constexpr int j = J;
          typedef Op<RING + j * 512, 256, 128, 0, 1> OB;
          if constexpr (is_ss(j)) wg_ss16<j != 0, OpW<j>, OB>(d, da, d0);
          else wg_rs16<j != 0, OB>(d, is_lo(j) ? stg[LOQ(lo_before(j))] : wr + 4 * reg_idx(j), d0);
        });
        wg_commit();
        if (q == 0 && s > 0) mbar_wait(sb + B_BFREE, (s & 1) ^ 1, budget);
        sfor<q ? q + 1 : 0, q < 3 ? q + 2 : 0>([&](auto N) {
          constexpr int n = N;
          LANE_NOW;
          const uint32_t r = mapr(h, sb, n >> 1);
          uint32_t t[4];
#pragma unroll
          for (int i = 0; i < 4; i++) { if (n == 0) t[i] = pk[i]; else asm volatile("xor.b32 %0, %1, %2;" : "=r"(t[i]) : "r"(pk[4*n+i]), "r"(zero)); }
          st_cl128(rank == n >> 1, r + QB + ((pos >> (4 + 4 * c)) & 15) * RG + w * 256 + (n & 1) * 128 + g * 16, t[0], t[1], t[2], t[3], r + bar);
        });
        if constexpr (q > 0) {
          wg_wait<1>();
          arrive_if_eq(sb + B_EMPTY + 8 * (q - 1), lane0, ww * 32);
        }
      });
      LANE_NOW;
      const uint32_t dst = QB + (pos & 15) * RG + w * 256 + lane * 4;
      wg_wait<0>();
      pin<8>(d);
      {
        const uint32_t x0 = pack_bf16(d[0], d[1]), x1 = pack_bf16(d[2], d[3]), y0 = pack_bf16(d[4], d[5]), y1 = pack_bf16(d[6], d[7]);
        const uint32_t r = mapr(h, sb, rank == 0);
        if (rank < 2) { sts32v(sb + dst, rank ? y0 : x0); sts32v(sb + dst + 128, rank ? y1 : x1); fence_proxy_async(); }
        st_async32(r + dst, rank ? x0 : y0, r + bar); st_async32(r + dst + 128, rank ? x1 : y1, r + bar);
        if (rank < 2) e_arrive(sb + B_QK);
        else { const uint32_t r1 = mapr(h, sb, 1); st_async32(r1 + dst, y0, r1 + bar); st_async32(r1 + dst + 128, y1, r1 + bar); }
      }
      PROFW(0, 17);
      if (s == NSTEP - 1) break;
      arrive_if_eq(sb + B_EMPTY + 24, lane0, ww * 32);
    } else e_arrive(sb + B_EMPTY + 8 * ww);
    float d[32];
    const bool gate = rank < 2 && s >= 0;
    sfor<0, 16>([&](auto C) {
      constexpr int cc = C, sl = (cc + 4) % 5;
      if constexpr (cc == 0) mbar_wait(sb + B_FULL + 8 * sl, 0, budget);
      if constexpr (cc == P_G1) { if (gate) nbar_sync<NB_G1, 384>(); }
      if constexpr (cc == P_G2) { if (gate) nbar_sync<NB_G2, 384>(); }
      if constexpr (cc == P_NA) {
        PROFW(0, 18);
        nbar_sync<NB_WO, 384>();
      }
      if constexpr (cc == P_G4 || cc == P_G5) { if (gate && cc == (rank ? P_G5 : P_G4)) nbar_sync<NB_G4, 384>(); }
      wg_fence();
      sfor<0, 4>([&](auto I) {
        constexpr int i = I, j = cc * 4 + i;
        typedef Op<RING + sl * 8192 + i * 32, 16, 1024, 1, 0> OB;
        if constexpr (is_ss(j)) wg_ss64<j != 0, OpW<j>, OB>(d, da, d0);
        else wg_rs64<j != 0, OB>(d, is_lo(j) ? stg[0] : wr + 4 * reg_idx(j), d0);
      });
      wg_commit();
      if constexpr (cc == P_NA) PROFW(0, 19);
      if constexpr (cc < 15) {
        if constexpr (is_lo(cc * 4 + 4)) stage(stg[0], reg_idx(cc * 4 + 4));
        mbar_wait(sb + B_FULL + 8 * ((sl + 1) % 5), ((cc + 5) / 5) & 1, budget);
      }
      wg_wait<0>();
      arrive_if_eq(sb + B_EMPTY + 8 * sl, lane0, ww * 32);
    });
    pin<32>(d);
    PROFW(0, 20);
#pragma unroll
    for (int i = 0; i < 16; i++) pk[i] = pack_bf16(d[16 * (i >> 3) + 4 * (i & 3) + ((i >> 1) & 2)], d[16 * (i >> 3) + 4 * (i & 3) + ((i >> 1) & 2) + 1]);
  }
}

DEVI float softmax_row(float* v, uint32_t* p) {
  constexpr float SC = 0.08838834764831845f * 1.4426950408889634f;
  float m = fmaxf(fmaxf(fmaxf(fmaxf(v[0], v[1]), fmaxf(v[2], v[3])), fmaxf(fmaxf(v[4], v[5]), fmaxf(v[6], v[7]))), fmaxf(v[8], v[9]));
  m = fmaxf(m, __shfl_xor_sync(0xffffffffu, m, 1));
  m = fmaxf(m, __shfl_xor_sync(0xffffffffu, m, 2));
  const float ms = -m * SC, mh = fmaf(m, -SC, -1.f);
#pragma unroll
  for (int i = 0; i < 10; i++) asm("ex2.approx.ftz.f32 %0, %1;" : "=f"(v[i]) : "f"(fmaf(v[i], SC, i < 8 ? ms : mh)));
#pragma unroll
  for (int n = 0; n < 5; n++) p[n] = pack_bf16(v[2*n], v[2*n+1]);
  return fmaf(v[8] + v[9], 2.f, ((v[0] + v[1]) + (v[2] + v[3])) + ((v[4] + v[5]) + (v[6] + v[7])));
}

template<bool ATT>
DEVI void rec_attn(const uint32_t sb, int h, int rank, int w, const bf16* __restrict__ Wo, const bf16* __restrict__ mem0) {
  using namespace rec;
  const int lane0 = lane_reg();
  int budget = SPIN_BUDGET;
  constexpr int NT = ATT ? 5 : 6;
  uint32_t wl[16];
  if (!ATT) {
    LANE_NOW;
#pragma unroll
    for (int i = 0; i < 16; i++) {
      const int dh = 8 * (i >> 1) + 2 * c;
      const unsigned short* p = (const unsigned short*)Wo + (size_t)(h * DH + dh) * DM + 15 * 64 + 16 * w + 8 * (i & 1) + g;
      wl[i] = p[0] | (uint32_t)p[DM] << 16;
    }
  }
  mbar_wait(sb + B_WO, 0, budget);
  cluster_arrive(); cluster_wait();
  const uint32_t d0 = desc_base(sb);
  uint32_t pph = 0;
#pragma unroll 1
  for (int s = -1; s < NSTEP; s++) {
    asm volatile("" : "+r"(h), "+r"(rank), "+r"(w));
    const uint32_t sp = s & 1;
    const int t0 = ATT ? rank + 1 : 0;
    const bool more = s + 1 < NSTEP;
    float hold[10] = {0, 0, 0, 0, 0, 0, 0, 0, 0, 0};
    if (ATT && s >= 0) {
      float sc[20];
      LANE_NOW;
      mbar_wait(sb + B_QK, sp, budget);
      PROFW(0, 1);
      fence_proxy_async();
      wg_fence();
      sfor<0, 8>([&](auto K) { constexpr int k = K; wg_ss40<k != 0, Op<QB + k * 256, 128, RG, 0, 1>, Op<QB + 3 * RG + k * 256, 128, 2 * RG, 0, 1>>(sc, d0, d0); });
      wg_commit();
      if (P_G1 < 16 && more) nbar_arrive<NB_G1, 384>();
      mbar_wait(sb + B_V, sp, budget);
      wg_wait<0>();
      pin<20>(sc);
      if (w == 3 && more) nbar_arrive<NB_S, 64>();
      PROFW(1, 2);
      if (w == 0) {
        uint32_t p[5];
        float v[10];
#pragma unroll
        for (int i = 0; i < 10; i++) v[i] = sc[4 * (i >> 1) + (i & 1)];
        softmax_row(v, p);
        const uint32_t a = sb + lane * 4;
        sts32v(a + PM0, p[0]); sts32v(a + PM0 + 128, p[1]); sts32v(a + PM1, p[2]); sts32v(a + PM1 + 128, p[3]); sts32v(a + PM2, p[4]);
      }
      if (more) {
        float rs[4], ot[2][4];
        uint32_t one[4];
#pragma unroll
        for (int i = 0; i < 4; i++) one[i] = 0x3F803F80u + ((uint32_t)budget >> (31 - i));
        typedef Op<PM0, 128, 128, 0, 0> P0; typedef Op<PM1, 128, 128, 0, 0> P1; typedef Op<PM2, 0, 128, 0, 0> P2;
        fence_proxy_async();
        nbar_sync<NB_P, 128>();
        PROFW(0, 3);
        wg_fence();
        wg_rs8<0, P0>(rs, one, d0); wg_rs8<1, P1>(rs, one, d0); wg_rs8<1, P2>(rs, one, d0);
        wg_commit();
        sfor<0, 2>([&](auto T) {
          constexpr int t = T;
          wg_ss8<0, Op<QB + 8 * RG + t * 1024, 2 * RG, 128, 0, 0>, P0>(ot[t], d0, d0);
          wg_ss8<1, Op<QB + 12 * RG + t * 1024, RG, 128, 0, 0>, P1>(ot[t], d0, d0);
          wg_ss8<1, Op<QB + 14 * RG + t * 1024, 0, 128, 0, 0>, P2>(ot[t], d0, d0);
        });
        wg_commit();
        if (P_G2 < 16 && !P_G2L) nbar_arrive<NB_G2, 384>();
        const uint32_t oa = w * 256 + lane * 4, r1 = mapr(h, sb, rank ^ 1), r2 = mapr(h, sb, 2);
        mbar_wait(sb + B_SDONE, sp, budget);
        wg_wait<1>();
        pin<4>(rs);
        float i0, i1;
        asm volatile("rcp.approx.ftz.f32 %0, %1;" : "=f"(i0) : "f"(rs[0]));
        asm volatile("rcp.approx.ftz.f32 %0, %1;" : "=f"(i1) : "f"(rs[1]));
        wg_wait<0>();
        pin<4>(ot[0]); pin<4>(ot[1]);
        uint32_t x[4];
#pragma unroll
        for (int j = 0; j < 4; j++) {
          x[j] = pack_bf16(ot[j >> 1][2 * (j & 1)] * i0, ot[j >> 1][2 * (j & 1) + 1] * i1);
          sts32v(sb + OM + rank * OMS + oa + (j >> 1) * 1024 + (j & 1) * 128, x[j]);
        }
        fence_proxy_async();
#pragma unroll
        for (int j = 0; j < 8; j++) {
          const int i = P_OS ? j >> 1 : j & 3;
          if (P_OS ? j & 1 : j >> 2) st_async32(r1 + OM + rank * OMS + oa + (i >> 1) * 1024 + (i & 1) * 128, x[i], r1 + B_OM);
          else st_async32(r2 + OM2 + rank * OM2S + oa + (i >> 1) * 1024 + (i & 1) * 128, x[i], r2 + B_OM);
        }
        e_arrive(sb + B_OM);
        if (P_G2 < 16 && P_G2L) nbar_arrive<NB_G2, 384>();
        PROFW(0, 4);
      }
#pragma unroll
      for (int i = 0; i < 10; i++) hold[i] = w ? sc[4 * (i >> 1) + (i & 1)] : sc[4 * (i >> 1) + 2 + (i & 1)];
    }
    if (more && s >= 0) {
      LANE_NOW;
      char* const pw = (char*)g_part + (uint32_t)((t0 * 16 + w * 4 + (lane >> 3)) * 4096 + h * 128 + ((lane ^ h) & 7) * 16);
      mbar_wait(sb + B_OM, sp, budget);
      if (w == 0) nbar_arrive<NB_G, 128>();
      PROFW(1, 5);
      if (!ATT) fence_proxy_async();
      float acc[3][8];
      sfor<0, NT + 1>([&](auto J) {
        constexpr int j = J;
        if constexpr (j < NT) {
          if constexpr (ATT && j == JA) { mbar_wait(sb + B_WA, sp, budget); PROFW(2, 0); }
          wg_fence();
          sfor<0, 8>([&](auto K) {
            constexpr int k = K;
            typedef Op<(ATT ? OM : OM2) + k * 256, 128, ATT ? OMS : OM2S, 0, 1> OB;
            if constexpr (j == 5 && k < 4) wg_rs16<k ? 1 : 2, OB>(acc[j % 3], wl + 4 * k, d0);
            else wg_ss16<k ? 1 : j < 3 ? 0 : 2, Op<(j == JA ? WA : j < 5 ? WO + (j - (j > JA)) * 16384 : WH - 8192) + k * 2048, 16, 1024, 1, 1>, OB>(acc[j % 3], d0, d0);
          });
          wg_commit();
          if constexpr (j == 0) { if (w == 3) e_expect_tx(sb + B_OM, ATT ? 2048 : 4096); }
          if constexpr (j == NT - 1) nbar_arrive<NB_WO, 384>();
        }
        if constexpr (j > 0) {
          if constexpr (j < NT) wg_wait<1>(); else wg_wait<0>();
          float* d = acc[(j - 1) % 3];
          pin<8>(d);
          uint32_t x[4];
#pragma unroll
          for (int i = 0; i < 4; i++) { const uint32_t m = (h >> 3) == i; x[i] = (pack_bf16(d[2*i], d[2*i+1]) & ~m) | (m & ~sp); }
          stg_rlx128(pw + (j - 1) * (48 * 4096), x[0], x[1], x[2], x[3]);
          if constexpr (ATT && j == JA + 1) nbar_arrive<NB_TR, 160>();
          if constexpr (j == 3) PROFW(3, 26);
        }
      });
    } else if (more) nbar_arrive<NB_WO, 384>();
    PROFW(0, 6);
    asm volatile("" : "+r"(h), "+r"(rank), "+r"(w));
    if (ATT) {
      LANE_NOW;
      const int lim = 8 * (g >> 1) + (g & 1) + 2 * w - 8 * c;
      uint32_t p[5];
#pragma unroll
      for (int i = 0; i < 8; i++) hold[2+i] = i <= lim ? hold[2+i] : -INFINITY;
      if (w == 3 && lane < 14) sts128(sb + PM1 + lane * 16, (lane >> 1) == 3 ? 0x3F803F80u : 0);
      const float psum = softmax_row(hold, p);
#pragma unroll
      for (int i = 0; i < 5; i++) hold[i] = __uint_as_float(p[i]);
      hold[5] = psum;
      pin<6>(hold);
    }
    if (ATT && more) {
      LANE_NOW;
      const int blk = rank * 32 + h;
      char* const mw = (char*)g_mem + (uint32_t)(sp * 32768 + blk * 512 + w * 128 + lane * 4);
      const bool start = s == -1 || (s == LAG - 1 && (w & 1));
      uint32_t v = 0;
      if (start) {
        const unsigned short* q = (const unsigned short*)mem0 + c * 2 * DM + blk * 16 + (w >> 1) * 8 + g;
        v = q[0] | (uint32_t)q[DM] << 16;
        if (v == 0) v = 0x8000u;
      }
      keep(mw);
      if (s >= 0) {
        fence_proxy_async();
        nbar_sync<NB_P, 128>();
        const uint32_t ca = sb + WA + lane * 128 + (((2 * w) ^ lane) & 7) * 16 + (lane >> 3) * 4;
        const uint32_t sa = sb + OM + (((g >> 1) & 1) * 2 + (g >> 2)) * 128 + (2 * c + (w >> 1)) * 16 + (w & 1) * 8 + (g & 1) * 2;
        for (bool first = true; ; first = false) {
          float r[4];
          mbar_wait(sb + B_PART, pph, budget);
          PROFW(0, 11);
          pph ^= 1;
          wg_fence();
          sfor<0, 8>([&](auto K) { constexpr int k = K; wg_ss8<k != 0, Op<WA + k * 2048, 16, 1024, 1, 1>, Op<PM1 + (6 - (k & 6)) * 16, 0, 128, 0, 0>>(r, d0, d0); });
          wg_commit();
          if (P_G4 < 16 && first) nbar_arrive<NB_G4, 384>();
          const uint32_t x0 = lds32v(ca), x1 = lds32v(ca + 4096), x2 = lds32v(ca + 8192), x3 = lds32v(ca + 12288);
          const bool bad = __any_sync(0xffffffffu, (sp ? x0 | x1 | x2 | x3 : ~(x0 & x1 & x2 & x3)) & 1) && budget > 0;
          wg_wait<0>();
          pin<4>(r);
          uint32_t y = pack_bf16(r[0], r[2]);
          y |= (y & 0xffffu) ? 0 : 0x8000u;
          y |= (y >> 16) ? 0 : 0x80000000u;
          if (bad) y = 0;
          sts16(sa, y); sts16(sa + 4, y >> 16);
          nbar_sync<NB_P, 128>();
          y = lds32v(sb + OM + w * 128 + lane * 4);
          if (!__any_sync(0xffffffffu, y == 0)) { if (!start) v = y; break; }
          nbar_sync<NB_P, 128>();
          budget--;
          if (w == 0) { e_expect_tx(sb + B_PART, 16384); e_bulk_g2s(sb + WA, (const char*)g_part + blk * 16384, 16384, sb + B_PART); }
          __syncwarp();
        }
      }
      stg_rlx32(mw, v);
      stg_rlx32(mw + (sp ? -32768 : 32768), 0);
      PROFW(1, 8);
    }
    if (ATT && s >= 0) {
      const int seg = s - (rank ? LAG : 0);
      const bool act = (unsigned)seg < NSEG;
      LANE_NOW;
      uint32_t a[12];
#pragma unroll
      for (int i = 0; i < 12; i++) a[i] = __float_as_uint(hold[i < 10 ? i >> 1 : 4]) + ((uint32_t)budget >> (31 - (i & 3)));
      float o[32], inv, psum = hold[5];
      char* const ob = (char*)g_o[rank] + ((size_t)(seg * 32 + 8 * (g >> 1) + (g & 1) + 2 * w) * (NH * DH) + h * DH + c * 8) * 2;
      sfor<0, 2>([&](auto HF) {
        constexpr int hf = HF;
        wg_fence();
        wg_rs64<hf * 2, Op<QB + 8 * RG + hf * 1024, 2 * RG, 128, 0, 0>>(o, a, d0);
        wg_rs64<1, Op<QB + 12 * RG + hf * 1024, RG, 128, 0, 0>>(o, a + 4, d0);
        wg_rs64<1, Op<QB + 14 * RG + hf * 1024, 0, 128, 0, 0>>(o, a + 8, d0);
        wg_commit();
        if constexpr (hf == 0) {
          psum += __shfl_xor_sync(0xffffffffu, psum, 1);
          psum += __shfl_xor_sync(0xffffffffu, psum, 2);
          asm("rcp.approx.ftz.f32 %0, %1;" : "=f"(inv) : "f"(psum));
        }
        wg_wait<0>();
        pin<32>(o);
        if constexpr (hf == 1) { if (w < 3 && more) e_arrive_cl(mapr(h, sb + B_BFREE, w)); }
        if (act) {
#pragma unroll
          for (int i = 0; i < 2; i++)
            stg128(ob + (hf * 2 + i) * 64, pack_bf16(o[16*i] * inv, o[16*i+1] * inv), pack_bf16(o[16*i+4] * inv, o[16*i+5] * inv),
                   pack_bf16(o[16*i+8] * inv, o[16*i+9] * inv), pack_bf16(o[16*i+12] * inv, o[16*i+13] * inv));
        }
      });
      PROFW(0, 7);
      if (act && (seg & 3) == 3) {
        __syncwarp();
        e_flag_add(g_fl.dep + grp(0, rank, seg >> 2));
      }
    } else if (!ATT && w == 3) {
      if (s + 4 < NSEG) e_prefetch(g_xn[0] + (size_t)((s + 4) * 32 + h) * DM, 2048);
    }
  }
  cluster_arrive(); cluster_wait();
  char* const pw = (char*)g_part + (size_t)((ATT ? rank + 1 : 0) * 16 + w * 4 + (lane0 >> 3)) * 4096 + h * 128 + (lane0 & 7) * 16;
#pragma unroll
  for (int j = 0; j < NT; j++) stg_rlx128(pw + j * (48 * 4096), 0, 0, 0, 0);
}

DEVI void rec_load(const uint32_t sb, const int h, const int rank, const int w, const CUtensorMap* mX, const CUtensorMap* mWo) {
  using namespace rec;
  static_assert(((NSTEP - 1) & 31) != 1 && ((NSTEP - 2) & 31) != 2, "stale time stamps of the previous launch never match");
  const int lane0 = lane_reg(), mq = (w + 3) & 3;
  int budget = SPIN_BUDGET;
  cluster_arrive(); cluster_wait();
  if (w == 0) { if (lane0 < 4) mbar_arrive(sb + B_FULL + 8 * lane0); __syncwarp(); }
  uint32_t lph = 0;
#pragma unroll 1
  for (int s = -1; s < NSTEP - 1; s++) {
    if (w == 0) {
      const int sa = s + 1, sn = sa - LAG;
      if ((sa & 3) == 0 && sa < NSEG) flag_wait(g_fl.xn[0][sa >> 2], 128, budget);
      if ((sn & 3) == 0 && (unsigned)sn < NSEG) flag_wait(g_fl.xn[1][sn >> 2], 128, budget);
      int sl = 4, ph = 1;
#pragma unroll 1
      for (int i = 0; i < 16; i++) {
        mbar_wait(sb + B_EMPTY + 8 * sl, ph, budget);
        e_expect_tx(sb + B_FULL + 8 * sl, 8192);
        e_tma_3d(sb + RING + sl * 8192, mX, i * 64, (s + 1) * 32, sb + B_FULL + 8 * sl);
        if (++sl == 5) { sl = 0; ph ^= 1; }
      }
      nbar_arrive<NB_X, 128>();
    }
    uint32_t t = gtime();
    if (s >= 0) {
      uint2 a;
      if (w == 2 && rank < 2) {
        nbar_sync<NB_S, 64>();
        e_expect_tx(sb + B_WA, 16384);
        e_tma_2d(sb + WA, mWo, (3 * JA + 1 + rank) * 64, h * DH, sb + B_WA);
        e_tma_2d(sb + WA + 8192, mWo, (3 * JA + 1 + rank) * 64, h * DH + 64, sb + B_WA);
        e_arrive_cl(mapr(h, sb + B_SDONE, rank ^ 1));
        stg_rlx32(&g_ann[s & 1][lane0][h * 2 + rank], (gtime() & ~31u) | ((s + 1) & 31));
        e_expect_tx(sb + B_QK, 10240);
        e_expect_tx(sb + B_V, 10240);
      }
      if (w) nbar_sync<NB_G, 128>();
      do { a = ldg_rlx64(&g_ann[s & 1][h][lane0 * 2]); } while (__any_sync(0xffffffffu, ((a.x ^ (s + 1)) | (a.y ^ (s + 1))) & 31) && --budget > 0);
      t += __reduce_max_sync(0xffffffffu, max((int)(a.x - t), (int)(a.y - t)));
      t &= ~31u;
      PROFW(1, 12);
      if (w == 1 && rank < 2) {
        nbar_sync<NB_TR, 160>();
        wait_time(t + (rank ? TUN(1, 1750) : TUN(0, 1500)), budget);
        e_expect_tx(sb + B_PART, 16384);
        e_bulk_g2s(sb + WA, (const char*)g_part + (rank * 32 + h) * 16384, 16384, sb + B_PART);
        PROFW(1, 21);
      }
      t += mq == 0 ? TUN(2, 2500) : mq == 1 ? TUN(3, 2550) : mq == 2 ? TUN(4, 2800) : TUN(5, 2800);
    }
    if (w) nbar_sync<NB_X, 128>();
    mbar_wait(sb + B_EMPTY + 8 * mq, 1, budget);
    PROFW(1, 9);
    wait_time(t, budget);
    PROFW(1, 22); PROFW(3, 23);
    while (true) {
      e_expect_tx(sb + B_MLAND + 8 * mq, 8192);
      e_bulk_g2s(sb + RING + mq * 8192, (const char*)g_mem + (s & 1) * 32768 + mq * 8192, 8192, sb + B_MLAND + 8 * mq);
      const uint32_t a = sb + RING + mq * 8192 + lane0 * 32 + (lane0 >> 2) * 4;
      mbar_wait(sb + B_MLAND + 8 * mq, lph, budget);
      lph ^= 1;
      PROFW(1, 24);
      uint32_t mn = 0xffffffffu;
#pragma unroll
      for (int i = 0; i < 8; i++) mn = min(mn, lds32v(a + i * 1024));
      if (!__any_sync(0xffffffffu, mn == 0) || --budget <= 0) break;
    }
    e_arrive(sb + B_FULL + 8 * mq);
    PROFW(1, 10); PROFW(2, 13); PROFW(3, 14); PROFW(0, 15);
  }
}

struct RecMaps { CUtensorMap w[3], wo, x; };
__global__ void __cluster_dims__(R_CL, 1, 1) __launch_bounds__(512, 1)
rec_kernel(const __grid_constant__ RecMaps M, const bf16* __restrict__ Wo, const bf16* __restrict__ mem0, uint32_t zero) {
  using namespace rec;
  extern __shared__ __align__(1024) uint8_t smem[];
  const uint32_t sb = smem_u32(smem);
  const int tid = threadIdx.x, warp = __shfl_sync(0xffffffffu, tid >> 5, 0), wg = warp >> 2, lane = tid & 31;
  const int h = blockIdx.x / 3, rank = blockIdx.x % 3;
  if (warp == 0) {
    if (lane < 20) mbar_init(sb + BARS + 8 * lane, (lane >= 5 && lane < 10) || lane == 19 ? 2 : lane == 14 ? 9 : lane == 16 && rank < 2 ? 5 : 1);
    else if (lane < 23) mbar_init(sb + B_W1 + 8 * (lane - 20), 1);
    else if (lane == 23) mbar_init(sb + B_PART, 1);
    fence_mbar_init();
    __syncwarp();
    if (lane == 0) { mbar_expect_tx(sb + B_W1, (NSS + R1) * 4096); mbar_expect_tx(sb + B_QK, 10240); mbar_expect_tx(sb + B_V, 10240); mbar_expect_tx(sb + B_OM, rank < 2 ? 2048 : 4096); }
    __syncwarp();
    for (int i = lane; i < 128; i += 32) {
      const int j = i >> 1, t = i & 1, r = reg_idx(j);
      if (is_ss(j)) tma_load_2d(sb + WS + (t * NSS + ss_before(j)) * 2048, &M.w[rank], h * DH + t * 64, j * 16, sb + B_W1);
      else if (r < R1) tma_load_2d(sb + WO + (t * R1 + r) * 2048, &M.w[rank], h * DH + t * 64, j * 16, sb + B_W1);
      else tma_prefetch_2d(&M.w[rank], h * DH + t * 64, j * 16);
    }
    const int t = 3 * (lane >> 1) + (rank + 1) % 3;
    if (t < 16) tma_prefetch_2d(&M.wo, t * 64, h * DH + (lane & 1) * 64);
  } else if (warp == 1) {
    constexpr int N = (sizeof(Flags) - sizeof(g_fl.xn)) / 16;
    if (lane == 0 && blockIdx.x < N) ((uint4*)g_fl.dep)[blockIdx.x] = make_uint4(0, 0, 0, 0);
    static_assert(N <= 96, "flag reset");
    __threadfence();
    __syncwarp();
    asm volatile("griddepcontrol.launch_dependents;" ::: "memory");
  }
  __syncthreads();
  if (wg == 3) {
    reg_dec<24>();
    rec_load(sb, h, rank, warp & 3, &M.x, &M.wo);
    cluster_arrive(); cluster_wait();
  } else if (wg == 2) {
    reg_dec<72>();
    if (rank < 2) rec_attn<true>(sb, h, rank, warp & 3, Wo, mem0);
    else rec_attn<false>(sb, h, rank, warp & 3, Wo, mem0);
  } else {
    reg_inc<208>();
    rec_proj(sb, h, rank, warp, &M.w[rank], &M.wo, zero);
    cluster_arrive(); cluster_wait();
  }
}

namespace gm {
#define G_ST 6
constexpr int STAGES = G_ST, STAGE_BYTES = 32768;
constexpr uint32_t SO = STAGES * STAGE_BYTES, B_FULL = SO + 32768, B_EMPTY = B_FULL + 64, B_JOB = B_FULL + 128, B_MSG = B_FULL + 144, B_TRIG = B_FULL + 56, JOB = B_FULL + 160, MSG = JOB + 8, SMEM = B_FULL + 192;
constexpr int T_O = 0, T_GU = 1, T_D = 2, T_END = 3, NEARLY = 32;
#define G_NO 8
#define G_NG 14
#define G_ND 8
__host__ __device__ constexpr bool is_split(int ty, int l, int cb) { return ty == T_O && l && cb >= 16 - NSPL; }
#define G_LOOK 8
struct Pipe { int s, ph; DEVI void next() { if (++s == STAGES) { s = 0; ph ^= 1; } } };
}
struct GemmMaps { CUtensorMap o, wo, x, x1, xm, wg, wu, h, hs, wd, x2, pt, out; };

DEVI float geglu(float g, float u) {
  const float z = g * (0.7978845608028654f + 0.035677408136300125f * g * g);
  float t; asm("tanh.approx.f32 %0, %1;" : "=f"(t) : "f"(z));
  const float hg = 0.5f * g;
  return fmaf(hg, t, hg) * u;
}
DEVI int h_ready(int v) { const int t = v ^ 0x0e0e0e0e; return t ? ((__ffs(t) - 1) >> 3) * 14 : 56; }
DEVI int h_wait(const int* p, int i, int& budget) {
  int n = 64;
  while ((n = h_ready(ld_acquire(p))) <= i && --budget > 0) __nanosleep(32);
  asm volatile("fence.proxy.async.global;" ::: "memory");
  return n;
}
#define LN_LD 0
DEVI uint4 ld_ln(const uint4* p) {
  uint4 v;
  if (LN_LD == 0) v = __ldcg(p);
  if (LN_LD == 1) asm volatile("ld.relaxed.gpu.global.v4.b32 {%0,%1,%2,%3}, [%4];" : "=r"(v.x), "=r"(v.y), "=r"(v.z), "=r"(v.w) : "l"(p));
  if (LN_LD == 2) asm volatile("ld.global.L1::no_allocate.v4.b32 {%0,%1,%2,%3}, [%4];" : "=r"(v.x), "=r"(v.y), "=r"(v.z), "=r"(v.w) : "l"(p));
  if (LN_LD == 3) asm volatile("ld.global.nc.L1::no_allocate.v4.b32 {%0,%1,%2,%3}, [%4];" : "=r"(v.x), "=r"(v.y), "=r"(v.z), "=r"(v.w) : "l"(p));
  return v;
}
template<int NP> DEVI void ln_row(const bf16* res, const bf16* pt, uint4* u, bf16* xn, int lane) {
  uint32_t* x = (uint32_t*)u;
  float sum = 0;
#pragma unroll
  for (int hf = 0; hf < 2; hf++) {
    uint4 p[2][NP + 1];
#pragma unroll
    for (int i = 0; i < 2; i++)
#pragma unroll
      for (int k = 0; k <= NP; k++) p[i][k] = ld_ln((const uint4*)(k ? pt + (k - 1) * (128 * DM) : res) + (hf * 2 + i) * 32 + lane);
#pragma unroll
    for (int i = 0; i < 8; i++) {
      uint32_t y = ((const uint32_t*)&p[i >> 2][0])[i & 3];
      if (NP) {
        float lo = 0, hi = 0;
#pragma unroll
        for (int k = 1; k <= NP; k++) { const uint32_t z = ((const uint32_t*)&p[i >> 2][k])[i & 3]; lo += bf_lo(z); hi += bf_hi(z); }
        y = pack_bf16(lo + bf_lo(y), hi + bf_hi(y));
      }
      x[hf * 8 + i] = y;
      sum += bf_lo(y) + bf_hi(y);
    }
  }
  float mean = sum * (1.f / 32), q = 0;
#pragma unroll
  for (int i = 0; i < 16; i++) { const float a = bf_lo(x[i]) - mean, b = bf_hi(x[i]) - mean; q = fmaf(a, a, fmaf(b, b, q)); }
#pragma unroll
  for (int o = 1; o < 32; o *= 2) {
    const float m2 = __shfl_xor_sync(0xffffffffu, mean, o), q2 = __shfl_xor_sync(0xffffffffu, q, o), dl = m2 - mean;
    q = fmaf(dl * dl, 16.f * o, q + q2);
    mean = 0.5f * (mean + m2);
  }
  const float rs = rsqrtf(q * (1.f / DM) + 1e-5f), mr = -mean * rs;
#pragma unroll
  for (int i = 0; i < 4; i++) {
    uint32_t y[4];
#pragma unroll
    for (int k = 0; k < 4; k++) y[k] = pack_bf16(fmaf(bf_lo(x[4*i+k]), rs, mr), fmaf(bf_hi(x[4*i+k]), rs, mr));
    stg128((uint4*)xn + i * 32 + lane, y[0], y[1], y[2], y[3]);
  }
}

__global__ void __cluster_dims__(2, 1, 1) __launch_bounds__(512, 1) gemm_kernel(const __grid_constant__ GemmMaps M, const bf16* __restrict__ x) {
  using namespace gm;
  extern __shared__ __align__(1024) uint8_t smem[];
  const uint32_t sb = smem_u32(smem);
  const int tid = threadIdx.x, wid = __shfl_sync(0xffffffffu, tid >> 5, 0), wg = wid >> 2, warp = wid & 3;
  int budget = SPIN_BUDGET;
  const int rank = blockIdx.x & 1;
  const uint32_t peer = mapa(sb, rank ^ 1);
  if (tid < 20) mbar_init(sb + B_FULL + 8 * tid, tid >> 3 == 1 ? 2 : 1);
  fence_mbar_init();
  if (wid == 1 && rank == 0) sts32v(sb + JOB + 16, bcast(e_ticket(g_fl.ticket)));
  cluster_arrive(); cluster_wait();
  int cta;
  asm volatile("ld.shared::cluster.u32 %0, [%1];" : "=r"(cta) : "r"(mapa(sb + JOB + 16, 0)) : "memory");
  cta = __shfl_sync(0xffffffffu, cta, 0) * 2 + rank;
  const int lane = lane_reg();
  if (wg >= 2) {
    reg_dec<64>();
    if (wid == 8) {
      Pipe p; p.s = 0; p.ph = 1;
      for (int n = 0; ; n++) {
        e_expect_tx(sb + B_MSG + 8 * (n & 1), 4);
        mbar_wait(sb + B_MSG + 8 * (n & 1), (n >> 1) & 1, budget);
        const int msg = __shfl_sync(0xffffffffu, lds32v(sb + MSG + 4 * (n & 1)), 0);
        const int ty = (msg >> 11) & 3, l = (msg >> 10) & 1, shb = ty == T_GU && l;
        const int cb = ((msg >> 6) & 15) + (shb ? rank : 0), j = (msg & 63) + (ty == T_END || shb ? 0 : rank);
        const int job = ty << 11 | l << 10 | cb << 6 | j, row = l * SEQ + cb * 128;
        mbar_wait(sb + B_EMPTY + 8 * p.s, p.ph, budget);
        trap_if_spent(budget);
        sts32v(sb + JOB + 4 * (n & 1), job | p.s << 16 | (p.ph ^ 1) << 20);
        e_arrive(sb + B_JOB + 8 * (n & 1));
        if (ty == T_END) break;
        const bool spl = is_split(ty, l, cb);
        const int nk = ty == T_D ? 56 : ty == T_GU || spl ? 16 : 64, k0 = spl ? (j >> 3) * 16 : 0, jt = j & 7;
        int rdy = msg >> 16;
        if (ty != T_GU && !spl) {
          const uint32_t fb = sb + B_FULL + 8 * p.s, a = sb + p.s * STAGE_BYTES;
          const CUtensorMap* const m = ty == T_D ? &M.x1 : l ? &M.x2 : &M.x;
          const int r = ty == T_D ? row : cb * 128;
          e_expect_tx(fb, STAGE_BYTES);
          e_tma_2d(a, m, jt * 128, r, fb); e_tma_2d(a + 16384, m, jt * 128 + 64, r, fb);
          p.next();
        }
        const CUtensorMap* const ma = ty == T_O ? &M.o : ty == T_GU ? &M.xm : &M.h;
        for (int i = k0; i < k0 + nk; i++) {
          if (i == k0 + nk - G_LOOK) e_arrive(sb + B_TRIG);
          const uint32_t fb = sb + B_FULL + 8 * p.s, a = sb + p.s * STAGE_BYTES, b = a + 16384;
          mbar_wait(sb + B_EMPTY + 8 * p.s, p.ph, budget);
          e_expect_tx(fb, STAGE_BYTES);
          if (ty == T_O) { e_tma_5d(b, &M.wo, jt * 128, i * 2, fb); e_tma_5d(b + 8192, &M.wo, jt * 128 + 64, i * 2, fb); }
          else if (shb) e_tma_2d_mc(b + rank * 8192, rank ? &M.wu : &M.wg, j * 64, i * 64, fb);
          else if (ty == T_GU) { e_tma_2d(b, &M.wg, j * 64, i * 64, fb); e_tma_2d(b + 8192, &M.wu, j * 64, i * 64, fb); }
          else {
            e_tma_2d(b, &M.wd, jt * 128, i * 64, fb); e_tma_2d(b + 8192, &M.wd, jt * 128 + 64, i * 64, fb);
            if (i >= rdy) rdy = h_wait(g_fl.dep + grp(T_D, l, cb), i, budget);
          }
          if (shb) { e_tma_2d(a, ma, i * 64, row, fb); e_tma_2d(a + 8192, ma, i * 64, row + 64, fb); }
          else e_tma_2d_mc(a + rank * 8192, ma, i * 64, row + rank * 64, fb);
          p.next();
        }
      }
    } else if (wid == 9 && rank == 0) {
      const int role = cta < G_NO ? T_O : cta < G_NO + G_NG ? T_GU : cta < G_NO + G_NG + G_ND ? T_D : T_END;
      int k1 = role == T_O ? cta : role == T_GU ? cta - G_NO : role == T_D ? cta - G_NO - G_NG : 1024;
      for (int n = 0, ty = 0; ty != T_END; n++) {
        mbar_wait(sb + B_TRIG, (n & 1) ^ 1, budget);
        int l = 0, cb = 0, j = 0;
        if (k1 < (role == T_GU ? 896 : 128)) {
          ty = role;
          cb = role == T_GU ? k1 / 56 : k1 >> 3; j = k1 - cb * (role == T_GU ? 56 : 8);
          k1 += role == T_O ? G_NO : role == T_GU ? G_NG : G_ND;
        } else while (true) {
          int d0 = ld_relaxed(g_fl.dep + lane), d1 = ld_relaxed(g_fl.dep + 32 + lane);
          const int t0 = ld_relaxed(g_fl.taken + lane), t1 = ld_relaxed(g_fl.taken + 32 + lane);
          const bool l0 = t0 < (lane >= 16 ? (lane & 1 ? 0 : 56) : is_split(T_O, 1, lane) ? 4 * KS : 4), l1 = lane < 16 && t1 < 4;
          const uint32_t rd = __ballot_sync(0xffffffffu, d0 >= 128);
          const uint32_t ok0 = __ballot_sync(0xffffffffu, l0) & rd & (rd >> 1 | 0xffff), ok1 = __ballot_sync(0xffffffffu, l1 && h_ready(d1) > 0);
          ty = T_END; l = 1;
          if (!__any_sync(0xffffffffu, l0 || l1)) break;
          uint32_t m = ok0 ? ok0 : ok1;
          if (!m) __nanosleep(100);
          while (m) {
            const int nth = ok0 ? 0 : (cta >> 1) % __popc(m);
            const int b = __ffs(__ballot_sync(0xffffffffu, __popc(m << (31 - lane)) > nth)) - 1, gn = b + (ok0 ? 0 : 32);
            const int t = bcast(e_ticket(g_fl.taken + gn));
            if (t < (gn >> 4 == T_GU ? 56 : is_split(gn >> 4, 1, gn & 15) ? 4 * KS : 4)) { ty = gn >> 4; cb = gn & 15; j = ty == T_GU ? t : 2 * t; break; }
            m &= ~(1u << b);
          }
          if (ty != T_END) break;
          trap_if_spent(--budget);
        }
        int rdy = 64;
        if (ty == T_D) rdy = h_wait(g_fl.dep + grp(T_D, l, cb), 0, budget);
        else if (ty != T_END) flag_wait(g_fl.dep + grp(ty, l, cb), 128, budget);
        if (ty == T_GU && l) flag_wait(g_fl.dep + grp(ty, l, cb + 1), 128, budget);
        const int msg = rdy << 16 | ty << 11 | l << 10 | cb << 6 | j;
        e_st_async32(peer + MSG + 4 * (n & 1), msg, peer + B_MSG + 8 * (n & 1));
        e_st_async32(sb + MSG + 4 * (n & 1), msg, sb + B_MSG + 8 * (n & 1));
      }
    } else if (cta < NEARLY && wg == 3) {
      const int r0 = warp * NEARLY + (NEARLY - 1 - cta);
      int nb = r0 < 128 && lane < 3 ? 0 : 16;
      while (__any_sync(0xffffffffu, nb < 16)) {
        int v = 0;
        if (nb < 16) asm volatile("ld.acquire.gpu.global.s32 %0, [%1];" : "=r"(v) : "l"(g_fl.part + lane * 16 + nb) : "memory");
        const uint32_t ok = __ballot_sync(0xffffffffu, v >= (is_split(lane, 1, nb) ? 8 * KS : 8));
        if (!ok) {
          if (--budget <= 0) break;
          __nanosleep(64);
          continue;
        }
        const int st = 31 - __clz(ok), cb = __shfl_sync(0xffffffffu, nb, st);
        nb += lane == st;
#pragma unroll 1
        for (int r = r0; r < 128; r += 4 * NEARLY) {
          const size_t o = (size_t)(cb * 128 + r) * DM;
          uint4 u[4];
          if (is_split(st, 1, cb)) {
            ln_row<KS>(g_x2 + o, g_pt + (size_t)((cb - 16 + NSPL) * KS * 128 + r) * DM, u, g_xm[1] + o, lane);
#pragma unroll
            for (int i = 0; i < 4; i++) stg128((uint4*)(g_x1[1] + o) + i * 32 + lane, u[i].x, u[i].y, u[i].z, u[i].w);
          } else ln_row<0>((st == 2 ? g_x2 : g_x1[st ^ 1]) + o, nullptr, u, (st == 2 ? g_xn[1] + LAG * 32 * DM : g_xm[st ^ 1]) + o, lane);
          __syncwarp();
          e_flag_add(st == 2 ? g_fl.xn[1][cb] : g_fl.dep + grp(T_GU, st ^ 1, cb));
        }
      }
      if (cta == 0 && wid == 12) {
        asm volatile("griddepcontrol.wait;" ::: "memory");
        g_fl.xn[lane >> 4][lane & 15][0] = 0;
      }
    }
    cluster_arrive(); cluster_wait();
  } else {
    reg_inc<192>();
    if (cta < NEARLY) {
#pragma unroll 1
      for (int r = 2 * (cta * 8 + wid); r < SEQ; r += 16 * NEARLY) {
        uint4 u[4];
        ln_row<0>(x + (size_t)r * DM, nullptr, u, g_xn[0] + (size_t)r * DM, lane);
        ln_row<0>(x + (size_t)(r + 1) * DM, nullptr, u, g_xn[0] + (size_t)(r + 1) * DM, lane);
        __syncwarp();
        e_flag_add(g_fl.xn[0][r >> 7], 2);
      }
    }
    const bool lead = warp == 0;
    const uint32_t eb = (warp == 1 ? peer : sb) + B_EMPTY;
    const int rl = warp < 2 ? 0 : -1;
    const uint32_t so = sb + SO + wg * 16384;
    const int r0 = warp * 16 + (lane & 7) + ((lane >> 3) & 1) * 8;
    const uint32_t sw = r0 * 128 + (((lane >> 4) ^ (r0 & 7)) << 4);
    for (int n = wg; ; n += 2) {
      float d0[64], d1[64];
      mbar_wait(sb + B_JOB + 8 * wg, (n >> 1) & 1, budget);
      fault_if_spent(budget);
      const int job = __shfl_sync(0xffffffffu, lds32v(sb + JOB + 4 * wg), 0);
      const int ty = (job >> 11) & 3, l = (job >> 10) & 1, cb = (job >> 6) & 15, j = job & 63;
      if (ty == T_END) {
        if (n > 0) nbar_sync_r(1 + wg, 256);
        if (lead && !(job & 1)) { sts32v(sb + JOB + 4 * (wg ^ 1), job | 1); e_arrive(sb + B_JOB + 8 * (wg ^ 1)); }
        if (!(job & 1)) nbar_arrive_r(1 + (wg ^ 1), 256);
        break;
      }
      Pipe q; q.s = (job >> 16) & 15; q.ph = job >> 20;
      const bool spl = is_split(ty, l, cb);
      if (ty != T_GU && !spl) {
        mbar_wait(sb + B_FULL + 8 * q.s, q.ph, budget);
#pragma unroll
        for (int m = 0; m < 2; m++)
#pragma unroll
          for (int c = 0; c < 8; c++) {
            float* d = (m ? d1 : d0) + 8 * c;
            uint32_t r[4];
            ldsm4(sb + q.s * STAGE_BYTES + (c >> 2) * 16384 + m * 8192 + (sw ^ ((c & 3) << 5)), r[0], r[1], r[2], r[3]);
#pragma unroll
            for (int i = 0; i < 4; i++) { d[2*i] = bf_lo(r[i]); d[2*i+1] = bf_hi(r[i]); }
          }
        fence_proxy_async();
        nbar_sync_r(3 + wg, 128);
        arrive_cl_if_eq(eb + 8 * q.s, lane, rl);
        q.next();
      } else {
#pragma unroll
        for (int i = 0; i < 64; i++) d0[i] = d1[i] = 0.f;
      }
      pin<64>(d0); pin<64>(d1);
      if (n > 0) nbar_sync_r(1 + wg, 256);
      const int nk = ty == T_D ? 56 : ty == T_GU || spl ? 16 : 64;
      int prev = 0;
      for (int i = 0; i < nk; i++) {
        mbar_wait(sb + B_FULL + 8 * q.s, q.ph, budget);
        const uint32_t da = desc_base(sb) + q.s * (STAGE_BYTES / 16);
        wg_fence();
        sfor<0, 4>([&](auto K) {
          constexpr int k = K;
          typedef Op<16384 + k * 2048, 8192, 1024, 1, 1> OB;
          wg_ss128<1, Op<k * 32, 16, 1024, 1, 0>, OB>(d0, da, da);
          wg_ss128<1, Op<8192 + k * 32, 16, 1024, 1, 0>, OB>(d1, da, da);
        });
        wg_commit();
        wg_wait<1>();
        arrive_cl_if_eq(eb + 8 * prev, lane, i ? rl : -1);
        prev = q.s;
        q.next();
      }
      nbar_arrive_r(1 + (wg ^ 1), 256);
      wg_wait<0>();
      pin<64>(d0); pin<64>(d1);
      arrive_cl_if_eq(eb + 8 * prev, lane, rl);
      if (ty == T_GU) {
#pragma unroll
        for (int m = 0; m < 2; m++)
#pragma unroll
          for (int c = 0; c < 4; c++) {
            const float* d = (m ? d1 : d0) + 8 * c;
            uint32_t r[4];
#pragma unroll
            for (int i = 0; i < 4; i++) r[i] = pack_bf16(geglu(d[2*i], d[32+2*i]), geglu(d[2*i+1], d[32+2*i+1]));
            stsm4(so + m * 8192 + (sw ^ (c << 5)), r[0], r[1], r[2], r[3]);
          }
        fence_proxy_async();
        nbar_sync_r(3 + wg, 128);
        if (lead) {
          e_tma_store_2d(&M.hs, so, j * 64, l * SEQ + cb * 128);
          bulk_commit(); bulk_wait<0>();
          e_flag_add(g_fl.dep + grp(T_D, l, cb), 1 << (j / 14 * 8));
        }
      } else {
        const CUtensorMap* const mo = spl ? &M.pt : ty == T_O ? &M.x1 : l ? &M.out : &M.x2;
        const int row = spl ? ((cb - 16 + NSPL) * KS + (j >> 3)) * 128 : (ty == T_O ? l * SEQ : 0) + cb * 128;
#pragma unroll
        for (int hf = 0; hf < 2; hf++) {
          if (hf) nbar_sync_r(3 + wg, 128);
#pragma unroll
          for (int m = 0; m < 2; m++)
#pragma unroll
            for (int c = 0; c < 4; c++) {
              const float* d = (m ? d1 : d0) + 32 * hf + 8 * c;
              stsm4(so + m * 8192 + (sw ^ (c << 5)), pack_bf16(d[0], d[1]), pack_bf16(d[2], d[3]), pack_bf16(d[4], d[5]), pack_bf16(d[6], d[7]));
            }
          fence_proxy_async();
          nbar_sync_r(3 + wg, 128);
          if (lead) {
            e_tma_store_2d(mo, so, (j & 7) * 128 + hf * 64, row);
            bulk_commit();
            if (hf == 0) bulk_wait_read<0>();
            else {
              bulk_wait<0>();
              if (ty == T_O || !l) e_flag_add(g_fl.part + (ty == T_O ? l ^ 1 : 2) * 16 + cb);
            }
          }
        }
      }
    }
    cluster_arrive(); cluster_wait();
  }
}

typedef CUresult (*PFN_encodeTiled)(CUtensorMap*, CUtensorMapDataType, cuuint32_t, void*, const cuuint64_t*, const cuuint64_t*,
                                    const cuuint32_t*, const cuuint32_t*, CUtensorMapInterleave, CUtensorMapSwizzle,
                                    CUtensorMapL2promotion, CUtensorMapFloatOOBfill);
static PFN_encodeTiled g_encode = nullptr;
static int g_sms = 0;
static CUtensorMap encode(const void* ptr, int rank, const cuuint64_t* dims, const cuuint64_t* strides, const cuuint32_t* box) {
  CUtensorMap m;
  const cuuint32_t es[5] = {1, 1, 1, 1, 1};
  g_encode(&m, CU_TENSOR_MAP_DATA_TYPE_BFLOAT16, rank, (void*)ptr, dims, strides, box, es, CU_TENSOR_MAP_INTERLEAVE_NONE,
           CU_TENSOR_MAP_SWIZZLE_128B, CU_TENSOR_MAP_L2_PROMOTION_L2_256B, CU_TENSOR_MAP_FLOAT_OOB_FILL_NONE);
  return m;
}
static CUtensorMap make_map(const void* ptr, uint64_t rows, uint64_t cols, uint32_t box_rows) {
  const cuuint64_t dims[2] = {cols, rows}, strides[1] = {cols * 2};
  const cuuint32_t box[2] = {64, box_rows};
  return encode(ptr, 2, dims, strides, box);
}
static CUtensorMap make_map_x(const void* ptr) {
  const cuuint64_t dims[3] = {DM, NSTEP * 32, 2}, strides[2] = {DM * 2, (cuuint64_t)NSTEP * 32 * DM * 2};
  const cuuint32_t box[3] = {64, 32, 2};
  return encode(ptr, 3, dims, strides, box);
}
static CUtensorMap make_map_wo(const void* ptr) {
  const cuuint64_t dims[5] = {DM, 2, 4, 4, NH * DH / 32}, strides[4] = {DM * 2, 8 * DM * 2, 2 * DM * 2, 32 * DM * 2};
  const cuuint32_t box[5] = {64, 2, 4, 4, 2};
  return encode(ptr, 5, dims, strides, box);
}

extern "C" void kernel_launch(void* const* d_in, const int* in_sizes, int n_in, void* d_out, int out_size) {
  const bf16 *x = (const bf16*)d_in[0], *mem0 = (const bf16*)d_in[1], *Wo = (const bf16*)d_in[5];
  if (!g_encode) {
    void* p = nullptr; cudaDriverEntryPointQueryResult q;
    cudaGetDriverEntryPoint("cuTensorMapEncodeTiled", &p, cudaEnableDefault, &q);
    g_encode = (PFN_encodeTiled)p;
    int dev = 0;
    cudaGetDevice(&dev);
    cudaDeviceGetAttribute(&g_sms, cudaDevAttrMultiProcessorCount, dev);
    cudaFuncSetAttribute(rec_kernel, cudaFuncAttributeMaxDynamicSharedMemorySize, rec::SMEM);
    cudaFuncSetAttribute(gemm_kernel, cudaFuncAttributeMaxDynamicSharedMemorySize, gm::SMEM);
  }
  void *xn, *o, *x1, *xm, *x2, *pt, *hh;
  cudaGetSymbolAddress(&xn, g_xn); cudaGetSymbolAddress(&o, g_o); cudaGetSymbolAddress(&x1, g_x1);
  cudaGetSymbolAddress(&xm, g_xm); cudaGetSymbolAddress(&pt, g_pt); cudaGetSymbolAddress(&x2, g_x2); cudaGetSymbolAddress(&hh, g_h);
  RecMaps R;
  for (int i = 0; i < 3; i++) R.w[i] = make_map(d_in[2 + i], DM, NH * DH, 16);
  R.wo = make_map(Wo, NH * DH, DM, 64); R.x = make_map_x(xn);
  rec_kernel<<<96, 512, rec::SMEM>>>(R, Wo, mem0, 0);
  GemmMaps G;
  G.o = make_map(o, 2 * SEQ, NH * DH, 64); G.wo = make_map_wo(Wo);
  G.x1 = make_map(x1, 2 * SEQ, DM, 128); G.xm = make_map(xm, 2 * SEQ, DM, 64);
  G.wg = make_map(d_in[8], DM, DF, 64); G.wu = make_map(d_in[9], DM, DF, 64); G.wd = make_map(d_in[10], DF, DM, 64);
  G.h = make_map(hh, 2 * SEQ, DF, 64); G.hs = make_map(hh, 2 * SEQ, DF, 128); G.pt = make_map(pt, NSPL * KS * 128, DM, 128);
  G.x = make_map(x, SEQ, DM, 128); G.x2 = make_map(x2, SEQ, DM, 128); G.out = make_map(d_out, SEQ, DM, 128);
  cudaLaunchConfig_t cfg = {};
  cfg.gridDim = dim3(g_sms & ~1); cfg.blockDim = dim3(512); cfg.dynamicSmemBytes = gm::SMEM; cfg.stream = cudaStreamPerThread;
  cudaLaunchAttribute at;
  at.id = cudaLaunchAttributeProgrammaticStreamSerialization; at.val.programmaticStreamSerializationAllowed = 1;
  cfg.attrs = &at; cfg.numAttrs = 1;
  cudaLaunchKernelEx(&cfg, gemm_kernel, G, x);
}
```

```cpp
#include <cuda_runtime.h>
#include <cuda_bf16.h>
#include <cuda.h>
#include <stdint.h>

#define DEVI __device__ __forceinline__
typedef __nv_bfloat16 bf16;

#define LAG 18
constexpr int SEQ = 2048, DM = 1024, NH = 32, DH = 128, DF = 3584, NSEG = 64, NSTEP = NSEG + LAG;
static_assert(NSTEP % 2 == 0, "tags and slots of the exchange buffers return to their initial state");

__device__ __align__(1024) bf16 g_xn[2][NSTEP * 32 * DM];
__device__ __align__(1024) bf16 g_o[2][SEQ * NH * DH];
__device__ __align__(1024) bf16 g_x1[2][SEQ * DM];
__device__ __align__(1024) bf16 g_xm[2][SEQ * DM];
__device__ __align__(1024) bf16 g_x2[SEQ * DM];
__device__ __align__(1024) bf16 g_h[2][SEQ * DF];
__device__ __align__(1024) uint4 g_part[256 * 32 * 8];
__device__ __align__(1024) uint32_t g_ann[2][32][64];
__device__ __align__(1024) uint4 g_mem[2][2048];
#define NSPL 2
constexpr int KS = 4;
__device__ __align__(1024) bf16 g_pt[NSPL * KS * 128 * DM];
__host__ __device__ constexpr int grp(int type, int layer, int blk) { return (layer ? 0 : 48) + 16 * type + blk; }
struct Flags {
  int xn[2][16][32];
  int dep[96];
  int taken[64];
  int part[64];
  int ticket[32];
};
__device__ __align__(128) Flags g_fl;

DEVI uint32_t smem_u32(const void* p) { return (uint32_t)__cvta_generic_to_shared(p); }
DEVI void mbar_init(uint32_t bar, uint32_t cnt) { asm volatile("mbarrier.init.shared::cta.b64 [%0], %1;" :: "r"(bar), "r"(cnt) : "memory"); }
DEVI void mbar_expect_tx(uint32_t bar, uint32_t bytes) { asm volatile("mbarrier.arrive.expect_tx.shared::cta.b64 _, [%0], %1;" :: "r"(bar), "r"(bytes) : "memory"); }
DEVI void mbar_arrive(uint32_t bar) { asm volatile("mbarrier.arrive.shared::cta.b64 _, [%0];" :: "r"(bar) : "memory"); }
DEVI bool mbar_try(uint32_t bar, uint32_t parity) {
  uint32_t p;
  asm volatile("{.reg .pred p; mbarrier.try_wait.parity.shared::cta.b64 p, [%1], %2; selp.u32 %0, 1, 0, p;}" : "=r"(p) : "r"(bar), "r"(parity) : "memory");
  return p;
}
constexpr int SPIN_BUDGET = 1 << 20;
DEVI void mbar_wait(uint32_t bar, uint32_t parity, int& budget) {
  while (!mbar_try(bar, parity)) { if (--budget < 0) break; }
}
DEVI void trap_if_spent(int budget) { asm volatile("{.reg .pred p; setp.le.s32 p, %0, 0; @p trap;}" :: "r"(budget) : "memory"); }
DEVI void fault_if_spent(int budget) { asm volatile("{.reg .pred p; setp.le.s32 p, %0, 0; @p st.global.u32 [%1], 0;}" :: "r"(budget), "l"(0ull) : "memory"); }
DEVI uint32_t mapa(uint32_t addr, uint32_t rank) { uint32_t r; asm("mapa.shared::cluster.u32 %0, %1, %2;" : "=r"(r) : "r"(addr), "r"(rank)); return r; }
DEVI void cluster_arrive() { asm volatile("barrier.cluster.arrive.release.aligned;" ::: "memory"); }
DEVI void cluster_wait() { asm volatile("barrier.cluster.wait.acquire.aligned;" ::: "memory"); }
DEVI void fence_mbar_init() { asm volatile("fence.mbarrier_init.release.cluster;" ::: "memory"); }
DEVI void fence_proxy_async() { asm volatile("fence.proxy.async.shared::cta;" ::: "memory"); }
DEVI void tma_load_2d(uint32_t dst, const CUtensorMap* m, int c0, int c1, uint32_t bar) {
  asm volatile("cp.async.bulk.tensor.2d.shared::cluster.global.mbarrier::complete_tx::bytes [%0], [%1, {%3, %4}], [%2];"
    :: "r"(dst), "l"(m), "r"(bar), "r"(c0), "r"(c1) : "memory");
}
DEVI void tma_load_5d(uint32_t dst, const CUtensorMap* m, int c0, int c4, uint32_t bar) {
  asm volatile("cp.async.bulk.tensor.5d.shared::cluster.global.mbarrier::complete_tx::bytes [%0], [%1, {%3, %5, %5, %5, %4}], [%2];"
    :: "r"(dst), "l"(m), "r"(bar), "r"(c0), "r"(c4), "r"(0) : "memory");
}
DEVI void tma_prefetch_2d(const CUtensorMap* m, int c0, int c1) {
  asm volatile("cp.async.bulk.prefetch.tensor.2d.L2.global [%0, {%1, %2}];" :: "l"(m), "r"(c0), "r"(c1) : "memory");
}
DEVI void tma_prefetch_5d(const CUtensorMap* m, int c0, int c4) {
  asm volatile("cp.async.bulk.prefetch.tensor.5d.L2.global [%0, {%1, %3, %3, %3, %2}];" :: "l"(m), "r"(c0), "r"(c4), "r"(0) : "memory");
}
#define ELECT "{.reg .pred p; elect.sync _|p, 0xffffffff;\n @p "
DEVI void e_expect_tx(uint32_t bar, uint32_t bytes) { asm volatile(ELECT "mbarrier.arrive.expect_tx.shared::cta.b64 _, [%0], %1;}" :: "r"(bar), "r"(bytes) : "memory"); }
DEVI void e_arrive(uint32_t bar) { asm volatile(ELECT "mbarrier.arrive.shared::cta.b64 _, [%0];}" :: "r"(bar) : "memory"); }
DEVI void e_arrive_cl(uint32_t bar) { asm volatile(ELECT "mbarrier.arrive.shared::cluster.b64 _, [%0];}" :: "r"(bar) : "memory"); }
DEVI void e_tma_2d(uint32_t dst, const CUtensorMap* m, int c0, int c1, uint32_t bar) {
  asm volatile(ELECT "cp.async.bulk.tensor.2d.shared::cluster.global.mbarrier::complete_tx::bytes [%0], [%1, {%3, %4}], [%2];}"
    :: "r"(dst), "l"(m), "r"(bar), "r"(c0), "r"(c1) : "memory");
}
DEVI void e_tma_2d_mc(uint32_t dst, const CUtensorMap* m, int c0, int c1, uint32_t bar) {
  asm volatile(ELECT "cp.async.bulk.tensor.2d.shared::cluster.global.mbarrier::complete_tx::bytes.multicast::cluster [%0], [%1, {%3, %4}], [%2], %5;}"
    :: "r"(dst), "l"(m), "r"(bar), "r"(c0), "r"(c1), "h"((unsigned short)3) : "memory");
}
DEVI void e_st_async32(uint32_t a, uint32_t x, uint32_t bar) {
  asm volatile(ELECT "st.async.weak.shared::cluster.mbarrier::complete_tx::bytes.b32 [%0], %1, [%2];}" :: "r"(a), "r"(x), "r"(bar) : "memory");
}
DEVI void e_tma_store_2d(const CUtensorMap* m, uint32_t src, int c0, int c1) {
  asm volatile(ELECT "cp.async.bulk.tensor.2d.global.shared::cta.bulk_group [%0, {%2, %3}], [%1];}" :: "l"(m), "r"(src), "r"(c0), "r"(c1) : "memory");
}
DEVI void e_flag_add(int* p, int v = 1) {
  asm volatile("{.reg .pred p; elect.sync _|p, 0xffffffff;\n fence.proxy.async.global; @p red.release.gpu.global.add.s32 [%0], %1;}" :: "l"(p), "r"(v) : "memory");
}
DEVI int e_ticket(int* p) { int v = 0; asm volatile(ELECT "atom.relaxed.gpu.global.add.s32 %0, [%1], 1;}" : "+r"(v) : "l"(p) : "memory"); __syncwarp(); return v; }
DEVI int bcast(int v) { return __reduce_max_sync(0xffffffffu, v); }
DEVI int ld_relaxed(const int* p) { int v; asm volatile("ld.relaxed.gpu.global.s32 %0, [%1];" : "=r"(v) : "l"(p) : "memory"); return v; }
DEVI int ld_acquire(const int* p) { int v; asm volatile("ld.acquire.gpu.global.s32 %0, [%1];" : "=r"(v) : "l"(p) : "memory"); return __shfl_sync(0xffffffffu, v, 0); }
DEVI void e_tma_3d(uint32_t dst, const CUtensorMap* m, int c0, int c1, int c2, uint32_t bar) {
  asm volatile(ELECT "cp.async.bulk.tensor.3d.shared::cluster.global.mbarrier::complete_tx::bytes [%0], [%1, {%3, %4, %5}], [%2];}"
    :: "r"(dst), "l"(m), "r"(bar), "r"(c0), "r"(c1), "r"(c2) : "memory");
}
DEVI void e_tma_5d(uint32_t dst, const CUtensorMap* m, int c0, int c4, uint32_t bar) {
  asm volatile(ELECT "cp.async.bulk.tensor.5d.shared::cluster.global.mbarrier::complete_tx::bytes [%0], [%1, {%3, %5, %5, %5, %4}], [%2];}"
    :: "r"(dst), "l"(m), "r"(bar), "r"(c0), "r"(c4), "r"(0) : "memory");
}
DEVI void e_bulk_g2s(uint32_t dst, const void* src, uint32_t bytes, uint32_t bar) {
  asm volatile(ELECT "cp.async.bulk.shared::cluster.global.mbarrier::complete_tx::bytes [%0], [%1], %2, [%3];}" :: "r"(dst), "l"(src), "r"(bytes), "r"(bar) : "memory");
}
DEVI void e_prefetch(const void* src, uint32_t bytes) {
  asm volatile(ELECT "cp.async.bulk.prefetch.L2.global [%0], %1;}" :: "l"(src), "r"(bytes) : "memory");
}
DEVI void bulk_commit() { asm volatile("cp.async.bulk.commit_group;" ::: "memory"); }
template<int N> DEVI void bulk_wait_read() { asm volatile("cp.async.bulk.wait_group.read %0;" :: "n"(N) : "memory"); }
template<int N> DEVI void bulk_wait() { asm volatile("cp.async.bulk.wait_group %0;" :: "n"(N) : "memory"); }
template<int ID, int N> DEVI void nbar_sync() { asm volatile("bar.sync %0, %1;" :: "n"(ID), "n"(N) : "memory"); }
template<int ID, int N> DEVI void nbar_arrive() { asm volatile("bar.arrive %0, %1;" :: "n"(ID), "n"(N) : "memory"); }
DEVI void nbar_sync_r(int id, int n) { asm volatile("bar.sync %0, %1;" :: "r"(id), "r"(n) : "memory"); }
DEVI void nbar_arrive_r(int id, int n) { asm volatile("bar.arrive %0, %1;" :: "r"(id), "r"(n) : "memory"); }
template<int R> DEVI void reg_inc() { asm volatile("setmaxnreg.inc.sync.aligned.u32 %0;" :: "n"(R)); }
template<int R> DEVI void reg_dec() { asm volatile("setmaxnreg.dec.sync.aligned.u32 %0;" :: "n"(R)); }
DEVI void wg_fence() { asm volatile("wgmma.fence.sync.aligned;" ::: "memory"); }
DEVI void wg_commit() { asm volatile("wgmma.commit_group.sync.aligned;" ::: "memory"); }
template<int N> DEVI void wg_wait() { asm volatile("wgmma.wait_group.sync.aligned %0;" :: "n"(N) : "memory"); }
DEVI uint32_t pack_bf16(float lo, float hi) { uint32_t r; asm("cvt.rn.bf16x2.f32 %0, %1, %2;" : "=r"(r) : "f"(hi), "f"(lo)); return r; }
DEVI float bf_lo(uint32_t v) { return __uint_as_float(v << 16); }
DEVI float bf_hi(uint32_t v) { return __uint_as_float(v & 0xffff0000u); }
DEVI uint32_t movmat(uint32_t a) { uint32_t r; asm volatile("movmatrix.sync.aligned.m8n8.trans.b16 %0, %1;" : "=r"(r) : "r"(a)); return r; }
DEVI void ldsm4(uint32_t addr, uint32_t& r0, uint32_t& r1, uint32_t& r2, uint32_t& r3) {
  asm volatile("ldmatrix.sync.aligned.m8n8.x4.shared.b16 {%0,%1,%2,%3}, [%4];" : "=r"(r0), "=r"(r1), "=r"(r2), "=r"(r3) : "r"(addr) : "memory");
}
DEVI void ldsm4t(uint32_t addr, uint32_t& r0, uint32_t& r1, uint32_t& r2, uint32_t& r3) {
  asm volatile("ldmatrix.sync.aligned.m8n8.x4.trans.shared.b16 {%0,%1,%2,%3}, [%4];" : "=r"(r0), "=r"(r1), "=r"(r2), "=r"(r3) : "r"(addr) : "memory");
}
DEVI void stsm4(uint32_t addr, uint32_t r0, uint32_t r1, uint32_t r2, uint32_t r3) {
  asm volatile("stmatrix.sync.aligned.m8n8.x4.shared.b16 [%0], {%1,%2,%3,%4};" :: "r"(addr), "r"(r0), "r"(r1), "r"(r2), "r"(r3) : "memory");
}
DEVI uint32_t lds32v(uint32_t a) { uint32_t v; asm volatile("ld.volatile.shared.u32 %0, [%1];" : "=r"(v) : "r"(a) : "memory"); return v; }
DEVI void sts32v(uint32_t a, uint32_t v) { asm volatile("st.volatile.shared.u32 [%0], %1;" :: "r"(a), "r"(v) : "memory"); }
DEVI void st_async128(uint32_t a, uint32_t x, uint32_t y, uint32_t z, uint32_t w, uint32_t bar) {
  asm volatile("st.async.weak.shared::cluster.mbarrier::complete_tx::bytes.v4.b32 [%0], {%1,%2,%3,%4}, [%5];" :: "r"(a), "r"(x), "r"(y), "r"(z), "r"(w), "r"(bar) : "memory");
}
DEVI void st_async32(uint32_t a, uint32_t x, uint32_t bar) {
  asm volatile("st.async.weak.shared::cluster.mbarrier::complete_tx::bytes.b32 [%0], %1, [%2];" :: "r"(a), "r"(x), "r"(bar) : "memory");
}
DEVI void st_cl128(bool own, uint32_t a, uint32_t x, uint32_t y, uint32_t z, uint32_t w, uint32_t bar) {
  asm volatile("{.reg .pred p; setp.ne.u32 p, %6, 0; @p st.shared.v4.b32 [%0], {%1,%2,%3,%4};\n"
               "@!p st.async.weak.shared::cluster.mbarrier::complete_tx::bytes.v4.b32 [%0], {%1,%2,%3,%4}, [%5];}"
               :: "r"(a), "r"(x), "r"(y), "r"(z), "r"(w), "r"(bar), "r"((uint32_t)own) : "memory");
}
DEVI void st_cl32(bool own, uint32_t a, uint32_t x, uint32_t bar) {
  asm volatile("{.reg .pred p; setp.ne.u32 p, %3, 0; @p st.shared.b32 [%0], %1;\n"
               "@!p st.async.weak.shared::cluster.mbarrier::complete_tx::bytes.b32 [%0], %1, [%2];}" :: "r"(a), "r"(x), "r"(bar), "r"((uint32_t)own) : "memory");
}
DEVI uint4 ldg_rlx128(const void* p) {
  uint4 v;
  asm volatile("ld.relaxed.gpu.global.v4.b32 {%0,%1,%2,%3}, [%4];" : "=r"(v.x), "=r"(v.y), "=r"(v.z), "=r"(v.w) : "l"(p) : "memory");
  return v;
}
DEVI void stg_rlx128(void* p, uint32_t x, uint32_t y, uint32_t z, uint32_t w) {
  asm volatile("st.relaxed.gpu.global.v4.b32 [%0], {%1,%2,%3,%4};" :: "l"(p), "r"(x), "r"(y), "r"(z), "r"(w) : "memory");
}
DEVI void stg128(void* p, uint32_t x, uint32_t y, uint32_t z, uint32_t w) {
  asm volatile("st.global.v4.b32 [%0], {%1,%2,%3,%4};" :: "l"(p), "r"(x), "r"(y), "r"(z), "r"(w) : "memory");
}
DEVI void stg_rlx32(void* p, uint32_t x) { asm volatile("st.relaxed.gpu.global.b32 [%0], %1;" :: "l"(p), "r"(x) : "memory"); }
DEVI uint32_t clock32() { uint32_t c; asm volatile("mov.u32 %0, %%clock;" : "=r"(c) :: "memory"); return c; }
DEVI uint32_t gtime() { uint32_t c; asm volatile("mov.u32 %0, %%globaltimer_lo;" : "=r"(c) :: "memory"); return c; }
DEVI void wait_time(uint32_t t, int& budget) { while ((int)(gtime() - t) < 0 && --budget > 0) {} }
DEVI uint2 ldg_rlx64(const void* p) { uint2 v; asm volatile("ld.relaxed.gpu.global.v2.b32 {%0,%1}, [%2];" : "=r"(v.x), "=r"(v.y) : "l"(p) : "memory"); return v; }
DEVI void sts16(uint32_t a, uint32_t x) { asm volatile("st.shared.b16 [%0], %1;" :: "r"(a), "h"((unsigned short)x) : "memory"); }
DEVI void sts128(uint32_t a, uint32_t x) { asm volatile("st.shared.v4.b32 [%0], {%1,%1,%1,%1};" :: "r"(a), "r"(x) : "memory"); }
DEVI void arrive_if_eq(uint32_t bar, int a, int b) { asm volatile("{.reg .pred p; setp.eq.s32 p, %1, %2; @p mbarrier.arrive.shared::cta.b64 _, [%0];}" :: "r"(bar), "r"(a), "r"(b) : "memory"); }
DEVI void arrive_cl_if_eq(uint32_t bar, int a, int b) { asm volatile("{.reg .pred p; setp.eq.s32 p, %1, %2; @p mbarrier.arrive.shared::cluster.b64 _, [%0];}" :: "r"(bar), "r"(a), "r"(b) : "memory"); }
template<int ID, int N> DEVI bool nbar_or(bool x) {
  uint32_t r;
  asm volatile("{.reg .pred p, q; setp.ne.u32 p, %1, 0; bar.red.or.pred q, %2, %3, p; selp.u32 %0, 1, 0, q;}" : "=r"(r) : "r"((uint32_t)x), "n"(ID), "n"(N) : "memory");
  return __any_sync(0xffffffffu, r);
}
DEVI void spin_until(uint32_t t0, int d) { while ((int)(clock32() - t0) < d) {} }
DEVI void flag_wait(const int* p, int n, int& budget) {
  while (ld_acquire(p) < n && --budget > 0) __nanosleep(32);
  asm volatile("fence.proxy.async.global;" ::: "memory");
}

#define F4(C, o)  C(d[o+0]), C(d[o+1]), C(d[o+2]), C(d[o+3])
#define F8(C, o)  F4(C, o), F4(C, o+4)
#define F32(C, o) F8(C, o), F8(C, o+8), F8(C, o+16), F8(C, o+24)
#define R4  "{%0,%1,%2,%3}"
#define R8  "{%0,%1,%2,%3,%4,%5,%6,%7}"
#define R16 "{%0,%1,%2,%3,%4,%5,%6,%7,%8,%9,%10,%11,%12,%13,%14,%15}"
#define R20 "{%0,%1,%2,%3,%4,%5,%6,%7,%8,%9,%10,%11,%12,%13,%14,%15,%16,%17,%18,%19}"
#define R32 "{%0,%1,%2,%3,%4,%5,%6,%7,%8,%9,%10,%11,%12,%13,%14,%15,%16,%17,%18,%19,%20,%21,%22,%23,%24,%25,%26,%27,%28,%29,%30,%31}"
#define R64 "{%0,%1,%2,%3,%4,%5,%6,%7,%8,%9,%10,%11,%12,%13,%14,%15,%16,%17,%18,%19,%20,%21,%22,%23,%24,%25,%26,%27,%28,%29,%30,%31," \
  "%32,%33,%34,%35,%36,%37,%38,%39,%40,%41,%42,%43,%44,%45,%46,%47,%48,%49,%50,%51,%52,%53,%54,%55,%56,%57,%58,%59,%60,%61,%62,%63}"
template<uint32_t OFF, uint32_t LBO, uint32_t SBO, uint32_t SW, int T> struct Op {
  static constexpr uint32_t lo = (OFF >> 4) | ((LBO >> 4) << 16), hi = (SBO >> 4) | (SW << 30);
  static constexpr int t = T;
};
DEVI uint32_t desc_base(uint32_t addr) { return (addr & 0x3FFFF) >> 4; }
#define RS_ASM(SHAPE, REGS, A0, A1, A2, A3, B, LO, HI, T, SD) \
  "{.reg .b64 tb; .reg .b32 lb; add.u32 lb, " B ", " LO "; mov.b64 tb, {lb, " HI "};\n" \
  "wgmma.mma_async.sync.aligned." SHAPE ".f32.bf16.bf16 " REGS ", {" A0 "," A1 "," A2 "," A3 "}, tb, " SD ", 1, 1, " T ";}"
#define WG_RS(NAME, SHAPE, REGS, LIST, ...) \
  template<int ACC, class OB> DEVI void NAME(float* d, const uint32_t* a, uint32_t b) { \
    if (ACC) asm volatile(RS_ASM(SHAPE, REGS, __VA_ARGS__) \
      : LIST("+f") : "r"(a[0]), "r"(a[1]), "r"(a[2]), "r"(a[3]), "r"(b), "n"(OB::lo), "n"(OB::hi), "n"(OB::t), "n"(ACC & 1)); \
    else asm volatile(RS_ASM(SHAPE, REGS, __VA_ARGS__) \
      : LIST("=f") : "r"(a[0]), "r"(a[1]), "r"(a[2]), "r"(a[3]), "r"(b), "n"(OB::lo), "n"(OB::hi), "n"(OB::t), "n"(0)); \
  }
#define SS_ASM(SHAPE, REGS, A, B, LA, HA, TA, LB, HB, TB, SD) \
  "{.reg .b64 ta, tb; .reg .b32 la, lb; add.u32 la, " A ", " LA "; mov.b64 ta, {la, " HA "}; add.u32 lb, " B ", " LB "; mov.b64 tb, {lb, " HB "};\n" \
  "wgmma.mma_async.sync.aligned." SHAPE ".f32.bf16.bf16 " REGS ", ta, tb, " SD ", 1, 1, " TA ", " TB ";}"
#define WG_SS(NAME, SHAPE, REGS, LIST, ...) \
  template<int ACC, class OA, class OB> DEVI void NAME(float* d, uint32_t a, uint32_t b) { \
    if (ACC) asm volatile(SS_ASM(SHAPE, REGS, __VA_ARGS__) \
      : LIST("+f") : "r"(a), "r"(b), "n"(OA::lo), "n"(OA::hi), "n"(OA::t), "n"(OB::lo), "n"(OB::hi), "n"(OB::t), "n"(ACC & 1)); \
    else asm volatile(SS_ASM(SHAPE, REGS, __VA_ARGS__) \
      : LIST("=f") : "r"(a), "r"(b), "n"(OA::lo), "n"(OA::hi), "n"(OA::t), "n"(OB::lo), "n"(OB::hi), "n"(OB::t), "n"(0)); \
  }
#define L4(C)  F4(C, 0)
#define L8(C)  F8(C, 0)
#define L16(C) F8(C, 0), F8(C, 8)
#define L20(C) F8(C, 0), F8(C, 8), F4(C, 16)
#define L32(C) F32(C, 0)
WG_RS(wg_rs8, "m64n8k16", R4, L4, "%4", "%5", "%6", "%7", "%8", "%9", "%10", "%11", "%12")
WG_RS(wg_rs16, "m64n16k16", R8, L8, "%8", "%9", "%10", "%11", "%12", "%13", "%14", "%15", "%16")
WG_RS(wg_rs32, "m64n32k16", R16, L16, "%16", "%17", "%18", "%19", "%20", "%21", "%22", "%23", "%24")
WG_SS(wg_ss32, "m64n32k16", R16, L16, "%16", "%17", "%18", "%19", "%20", "%21", "%22", "%23", "%24")
WG_RS(wg_rs64, "m64n64k16", R32, L32, "%32", "%33", "%34", "%35", "%36", "%37", "%38", "%39", "%40")
WG_SS(wg_ss8, "m64n8k16", R4, L4, "%4", "%5", "%6", "%7", "%8", "%9", "%10", "%11", "%12")
WG_SS(wg_ss16, "m64n16k16", R8, L8, "%8", "%9", "%10", "%11", "%12", "%13", "%14", "%15", "%16")
WG_SS(wg_ss40, "m64n40k16", R20, L20, "%20", "%21", "%22", "%23", "%24", "%25", "%26", "%27", "%28")
WG_SS(wg_ss64, "m64n64k16", R32, L32, "%32", "%33", "%34", "%35", "%36", "%37", "%38", "%39", "%40")
#define L64(C) F32(C, 0), F32(C, 32)
WG_SS(wg_ss128, "m64n128k16", R64, L64, "%64", "%65", "%66", "%67", "%68", "%69", "%70", "%71", "%72")
template<int I> struct IC { __host__ __device__ constexpr operator int() const { return I; } };
template<int I, int N, class F> DEVI void sfor(F&& f) {
  if constexpr (I < N) { f(IC<I>{}); sfor<I + 1, N>(f); }
}

#define R_CL 6
namespace rec {
constexpr int NHI = 36, NLO = 5, NRS = NHI + NLO, NSS = 64 - NRS;
constexpr uint32_t WS = 0;
constexpr uint32_t WO = 2 * NSS * 2048;
constexpr uint32_t RING = WO + 65536;
constexpr uint32_t QB = RING + 40960, RG = 2080, POSQ = 0x64210, POSK = 0xB9753, POSV = 0xEDCA8;
#define JA 2
constexpr uint32_t WA = QB;
constexpr uint32_t OM = QB + 9 * RG, OMS = 2 * RG;
constexpr uint32_t OM2 = QB + 16384, OM2S = 2048;
constexpr uint32_t WH = QB + 20480;
constexpr uint32_t B_PART = QB + 15 * RG - 32;
constexpr uint32_t PM0 = QB + 16384, PM1 = QB + 15 * RG, PM2 = PM1 + 256;
constexpr uint32_t BARS = PM2 + 128;
constexpr uint32_t B_FULL = BARS, B_EMPTY = BARS + 40, B_MLAND = BARS + 80, B_QK = BARS + 112, B_V = BARS + 120, B_OM = BARS + 128,
                   B_WA = BARS + 136, B_SDONE = BARS + 144, B_BFREE = BARS + 152, B_W1 = PM1, B_W2 = PM1 + 8, B_WO = PM1 + 16;
constexpr uint32_t SMEM = BARS + 160;
static_assert(SMEM <= 232448 && QB % 1024 == 0, "smem map");
constexpr int R1 = (PM1 - WO) / 4096;
constexpr int NB_WO = 1, NB_ST = 2, NB_P = 3, NB_TR = 4, NB_X = 5, NB_G = 6, NB_G1 = 7, NB_G2 = 8, NB_G4 = 9, NB_S = 10;
__host__ __device__ constexpr bool is_lo(int j) { return j % 12 == 8; }
__host__ __device__ constexpr int lo_before(int j) { return (j + 3) / 12; }
__host__ __device__ constexpr int ss_before(int j) { return (j - lo_before(j)) * NSS / (64 - NLO); }
__host__ __device__ constexpr bool is_ss(int j) { return ss_before(j + 1) != ss_before(j); }
__host__ __device__ constexpr int reg_idx(int j) { return is_lo(j) ? NHI + lo_before(j) : j - ss_before(j) - lo_before(j); }
#define LOQ(i) ((0x12010 >> (4 * (i))) & 3)
template<int j> using OpW = Op<WS + ss_before(j) * 2048, 16, 1024, 1, 1>;
#define P_G1 1
#define P_G2 3
#define P_G2L 0
#define P_OS 1
#define P_NA 6
#define P_G4 10
#define P_G5 12
#define P_FW 0
#define P_SEND 0xff3f2f10u
#define P_WB 2
#define P_WOL 0
#define P_G4L 0
#define P_S1 1
#define P_S2 2
#define P_S0 3
#define P_MB 0
#define P_S4 5
#define P_S5 6
constexpr uint32_t SLOT1 = 0x32410324, USE1 = 0x22111110;
DEVI bool single(int s) { return s < LAG - 1 || s >= NSEG - 1; }
#define TUN(i, v) (v)
}
#define PROFW(wq, i)
DEVI uint32_t mapr(int h, uint32_t addr, int rank) { return mapa(addr, rank + (R_CL == 6 ? (h & 1) * 3 : 0)); }
template<int N> DEVI void pin(float* d) {
#pragma unroll
  for (int i = 0; i < N; i++) asm volatile("" : "+f"(d[i]) :: "memory");
}
DEVI void keep(const void* a) { asm volatile("{.reg .pred p; setp.eq.u64 p, %0, 0; vote.sync.any.pred p, p, 0xffffffff; @p exit;}" :: "l"(a) : "memory"); }
DEVI int lane_reg() { return __shfl_sync(0xffffffffu, threadIdx.x & 31, threadIdx.x & 31); }
#define LANE_NOW [[maybe_unused]] const int lane = lane0 + ((uint32_t)budget >> 30), g = lane >> 2, c = lane & 3

DEVI void rec_proj(const uint32_t sb, const int h, const int rank, const int w, const CUtensorMap* mW, const CUtensorMap* mWo, const uint32_t zero) {
  using namespace rec;
  const int lane0 = lane_reg(), wg = w >> 2, ww = w & 3;
  int budget = SPIN_BUDGET;
  uint32_t wr[NRS * 4];
  {
    LANE_NOW;
    const uint32_t wsw = ((lane & 7) + (lane >> 4) * 8) * 128 + (((ww * 2 + ((lane >> 3) & 1)) ^ (lane & 7)) << 4);
    mbar_wait(sb + B_W1, 0, budget);
#pragma unroll
    for (int r = 0; r < R1; r++) ldsm4t(sb + WO + (wg * R1 + r) * 2048 + wsw, wr[4*r], wr[4*r+1], wr[4*r+2], wr[4*r+3]);
    fence_proxy_async();
    nbar_sync<NB_ST, 256>();
    if (w == 0) {
      if (lane == 0) { mbar_expect_tx(sb + B_W2, (NRS - R1) * 4096); mbar_expect_tx(sb + B_WO, rank == 2 ? 65536 + 16384 + 8192 : 65536); }
      __syncwarp();
      for (int i = lane; i < 128; i += 32) {
        const int j = i & 63, t = i >> 6, r = reg_idx(j);
        if (!is_ss(j) && r >= R1) tma_load_2d(sb + RING + (t * (NRS - R1) + r - R1) * 2048, mW, h * DH + t * 64, j * 16, sb + B_W2);
      }
      const int t0 = (rank + 1) % 3;
      if (lane < 8) tma_load_2d(sb + WO + lane * 8192, mWo, (3 * ((lane >> 1) + (lane >> 1 >= JA)) + t0) * 64, h * DH + (lane & 1) * 64, sb + B_WO);
      else if (rank == 2 && lane < 11) tma_load_2d(lane < 10 ? sb + WA + (lane - 8) * 8192 : sb + WH, mWo, lane < 10 ? 3 * JA * 64 : 15 * 64, h * DH + (lane > 8) * 64, sb + B_WO);
    }
    mbar_wait(sb + B_W2, 0, budget);
#pragma unroll
    for (int r = R1; r < NRS; r++) ldsm4t(sb + RING + (wg * (NRS - R1) + r - R1) * 2048 + wsw, wr[4*r], wr[4*r+1], wr[4*r+2], wr[4*r+3]);
    fence_proxy_async();
    cluster_arrive(); cluster_wait();
  }
  const uint32_t d0 = desc_base(sb), da = d0 + wg * (NSS * 128);
  const uint32_t pos = rank == 0 ? POSQ : rank == 1 ? POSK : POSV, bar = rank == 2 ? B_V : B_QK;
  uint32_t stg[3][4] = {}, pk[16] = {};
  auto stage = [&](uint32_t* t, int r) {
#pragma unroll
    for (int i = 0; i < 4; i++) asm volatile("xor.b32 %0, %1, %2;" : "+r"(t[i]) : "r"(wr[4 * r + i]), "r"(zero));
  };
#pragma unroll 1
  for (int s = -1; s < NSTEP; s++) {
    const uint32_t fl = single(s) ? (s + 1) & 1 : 0;
    if (s >= 0) {
      float d[8];
      stage(stg[0], NHI);
      mbar_wait(sb + B_FULL, 0, budget);
      PROFW(0, 16);
      sfor<0, 8>([&](auto E) {
        constexpr int e = E, q = e >> 1;
        wg_fence();
        sfor<8 * e, 8 * e + 8>([&](auto J) {
          constexpr int j = J;
          typedef Op<RING + j * 512, 256, 128, 0, 1> OB;
          if constexpr (is_ss(j)) wg_ss16<j != 0, OpW<j>, OB>(d, da, d0);
          else wg_rs16<j != 0, OB>(d, is_lo(j) ? stg[LOQ(lo_before(j))] : wr + 4 * reg_idx(j), d0);
        });
        wg_commit();
        if constexpr (e == 0) { if (s > 0) mbar_wait(sb + B_BFREE, (s & 1) ^ 1, budget); }
        if constexpr (e > 0 && !(e & 1)) {
          wg_wait<1>();
          arrive_if_eq(sb + B_EMPTY + 8 * (q - 1), lane0, ww * 32);
        }
        if constexpr (e < 6 && !(e & 1)) sfor<lo_before(16 * q + 16), lo_before(16 * q + 32)>([&](auto I) { constexpr int i = I; stage(stg[LOQ(i)], NHI + i); });
        if constexpr (e < 6 && (e & 1) == P_FW) mbar_wait(sb + B_FULL + 8 * (q + 1), q ? fl : 0, budget);
        if constexpr (((P_SEND >> (4 * e)) & 15) < 4) {
          constexpr int n = (P_SEND >> (4 * e)) & 15;
          LANE_NOW;
          const uint32_t r = mapr(h, sb, n >> 1);
          uint32_t t[4];
#pragma unroll
          for (int i = 0; i < 4; i++) { if (n == 0) t[i] = pk[i]; else asm volatile("xor.b32 %0, %1, %2;" : "=r"(t[i]) : "r"(pk[4*n+i]), "r"(zero)); }
          st_cl128(rank == n >> 1, r + QB + ((pos >> (4 + 4 * c)) & 15) * RG + w * 256 + (n & 1) * 128 + g * 16, t[0], t[1], t[2], t[3], r + bar);
        }
      });
      LANE_NOW;
      const uint32_t dst = QB + (pos & 15) * RG + w * 256 + lane * 4;
      wg_wait<0>();
      pin<8>(d);
      {
        const uint32_t x0 = pack_bf16(d[0], d[1]), x1 = pack_bf16(d[2], d[3]), y0 = pack_bf16(d[4], d[5]), y1 = pack_bf16(d[6], d[7]);
        const uint32_t r = mapr(h, sb, rank == 0);
        if (rank < 2) { sts32v(sb + dst, rank ? y0 : x0); sts32v(sb + dst + 128, rank ? y1 : x1); fence_proxy_async(); }
        st_async32(r + dst, rank ? x0 : y0, r + bar); st_async32(r + dst + 128, rank ? x1 : y1, r + bar);
        if (rank < 2) e_arrive(sb + B_QK);
        else { const uint32_t r1 = mapr(h, sb, 1); st_async32(r1 + dst, y0, r1 + bar); st_async32(r1 + dst + 128, y1, r1 + bar); }
      }
      PROFW(0, 17);
      if (s == NSTEP - 1) break;
      arrive_if_eq(sb + B_EMPTY + 24, lane0, ww * 32);
    } else e_arrive(sb + B_EMPTY + 8 * ww);
    const bool gate = rank < 2 && s >= 0;
    if (single(s)) {
      float d[16];
      sfor<0, 8>([&](auto C) {
        constexpr int cc = C, sl = (SLOT1 >> (4 * cc)) & 15;
        if constexpr (cc == 0) mbar_wait(sb + B_FULL + 8 * sl, 0, budget);
        if constexpr (cc == P_S1) { if (gate) nbar_sync<NB_G1, 384>(); }
        if constexpr (cc == P_S2) { if (gate) nbar_sync<NB_G2, 384>(); }
        if constexpr (cc == P_S0) nbar_sync<NB_WO, 384>();
        if constexpr (cc == P_S4 || cc == P_S5) { if (gate && cc == (rank ? P_S5 : P_S4)) nbar_sync<NB_G4, 384>(); }
        if constexpr (lo_before(cc * 8 + 8) != lo_before(cc * 8)) stage(stg[0], NHI + lo_before(cc * 8));
        wg_fence();
        sfor<0, 8>([&](auto I) {
          constexpr int i = I, j = cc * 8 + i;
          typedef Op<RING + sl * 8192 + (i >> 2) * 4096 + (i & 3) * 32, 16, 1024, 1, 0> OB;
          if constexpr (is_ss(j)) wg_ss32<j != 0, OpW<j>, OB>(d, da, d0);
          else wg_rs32<j != 0, OB>(d, is_lo(j) ? stg[0] : wr + 4 * reg_idx(j), d0);
        });
        wg_commit();
        if constexpr (cc < 7) {
          constexpr int sn = (SLOT1 >> (4 * cc + 4)) & 15;
          mbar_wait(sb + B_FULL + 8 * sn, ((USE1 >> (4 * cc + 4)) & 1) ^ (sn >> 1 == 1 ? fl : 0), budget);
        }
        wg_wait<0>();
        arrive_if_eq(sb + B_EMPTY + 8 * sl, lane0, ww * 32);
      });
      pin<16>(d);
      PROFW(0, 20);
#pragma unroll
      for (int i = 0; i < 8; i++) pk[i] = pk[8 + i] = pack_bf16(d[4 * (i & 3) + ((i >> 1) & 2)], d[4 * (i & 3) + ((i >> 1) & 2) + 1]);
      continue;
    }
    float d[32];
    sfor<0, 16>([&](auto C) {
      constexpr int cc = C, sl = (cc + 4) % 5;
      if constexpr (cc == 0) mbar_wait(sb + B_FULL + 8 * sl, 0, budget);
      if constexpr (cc == P_G1) { if (gate) nbar_sync<NB_G1, 384>(); }
      if constexpr (cc == P_G2) { if (gate) nbar_sync<NB_G2, 384>(); }
      if constexpr (cc == P_NA) {
        PROFW(0, 18);
        nbar_sync<NB_WO, 384>();
      }
      if constexpr (cc == P_G4 || cc == P_G5) { if (gate && cc == (rank ? P_G5 : P_G4)) nbar_sync<NB_G4, 384>(); }
      wg_fence();
      sfor<0, 4>([&](auto I) {
        constexpr int i = I, j = cc * 4 + i;
        typedef Op<RING + sl * 8192 + i * 32, 16, 1024, 1, 0> OB;
        if constexpr (is_ss(j)) wg_ss64<j != 0, OpW<j>, OB>(d, da, d0);
        else wg_rs64<j != 0, OB>(d, is_lo(j) ? stg[0] : wr + 4 * reg_idx(j), d0);
      });
      wg_commit();
      if constexpr (cc == P_NA) PROFW(0, 19);
      if constexpr (cc < 15) {
        if constexpr (is_lo(cc * 4 + 4)) stage(stg[0], reg_idx(cc * 4 + 4));
        mbar_wait(sb + B_FULL + 8 * ((sl + 1) % 5), ((cc + 5) / 5) & 1, budget);
      }
      wg_wait<0>();
      arrive_if_eq(sb + B_EMPTY + 8 * sl, lane0, ww * 32);
    });
    pin<32>(d);
    PROFW(0, 20);
#pragma unroll
    for (int i = 0; i < 16; i++) pk[i] = pack_bf16(d[16 * (i >> 3) + 4 * (i & 3) + ((i >> 1) & 2)], d[16 * (i >> 3) + 4 * (i & 3) + ((i >> 1) & 2) + 1]);
  }
}

DEVI float softmax_row(float* v, uint32_t* p) {
  constexpr float SC = 0.08838834764831845f * 1.4426950408889634f;
  float m = fmaxf(fmaxf(fmaxf(fmaxf(v[0], v[1]), fmaxf(v[2], v[3])), fmaxf(fmaxf(v[4], v[5]), fmaxf(v[6], v[7]))), fmaxf(v[8], v[9]));
  m = fmaxf(m, __shfl_xor_sync(0xffffffffu, m, 1));
  m = fmaxf(m, __shfl_xor_sync(0xffffffffu, m, 2));
  const float ms = -m * SC, mh = fmaf(m, -SC, -1.f);
#pragma unroll
  for (int i = 0; i < 10; i++) asm("ex2.approx.ftz.f32 %0, %1;" : "=f"(v[i]) : "f"(fmaf(v[i], SC, i < 8 ? ms : mh)));
#pragma unroll
  for (int n = 0; n < 5; n++) p[n] = pack_bf16(v[2*n], v[2*n+1]);
  return fmaf(v[8] + v[9], 2.f, ((v[0] + v[1]) + (v[2] + v[3])) + ((v[4] + v[5]) + (v[6] + v[7])));
}

template<bool ATT>
DEVI void rec_attn(const uint32_t sb, int h, int rank, int w, const bf16* __restrict__ Wo, const bf16* __restrict__ mem0) {
  using namespace rec;
  const int lane0 = lane_reg();
  int budget = SPIN_BUDGET;
  constexpr int NT = ATT ? 5 : 6;
  uint32_t wl[16];
  if (!ATT) {
    LANE_NOW;
#pragma unroll
    for (int i = 0; i < 16; i++) {
      const int dh = 8 * (i >> 1) + 2 * c;
      const unsigned short* p = (const unsigned short*)Wo + (size_t)(h * DH + dh) * DM + 15 * 64 + 16 * w + 8 * (i & 1) + g;
      wl[i] = p[0] | (uint32_t)p[DM] << 16;
    }
  }
  mbar_wait(sb + B_WO, 0, budget);
  cluster_arrive(); cluster_wait();
  const uint32_t d0 = desc_base(sb);
  uint32_t pph = 0;
#pragma unroll 1
  for (int s = -1; s < NSTEP; s++) {
    asm volatile("" : "+r"(h), "+r"(rank), "+r"(w));
    const uint32_t sp = s & 1;
    const int t0 = ATT ? rank + 1 : 0;
    const bool more = s + 1 < NSTEP;
    float hold[10] = {0, 0, 0, 0, 0, 0, 0, 0, 0, 0};
    if (ATT && s >= 0) {
      float sc[20];
      LANE_NOW;
      mbar_wait(sb + B_QK, sp, budget);
      PROFW(0, 1);
      fence_proxy_async();
      wg_fence();
      sfor<0, 8>([&](auto K) { constexpr int k = K; wg_ss40<k != 0, Op<QB + k * 256, 128, RG, 0, 1>, Op<QB + 3 * RG + k * 256, 128, 2 * RG, 0, 1>>(sc, d0, d0); });
      wg_commit();
      if (P_G1 < 16 && more) nbar_arrive<NB_G1, 384>();
      mbar_wait(sb + B_V, sp, budget);
      wg_wait<0>();
      pin<20>(sc);
      if (w == 3 && more) nbar_arrive<NB_S, 64>();
      PROFW(1, 2);
      if (w == 0) {
        uint32_t p[5];
        float v[10];
#pragma unroll
        for (int i = 0; i < 10; i++) v[i] = sc[4 * (i >> 1) + (i & 1)];
        softmax_row(v, p);
        const uint32_t a = sb + lane * 4;
        sts32v(a + PM0, p[0]); sts32v(a + PM0 + 128, p[1]); sts32v(a + PM1, p[2]); sts32v(a + PM1 + 128, p[3]); sts32v(a + PM2, p[4]);
      }
      if (more) {
        float rs[4], ot[2][4];
        uint32_t one[4];
#pragma unroll
        for (int i = 0; i < 4; i++) one[i] = 0x3F803F80u + ((uint32_t)budget >> (31 - i));
        typedef Op<PM0, 128, 128, 0, 0> P0; typedef Op<PM1, 128, 128, 0, 0> P1; typedef Op<PM2, 0, 128, 0, 0> P2;
        fence_proxy_async();
        nbar_sync<NB_P, 128>();
        PROFW(0, 3);
        wg_fence();
        wg_rs8<0, P0>(rs, one, d0); wg_rs8<1, P1>(rs, one, d0); wg_rs8<1, P2>(rs, one, d0);
        wg_commit();
        sfor<0, 2>([&](auto T) {
          constexpr int t = T;
          wg_ss8<0, Op<QB + 8 * RG + t * 1024, 2 * RG, 128, 0, 0>, P0>(ot[t], d0, d0);
          wg_ss8<1, Op<QB + 12 * RG + t * 1024, RG, 128, 0, 0>, P1>(ot[t], d0, d0);
          wg_ss8<1, Op<QB + 14 * RG + t * 1024, 0, 128, 0, 0>, P2>(ot[t], d0, d0);
        });
        wg_commit();
        if (P_G2 < 16 && !P_G2L) nbar_arrive<NB_G2, 384>();
        const uint32_t oa = w * 256 + lane * 4, r1 = mapr(h, sb, rank ^ 1), r2 = mapr(h, sb, 2);
        mbar_wait(sb + B_SDONE, sp, budget);
        wg_wait<1>();
        pin<4>(rs);
        float i0, i1;
        asm volatile("rcp.approx.ftz.f32 %0, %1;" : "=f"(i0) : "f"(rs[0]));
        asm volatile("rcp.approx.ftz.f32 %0, %1;" : "=f"(i1) : "f"(rs[1]));
        wg_wait<0>();
        pin<4>(ot[0]); pin<4>(ot[1]);
        uint32_t x[4];
#pragma unroll
        for (int j = 0; j < 4; j++) {
          x[j] = pack_bf16(ot[j >> 1][2 * (j & 1)] * i0, ot[j >> 1][2 * (j & 1) + 1] * i1);
          sts32v(sb + OM + rank * OMS + oa + (j >> 1) * 1024 + (j & 1) * 128, x[j]);
        }
        fence_proxy_async();
#pragma unroll
        for (int j = 0; j < 8; j++) {
          const int i = P_OS ? j >> 1 : j & 3;
          if (P_OS ? j & 1 : j >> 2) st_async32(r1 + OM + rank * OMS + oa + (i >> 1) * 1024 + (i & 1) * 128, x[i], r1 + B_OM);
          else st_async32(r2 + OM2 + rank * OM2S + oa + (i >> 1) * 1024 + (i & 1) * 128, x[i], r2 + B_OM);
        }
        e_arrive(sb + B_OM);
        if (P_G2 < 16 && P_G2L) nbar_arrive<NB_G2, 384>();
        PROFW(0, 4);
      }
#pragma unroll
      for (int i = 0; i < 10; i++) hold[i] = w ? sc[4 * (i >> 1) + (i & 1)] : sc[4 * (i >> 1) + 2 + (i & 1)];
    }
    if (more && s >= 0) {
      LANE_NOW;
      char* const pw = (char*)g_part + (uint32_t)((t0 * 16 + w * 4 + (lane >> 3)) * 4096 + h * 128 + ((lane ^ h) & 7) * 16);
      mbar_wait(sb + B_OM, sp, budget);
      if (w == 0) nbar_arrive<NB_G, 128>();
      PROFW(1, 5);
      if (!ATT) fence_proxy_async();
      float acc[3][8];
      auto store = [&](auto J) {
        constexpr int j = J;
        float* d = acc[j % 3];
        pin<8>(d);
        uint32_t x[4];
#pragma unroll
        for (int i = 0; i < 4; i++) { const uint32_t m = (h >> 3) == i; x[i] = (pack_bf16(d[2*i], d[2*i+1]) & ~m) | (m & ~sp); }
        stg_rlx128(pw + j * (48 * 4096), x[0], x[1], x[2], x[3]);
        if constexpr (ATT && j == JA) nbar_arrive<NB_TR, 160>();
        if constexpr (j == 2) PROFW(3, 26);
      };
      sfor<0, NT>([&](auto J) {
        constexpr int j = J;
        if constexpr (ATT && j == JA) { mbar_wait(sb + B_WA, sp, budget); PROFW(2, 0); }
        wg_fence();
        sfor<0, 8>([&](auto K) {
          constexpr int k = K;
          typedef Op<(ATT ? OM : OM2) + k * 256, 128, ATT ? OMS : OM2S, 0, 1> OB;
          if constexpr (j == 5 && k < 4) wg_rs16<k ? 1 : 2, OB>(acc[j % 3], wl + 4 * k, d0);
          else wg_ss16<k ? 1 : j < 3 ? 0 : 2, Op<(j == JA ? WA : j < 5 ? WO + (j - (j > JA)) * 16384 : WH - 8192) + k * 2048, 16, 1024, 1, 1>, OB>(acc[j % 3], d0, d0);
        });
        wg_commit();
        if constexpr (j == 0) { if (w == 3) e_expect_tx(sb + B_OM, ATT ? 2048 : 4096); }
        if constexpr (j == NT - 1 && !P_WOL) nbar_arrive<NB_WO, 384>();
        if constexpr (j > 0 && j != P_WB + 1) { wg_wait<1>(); store(IC<j - 1>{}); }
        if constexpr (j == P_WB || j == NT - 1) { wg_wait<0>(); store(IC<j>{}); }
        if constexpr (j == P_WB) {
          const uint32_t t = clock32();
          if (ATT) {
            if (w == 3 && lane < 14) sts128(sb + PM1 + lane * 16, (lane >> 1) == 3 ? 0x3F803F80u : 0);
            if (w == 3 || P_MB) fence_proxy_async();
            nbar_sync<NB_P, 128>();
          } else if (P_MB) fence_proxy_async();
          spin_until(t, TUN(8, 100));
        }
      });
      if (P_WOL) { spin_until(clock32(), TUN(9, 0)); nbar_arrive<NB_WO, 384>(); }
    } else if (more) nbar_arrive<NB_WO, 384>();
    PROFW(0, 6);
    asm volatile("" : "+r"(h), "+r"(rank), "+r"(w));
#pragma unroll 1
    for (int pass = 0; ATT && pass < 2; pass++)
    if (pass != rank) {
      LANE_NOW;
      const int lim = 8 * (g >> 1) + (g & 1) + 2 * w - 8 * c;
      uint32_t p[5];
#pragma unroll
      for (int i = 0; i < 8; i++) hold[2+i] = i <= lim ? hold[2+i] : -INFINITY;
      const float psum = softmax_row(hold, p);
#pragma unroll
      for (int i = 0; i < 5; i++) hold[i] = __uint_as_float(p[i]);
      hold[5] = psum;
    } else if (more) {
      LANE_NOW;
      const int blk = rank * 32 + h;
      char* const mw = (char*)g_mem + (uint32_t)(sp * 32768 + blk * 512 + w * 128 + lane * 4);
      uint32_t v0 = 0;
      if (s == -1 || (s == LAG - 1 && (w & 1))) {
        const unsigned short* q = (const unsigned short*)mem0 + c * 2 * DM + blk * 16 + (w >> 1) * 8 + g;
        v0 = q[0] | (uint32_t)q[DM] << 16;
        if (v0 == 0) v0 = 0x8000u;
      }
      keep(mw);
      if (s >= 0) {
        const uint32_t ca = sb + WA + lane * 128 + (((2 * w) ^ lane) & 7) * 16 + (lane >> 3) * 4;
        const uint32_t sa = sb + OM + (((g >> 1) & 1) * 2 + (g >> 2)) * 128 + (2 * c + (w >> 1)) * 16 + (w & 1) * 8 + (g & 1) * 2;
        for (bool first = true; ; first = false) {
          float r[4];
          mbar_wait(sb + B_PART, pph, budget);
          PROFW(0, 11);
          pph ^= 1;
          wg_fence();
          sfor<0, 8>([&](auto K) { constexpr int k = K; wg_ss8<k != 0, Op<WA + k * 2048, 16, 1024, 1, 1>, Op<PM1 + (6 - (k & 6)) * 16, 0, 128, 0, 0>>(r, d0, d0); });
          wg_commit();
          if (P_G4 < 16 && !P_G4L && first) nbar_arrive<NB_G4, 384>();
          const uint32_t x0 = lds32v(ca), x1 = lds32v(ca + 4096), x2 = lds32v(ca + 8192), x3 = lds32v(ca + 12288);
          bool bad = __any_sync(0xffffffffu, (sp ? x0 | x1 | x2 | x3 : ~(x0 & x1 & x2 & x3)) & 1) && budget > 0;
          wg_wait<0>();
          pin<4>(r);
          uint32_t y = pack_bf16(r[0], r[2]);
          y |= (y & 0xffffu) ? 0 : 0x8000u;
          y |= (y >> 16) ? 0 : 0x80000000u;
          if (bad) y = 0;
          sts16(sa, y); sts16(sa + 4, y >> 16);
          nbar_sync<NB_P, 128>();
          y = lds32v(sb + OM + w * 128 + lane * 4);
          const bool ok = !__any_sync(0xffffffffu, y == 0);
          if (ok) stg_rlx32(mw, v0 ? v0 : y);
          if (P_G4 < 16 && P_G4L && first) nbar_arrive<NB_G4, 384>();
          if (ok) break;
          nbar_sync<NB_P, 128>();
          budget--;
          if (w == 0) { e_expect_tx(sb + B_PART, 16384); e_bulk_g2s(sb + WA, (const char*)g_part + blk * 16384, 16384, sb + B_PART); }
          __syncwarp();
        }
      } else stg_rlx32(mw, v0);
      stg_rlx32(mw + (sp ? -32768 : 32768), 0);
      PROFW(1, 8);
    }
    if (ATT && s >= 0) {
      const int seg = s - (rank ? LAG : 0);
      const bool act = (unsigned)seg < NSEG;
      LANE_NOW;
      uint32_t a[12];
#pragma unroll
      for (int i = 0; i < 12; i++) a[i] = __float_as_uint(hold[i < 10 ? i >> 1 : 4]) + ((uint32_t)budget >> (31 - (i & 3)));
      float o[32], inv, psum = hold[5];
      char* const ob = (char*)g_o[rank] + ((size_t)(seg * 32 + 8 * (g >> 1) + (g & 1) + 2 * w) * (NH * DH) + h * DH + c * 8) * 2;
      sfor<0, 2>([&](auto HF) {
        constexpr int hf = HF;
        wg_fence();
        wg_rs64<hf * 2, Op<QB + 8 * RG + hf * 1024, 2 * RG, 128, 0, 0>>(o, a, d0);
        wg_rs64<1, Op<QB + 12 * RG + hf * 1024, RG, 128, 0, 0>>(o, a + 4, d0);
        wg_rs64<1, Op<QB + 14 * RG + hf * 1024, 0, 128, 0, 0>>(o, a + 8, d0);
        wg_commit();
        if constexpr (hf == 0) {
          psum += __shfl_xor_sync(0xffffffffu, psum, 1);
          psum += __shfl_xor_sync(0xffffffffu, psum, 2);
          asm("rcp.approx.ftz.f32 %0, %1;" : "=f"(inv) : "f"(psum));
        }
        wg_wait<0>();
        pin<32>(o);
        if constexpr (hf == 1) { if (w < 3 && more) e_arrive_cl(mapr(h, sb + B_BFREE, w)); }
        if (act) {
#pragma unroll
          for (int i = 0; i < 2; i++)
            stg128(ob + (hf * 2 + i) * 64, pack_bf16(o[16*i] * inv, o[16*i+1] * inv), pack_bf16(o[16*i+4] * inv, o[16*i+5] * inv),
                   pack_bf16(o[16*i+8] * inv, o[16*i+9] * inv), pack_bf16(o[16*i+12] * inv, o[16*i+13] * inv));
        }
      });
      PROFW(0, 7);
      if (act && (seg & 3) == 3) {
        __syncwarp();
        e_flag_add(g_fl.dep + grp(0, rank, seg >> 2));
      }
    } else if (!ATT && w == 3) {
      if (s + 4 < NSEG) e_prefetch(g_xn[0] + (size_t)((s + 4) * 32 + h) * DM, 2048);
    }
  }
  cluster_arrive(); cluster_wait();
  char* const pw = (char*)g_part + (size_t)((ATT ? rank + 1 : 0) * 16 + w * 4 + (lane0 >> 3)) * 4096 + h * 128 + (lane0 & 7) * 16;
#pragma unroll
  for (int j = 0; j < NT; j++) stg_rlx128(pw + j * (48 * 4096), 0, 0, 0, 0);
}

DEVI void rec_load(const uint32_t sb, const int h, const int rank, const int w, const CUtensorMap* mX, const CUtensorMap* mWo) {
  using namespace rec;
  static_assert(((NSTEP - 1) & 31) != 1 && ((NSTEP - 2) & 31) != 2, "stale time stamps of the previous launch never match");
  const int lane0 = lane_reg(), mq = (w + 3) & 3;
  int budget = SPIN_BUDGET;
  cluster_arrive(); cluster_wait();
  if (w == 0) { if (lane0 < 4) mbar_arrive(sb + B_FULL + 8 * lane0); __syncwarp(); }
  uint32_t lph = 0;
#pragma unroll 1
  for (int s = -1; s < NSTEP - 1; s++) {
    if (w == 0) {
      const int sa = s + 1, sn = sa - LAG;
      if ((sa & 3) == 0 && sa < NSEG) flag_wait(g_fl.xn[0][sa >> 2], 128, budget);
      if ((sn & 3) == 0 && (unsigned)sn < NSEG) flag_wait(g_fl.xn[1][sn >> 2], 128, budget);
      if (single(s)) {
#pragma unroll 1
        for (int i = 0; i < 8; i++) {
          const int k = i < 5 ? (0x21430 >> (4 * i)) & 15 : i;
          const int sl = (SLOT1 >> (4 * k)) & 15;
          mbar_wait(sb + B_EMPTY + 8 * sl, (((USE1 >> (4 * k)) ^ (sl >> 1 == 1 ? s + 1 : 0)) & 1) ^ 1, budget);
          e_expect_tx(sb + B_FULL + 8 * sl, 8192);
          e_tma_3d(sb + RING + sl * 8192, mX + 1, 0, (s + 1 + (s < LAG ? 0 : NSTEP)) * 32, k * 2, sb + B_FULL + 8 * sl);
        }
      } else {
        int sl = 4, ph = 1;
#pragma unroll 1
        for (int i = 0; i < 16; i++) {
          mbar_wait(sb + B_EMPTY + 8 * sl, ph, budget);
          e_expect_tx(sb + B_FULL + 8 * sl, 8192);
          e_tma_3d(sb + RING + sl * 8192, mX, i * 64, (s + 1) * 32, 0, sb + B_FULL + 8 * sl);
          if (++sl == 5) { sl = 0; ph ^= 1; }
        }
      }
      nbar_arrive<NB_X, 128>();
    }
    uint32_t t = gtime();
    if (s >= 0) {
      uint2 a;
      if (w == 2 && rank < 2) {
        nbar_sync<NB_S, 64>();
        e_expect_tx(sb + B_WA, 16384);
        e_tma_2d(sb + WA, mWo, (3 * JA + 1 + rank) * 64, h * DH, sb + B_WA);
        e_tma_2d(sb + WA + 8192, mWo, (3 * JA + 1 + rank) * 64, h * DH + 64, sb + B_WA);
        e_arrive_cl(mapr(h, sb + B_SDONE, rank ^ 1));
        stg_rlx32(&g_ann[s & 1][lane0][h * 2 + rank], (gtime() & ~31u) | ((s + 1) & 31));
        e_expect_tx(sb + B_QK, 10240);
        e_expect_tx(sb + B_V, 10240);
      }
      if (w) nbar_sync<NB_G, 128>();
      do { a = ldg_rlx64(&g_ann[s & 1][h][lane0 * 2]); } while (__any_sync(0xffffffffu, ((a.x ^ (s + 1)) | (a.y ^ (s + 1))) & 31) && --budget > 0);
      t += __reduce_max_sync(0xffffffffu, max((int)(a.x - t), (int)(a.y - t)));
      t = (t & ~31u) - (single(s) ? TUN(6, 200) : 0);
      PROFW(1, 12);
      if (w == 1 && rank < 2) {
        nbar_sync<NB_TR, 160>();
        wait_time(t + (rank ? TUN(1, 1750) : TUN(0, 1400)), budget);
        e_expect_tx(sb + B_PART, 16384);
        e_bulk_g2s(sb + WA, (const char*)g_part + (rank * 32 + h) * 16384, 16384, sb + B_PART);
        PROFW(1, 21);
      }
      t -= single(s) ? TUN(7, 150) : 0;
      t += mq == 0 ? TUN(2, 2450) : mq == 1 ? TUN(3, 2500) : mq == 2 ? TUN(4, 2800) : TUN(5, 2850);
    }
    if (w) nbar_sync<NB_X, 128>();
    mbar_wait(sb + B_EMPTY + 8 * mq, mq >= 2 && single(s) ? (s + 1) & 1 : 1, budget);
    PROFW(1, 9);
    wait_time(t, budget);
    PROFW(1, 22); PROFW(3, 23);
    while (true) {
      e_expect_tx(sb + B_MLAND + 8 * mq, 8192);
      e_bulk_g2s(sb + RING + mq * 8192, (const char*)g_mem + (s & 1) * 32768 + mq * 8192, 8192, sb + B_MLAND + 8 * mq);
      const uint32_t a = sb + RING + mq * 8192 + lane0 * 32 + (lane0 >> 2) * 4;
      mbar_wait(sb + B_MLAND + 8 * mq, lph, budget);
      lph ^= 1;
      PROFW(1, 24);
      uint32_t mn = 0xffffffffu;
#pragma unroll
      for (int i = 0; i < 8; i++) mn = min(mn, lds32v(a + i * 1024));
      if (!__any_sync(0xffffffffu, mn == 0) || --budget <= 0) break;
    }
    e_arrive(sb + B_FULL + 8 * mq);
    PROFW(1, 10); PROFW(2, 13); PROFW(3, 14); PROFW(0, 15);
  }
}

struct RecMaps { CUtensorMap w[3], wo, x[2]; };
__global__ void __cluster_dims__(R_CL, 1, 1) __launch_bounds__(512, 1)
rec_kernel(const __grid_constant__ RecMaps M, const bf16* __restrict__ Wo, const bf16* __restrict__ mem0, uint32_t zero) {
  using namespace rec;
  extern __shared__ __align__(1024) uint8_t smem[];
  const uint32_t sb = smem_u32(smem);
  const int tid = threadIdx.x, warp = __shfl_sync(0xffffffffu, tid >> 5, 0), wg = warp >> 2, lane = tid & 31;
  const int h = blockIdx.x / 3, rank = blockIdx.x % 3;
  if (warp == 0) {
    if (lane < 20) mbar_init(sb + BARS + 8 * lane, (lane >= 5 && lane < 10) || lane == 19 ? 2 : lane == 14 ? 9 : lane == 16 && rank < 2 ? 5 : 1);
    else if (lane < 23) mbar_init(sb + B_W1 + 8 * (lane - 20), 1);
    else if (lane == 23) mbar_init(sb + B_PART, 1);
    fence_mbar_init();
    __syncwarp();
    if (lane == 0) { mbar_expect_tx(sb + B_W1, (NSS + R1) * 4096); mbar_expect_tx(sb + B_QK, 10240); mbar_expect_tx(sb + B_V, 10240); mbar_expect_tx(sb + B_OM, rank < 2 ? 2048 : 4096); }
    __syncwarp();
    for (int i = lane; i < 128; i += 32) {
      const int j = i >> 1, t = i & 1, r = reg_idx(j);
      if (is_ss(j)) tma_load_2d(sb + WS + (t * NSS + ss_before(j)) * 2048, &M.w[rank], h * DH + t * 64, j * 16, sb + B_W1);
      else if (r < R1) tma_load_2d(sb + WO + (t * R1 + r) * 2048, &M.w[rank], h * DH + t * 64, j * 16, sb + B_W1);
      else tma_prefetch_2d(&M.w[rank], h * DH + t * 64, j * 16);
    }
    const int t = 3 * (lane >> 1) + (rank + 1) % 3;
    if (t < 16) tma_prefetch_2d(&M.wo, t * 64, h * DH + (lane & 1) * 64);
  } else if (warp == 1) {
    constexpr int N = (sizeof(Flags) - sizeof(g_fl.xn)) / 16;
    if (lane == 0 && blockIdx.x < N) ((uint4*)g_fl.dep)[blockIdx.x] = make_uint4(0, 0, 0, 0);
    static_assert(N <= 96, "flag reset");
    __threadfence();
    __syncwarp();
    asm volatile("griddepcontrol.launch_dependents;" ::: "memory");
  }
  __syncthreads();
  if (wg == 3) {
    reg_dec<24>();
    rec_load(sb, h, rank, warp & 3, M.x, &M.wo);
    cluster_arrive(); cluster_wait();
  } else if (wg == 2) {
    reg_dec<72>();
    if (rank < 2) rec_attn<true>(sb, h, rank, warp & 3, Wo, mem0);
    else rec_attn<false>(sb, h, rank, warp & 3, Wo, mem0);
  } else {
    reg_inc<208>();
    rec_proj(sb, h, rank, warp, &M.w[rank], &M.wo, zero);
    cluster_arrive(); cluster_wait();
  }
}

namespace gm {
#define G_ST 6
constexpr int STAGES = G_ST, STAGE_BYTES = 32768;
constexpr uint32_t SO = STAGES * STAGE_BYTES, B_FULL = SO + 32768, B_EMPTY = B_FULL + 64, B_JOB = B_FULL + 128, B_MSG = B_FULL + 144, B_TRIG = B_FULL + 56, JOB = B_FULL + 160, MSG = JOB + 8, SMEM = B_FULL + 192;
constexpr int T_O = 0, T_GU = 1, T_D = 2, T_END = 3, NEARLY = 32;
#define G_NO 8
#define G_NG 16
#define G_ND 8
__host__ __device__ constexpr bool is_split(int ty, int l, int cb) { return ty == T_O && l && cb >= 16 - NSPL; }
#define G_LOOK 8
struct Pipe { int s, ph; DEVI void next() { if (++s == STAGES) { s = 0; ph ^= 1; } } };
}
struct GemmMaps { CUtensorMap o, wo, x, x1, xm, wg, wu, h, hs, wd, x2, pt, out; };

DEVI float geglu(float g, float u) {
  const float z = g * (0.7978845608028654f + 0.035677408136300125f * g * g);
  float t; asm("tanh.approx.f32 %0, %1;" : "=f"(t) : "f"(z));
  const float hg = 0.5f * g;
  return fmaf(hg, t, hg) * u;
}
DEVI int h_ready(int v) { const int t = v ^ 0x0e0e0e0e; return t ? ((__ffs(t) - 1) >> 3) * 14 : 56; }
DEVI int h_wait(const int* p, int i, int& budget) {
  int n = 64;
  while ((n = h_ready(ld_acquire(p))) <= i && --budget > 0) __nanosleep(32);
  asm volatile("fence.proxy.async.global;" ::: "memory");
  return n;
}
#define LN_LD 0
DEVI uint4 ld_ln(const uint4* p) {
  uint4 v;
  if (LN_LD == 0) v = __ldcg(p);
  if (LN_LD == 1) asm volatile("ld.relaxed.gpu.global.v4.b32 {%0,%1,%2,%3}, [%4];" : "=r"(v.x), "=r"(v.y), "=r"(v.z), "=r"(v.w) : "l"(p));
  if (LN_LD == 2) asm volatile("ld.global.L1::no_allocate.v4.b32 {%0,%1,%2,%3}, [%4];" : "=r"(v.x), "=r"(v.y), "=r"(v.z), "=r"(v.w) : "l"(p));
  if (LN_LD == 3) asm volatile("ld.global.nc.L1::no_allocate.v4.b32 {%0,%1,%2,%3}, [%4];" : "=r"(v.x), "=r"(v.y), "=r"(v.z), "=r"(v.w) : "l"(p));
  return v;
}
template<int NP> DEVI void ln_row(const bf16* res, const bf16* pt, uint4* u, bf16* xn, int lane) {
  uint32_t* x = (uint32_t*)u;
  float sum = 0;
#pragma unroll
  for (int hf = 0; hf < 2; hf++) {
    uint4 p[2][NP + 1];
#pragma unroll
    for (int i = 0; i < 2; i++)
#pragma unroll
      for (int k = 0; k <= NP; k++) p[i][k] = ld_ln((const uint4*)(k ? pt + (k - 1) * (128 * DM) : res) + (hf * 2 + i) * 32 + lane);
#pragma unroll
    for (int i = 0; i < 8; i++) {
      uint32_t y = ((const uint32_t*)&p[i >> 2][0])[i & 3];
      if (NP) {
        float lo = 0, hi = 0;
#pragma unroll
        for (int k = 1; k <= NP; k++) { const uint32_t z = ((const uint32_t*)&p[i >> 2][k])[i & 3]; lo += bf_lo(z); hi += bf_hi(z); }
        y = pack_bf16(lo + bf_lo(y), hi + bf_hi(y));
      }
      x[hf * 8 + i] = y;
      sum += bf_lo(y) + bf_hi(y);
    }
  }
  float mean = sum * (1.f / 32), q = 0;
#pragma unroll
  for (int i = 0; i < 16; i++) { const float a = bf_lo(x[i]) - mean, b = bf_hi(x[i]) - mean; q = fmaf(a, a, fmaf(b, b, q)); }
#pragma unroll
  for (int o = 1; o < 32; o *= 2) {
    const float m2 = __shfl_xor_sync(0xffffffffu, mean, o), q2 = __shfl_xor_sync(0xffffffffu, q, o), dl = m2 - mean;
    q = fmaf(dl * dl, 16.f * o, q + q2);
    mean = 0.5f * (mean + m2);
  }
  const float rs = rsqrtf(q * (1.f / DM) + 1e-5f), mr = -mean * rs;
#pragma unroll
  for (int i = 0; i < 4; i++) {
    uint32_t y[4];
#pragma unroll
    for (int k = 0; k < 4; k++) y[k] = pack_bf16(fmaf(bf_lo(x[4*i+k]), rs, mr), fmaf(bf_hi(x[4*i+k]), rs, mr));
    stg128((uint4*)xn + i * 32 + lane, y[0], y[1], y[2], y[3]);
  }
}

__global__ void __cluster_dims__(2, 1, 1) __launch_bounds__(512, 1) gemm_kernel(const __grid_constant__ GemmMaps M, const bf16* __restrict__ x) {
  using namespace gm;
  extern __shared__ __align__(1024) uint8_t smem[];
  const uint32_t sb = smem_u32(smem);
  const int tid = threadIdx.x, wid = __shfl_sync(0xffffffffu, tid >> 5, 0), wg = wid >> 2, warp = wid & 3;
  int budget = SPIN_BUDGET;
  const int rank = blockIdx.x & 1;
  const uint32_t peer = mapa(sb, rank ^ 1);
  if (tid < 20) mbar_init(sb + B_FULL + 8 * tid, tid >> 3 == 1 ? 2 : 1);
  fence_mbar_init();
  if (wid == 1 && rank == 0) sts32v(sb + JOB + 16, bcast(e_ticket(g_fl.ticket)));
  cluster_arrive(); cluster_wait();
  int cta;
  asm volatile("ld.shared::cluster.u32 %0, [%1];" : "=r"(cta) : "r"(mapa(sb + JOB + 16, 0)) : "memory");
  cta = __shfl_sync(0xffffffffu, cta, 0) * 2 + rank;
  const int lane = lane_reg();
  if (wg >= 2) {
    reg_dec<64>();
    if (wid == 8) {
      Pipe p; p.s = 0; p.ph = 1;
      for (int n = 0; ; n++) {
        e_expect_tx(sb + B_MSG + 8 * (n & 1), 4);
        mbar_wait(sb + B_MSG + 8 * (n & 1), (n >> 1) & 1, budget);
        const int msg = __shfl_sync(0xffffffffu, lds32v(sb + MSG + 4 * (n & 1)), 0);
        const int ty = (msg >> 11) & 3, l = (msg >> 10) & 1, shb = ty == T_GU && l;
        const int cb = ((msg >> 6) & 15) + (shb ? rank : 0), j = (msg & 63) + (ty == T_END || shb ? 0 : rank);
        const int job = ty << 11 | l << 10 | cb << 6 | j, row = l * SEQ + cb * 128;
        mbar_wait(sb + B_EMPTY + 8 * p.s, p.ph, budget);
        trap_if_spent(budget);
        sts32v(sb + JOB + 4 * (n & 1), job | p.s << 16 | (p.ph ^ 1) << 20);
        e_arrive(sb + B_JOB + 8 * (n & 1));
        if (ty == T_END) break;
        const bool spl = is_split(ty, l, cb);
        const int nk = ty == T_D ? 56 : ty == T_GU || spl ? 16 : 64, k0 = spl ? (j >> 3) * 16 : 0, jt = j & 7;
        int rdy = msg >> 16;
        if (ty != T_GU && !spl) {
          const uint32_t fb = sb + B_FULL + 8 * p.s, a = sb + p.s * STAGE_BYTES;
          const CUtensorMap* const m = ty == T_D ? &M.x1 : l ? &M.x2 : &M.x;
          const int r = ty == T_D ? row : cb * 128;
          e_expect_tx(fb, STAGE_BYTES);
          e_tma_2d(a, m, jt * 128, r, fb); e_tma_2d(a + 16384, m, jt * 128 + 64, r, fb);
          p.next();
        }
        const CUtensorMap* const ma = ty == T_O ? &M.o : ty == T_GU ? &M.xm : &M.h;
        for (int i = k0; i < k0 + nk; i++) {
          if (i == k0 + nk - G_LOOK) e_arrive(sb + B_TRIG);
          const uint32_t fb = sb + B_FULL + 8 * p.s, a = sb + p.s * STAGE_BYTES, b = a + 16384;
          mbar_wait(sb + B_EMPTY + 8 * p.s, p.ph, budget);
          e_expect_tx(fb, STAGE_BYTES);
          if (ty == T_O) { e_tma_5d(b, &M.wo, jt * 128, i * 2, fb); e_tma_5d(b + 8192, &M.wo, jt * 128 + 64, i * 2, fb); }
          else if (shb) e_tma_2d_mc(b + rank * 8192, rank ? &M.wu : &M.wg, j * 64, i * 64, fb);
          else if (ty == T_GU) { e_tma_2d(b, &M.wg, j * 64, i * 64, fb); e_tma_2d(b + 8192, &M.wu, j * 64, i * 64, fb); }
          else {
            e_tma_2d(b, &M.wd, jt * 128, i * 64, fb); e_tma_2d(b + 8192, &M.wd, jt * 128 + 64, i * 64, fb);
            if (i >= rdy) rdy = h_wait(g_fl.dep + grp(T_D, l, cb), i, budget);
          }
          if (shb) { e_tma_2d(a, ma, i * 64, row, fb); e_tma_2d(a + 8192, ma, i * 64, row + 64, fb); }
          else e_tma_2d_mc(a + rank * 8192, ma, i * 64, row + rank * 64, fb);
          p.next();
        }
      }
    } else if (wid == 9 && rank == 0) {
      const int role = cta < G_NO ? T_O : cta < G_NO + G_NG ? T_GU : cta < G_NO + G_NG + G_ND ? T_D : T_END;
      int k1 = role == T_O ? cta : role == T_GU ? cta - G_NO : role == T_D ? cta - G_NO - G_NG : 1024;
      for (int n = 0, ty = 0; ty != T_END; n++) {
        mbar_wait(sb + B_TRIG, (n & 1) ^ 1, budget);
        int l = 0, cb = 0, j = 0;
        if (k1 < (role == T_GU ? 896 : 128)) {
          ty = role;
          cb = role == T_GU ? k1 / 56 : k1 >> 3; j = k1 - cb * (role == T_GU ? 56 : 8);
          k1 += role == T_O ? G_NO : role == T_GU ? G_NG : G_ND;
        } else while (true) {
          int d0 = ld_relaxed(g_fl.dep + lane), d1 = ld_relaxed(g_fl.dep + 32 + lane);
          const int t0 = ld_relaxed(g_fl.taken + lane), t1 = ld_relaxed(g_fl.taken + 32 + lane);
          const bool l0 = t0 < (lane >= 16 ? (lane & 1 ? 0 : 56) : is_split(T_O, 1, lane) ? 4 * KS : 4), l1 = lane < 16 && t1 < 4;
          const uint32_t rd = __ballot_sync(0xffffffffu, d0 >= 128);
          const uint32_t ok0 = __ballot_sync(0xffffffffu, l0) & rd & (rd >> 1 | 0xffff), ok1 = __ballot_sync(0xffffffffu, l1 && h_ready(d1) > 0);
          ty = T_END; l = 1;
          if (!__any_sync(0xffffffffu, l0 || l1)) break;
          uint32_t m = ok0 ? ok0 : ok1;
          if (!m) __nanosleep(100);
          while (m) {
            const int nth = ok0 ? 0 : (cta >> 1) % __popc(m);
            const int b = __ffs(__ballot_sync(0xffffffffu, __popc(m << (31 - lane)) > nth)) - 1, gn = b + (ok0 ? 0 : 32);
            const int t = bcast(e_ticket(g_fl.taken + gn));
            if (t < (gn >> 4 == T_GU ? 56 : is_split(gn >> 4, 1, gn & 15) ? 4 * KS : 4)) { ty = gn >> 4; cb = gn & 15; j = ty == T_GU ? t : 2 * t; break; }
            m &= ~(1u << b);
          }
          if (ty != T_END) break;
          trap_if_spent(--budget);
        }
        int rdy = 64;
        if (ty == T_D) rdy = h_wait(g_fl.dep + grp(T_D, l, cb), 0, budget);
        else if (ty != T_END) flag_wait(g_fl.dep + grp(ty, l, cb), 128, budget);
        if (ty == T_GU && l) flag_wait(g_fl.dep + grp(ty, l, cb + 1), 128, budget);
        const int msg = rdy << 16 | ty << 11 | l << 10 | cb << 6 | j;
        e_st_async32(peer + MSG + 4 * (n & 1), msg, peer + B_MSG + 8 * (n & 1));
        e_st_async32(sb + MSG + 4 * (n & 1), msg, sb + B_MSG + 8 * (n & 1));
      }
    } else if (cta < NEARLY && wg == 3) {
      const int r0 = warp * NEARLY + (NEARLY - 1 - cta);
      int nb = r0 < 128 && lane < 3 ? 0 : 16;
      while (__any_sync(0xffffffffu, nb < 16)) {
        int v = 0;
        if (nb < 16) asm volatile("ld.acquire.gpu.global.s32 %0, [%1];" : "=r"(v) : "l"(g_fl.part + lane * 16 + nb) : "memory");
        const uint32_t ok = __ballot_sync(0xffffffffu, v >= (is_split(lane, 1, nb) ? 8 * KS : 8));
        if (!ok) {
          if (--budget <= 0) break;
          __nanosleep(64);
          continue;
        }
        const int st = 31 - __clz(ok), cb = __shfl_sync(0xffffffffu, nb, st);
        nb += lane == st;
#pragma unroll 1
        for (int r = r0; r < 128; r += 4 * NEARLY) {
          const size_t o = (size_t)(cb * 128 + r) * DM;
          uint4 u[4];
          if (is_split(st, 1, cb)) {
            ln_row<KS>(g_x2 + o, g_pt + (size_t)((cb - 16 + NSPL) * KS * 128 + r) * DM, u, g_xm[1] + o, lane);
#pragma unroll
            for (int i = 0; i < 4; i++) stg128((uint4*)(g_x1[1] + o) + i * 32 + lane, u[i].x, u[i].y, u[i].z, u[i].w);
          } else ln_row<0>((st == 2 ? g_x2 : g_x1[st ^ 1]) + o, nullptr, u, (st == 2 ? g_xn[1] + LAG * 32 * DM : g_xm[st ^ 1]) + o, lane);
          __syncwarp();
          e_flag_add(st == 2 ? g_fl.xn[1][cb] : g_fl.dep + grp(T_GU, st ^ 1, cb));
        }
      }
      if (cta == 0 && wid == 12) {
        asm volatile("griddepcontrol.wait;" ::: "memory");
        g_fl.xn[lane >> 4][lane & 15][0] = 0;
      }
    }
    cluster_arrive(); cluster_wait();
  } else {
    reg_inc<192>();
    if (cta < NEARLY) {
#pragma unroll 1
      for (int r = 2 * (cta * 8 + wid); r < SEQ; r += 16 * NEARLY) {
        uint4 u[4];
        ln_row<0>(x + (size_t)r * DM, nullptr, u, g_xn[0] + (size_t)r * DM, lane);
        ln_row<0>(x + (size_t)(r + 1) * DM, nullptr, u, g_xn[0] + (size_t)(r + 1) * DM, lane);
        __syncwarp();
        e_flag_add(g_fl.xn[0][r >> 7], 2);
      }
    }
    const bool lead = warp == 0;
    const uint32_t eb = (warp == 1 ? peer : sb) + B_EMPTY;
    const int rl = warp < 2 ? 0 : -1;
    const uint32_t so = sb + SO + wg * 16384;
    const int r0 = warp * 16 + (lane & 7) + ((lane >> 3) & 1) * 8;
    const uint32_t sw = r0 * 128 + (((lane >> 4) ^ (r0 & 7)) << 4);
    for (int n = wg; ; n += 2) {
      float d0[64], d1[64];
      mbar_wait(sb + B_JOB + 8 * wg, (n >> 1) & 1, budget);
      fault_if_spent(budget);
      const int job = __shfl_sync(0xffffffffu, lds32v(sb + JOB + 4 * wg), 0);
      const int ty = (job >> 11) & 3, l = (job >> 10) & 1, cb = (job >> 6) & 15, j = job & 63;
      if (ty == T_END) {
        if (n > 0) nbar_sync_r(1 + wg, 256);
        if (lead && !(job & 1)) { sts32v(sb + JOB + 4 * (wg ^ 1), job | 1); e_arrive(sb + B_JOB + 8 * (wg ^ 1)); }
        if (!(job & 1)) nbar_arrive_r(1 + (wg ^ 1), 256);
        break;
      }
      Pipe q; q.s = (job >> 16) & 15; q.ph = job >> 20;
      const bool spl = is_split(ty, l, cb);
      if (ty != T_GU && !spl) {
        mbar_wait(sb + B_FULL + 8 * q.s, q.ph, budget);
#pragma unroll
        for (int m = 0; m < 2; m++)
#pragma unroll
          for (int c = 0; c < 8; c++) {
            float* d = (m ? d1 : d0) + 8 * c;
            uint32_t r[4];
            ldsm4(sb + q.s * STAGE_BYTES + (c >> 2) * 16384 + m * 8192 + (sw ^ ((c & 3) << 5)), r[0], r[1], r[2], r[3]);
#pragma unroll
            for (int i = 0; i < 4; i++) { d[2*i] = bf_lo(r[i]); d[2*i+1] = bf_hi(r[i]); }
          }
        fence_proxy_async();
        nbar_sync_r(3 + wg, 128);
        arrive_cl_if_eq(eb + 8 * q.s, lane, rl);
        q.next();
      } else {
#pragma unroll
        for (int i = 0; i < 64; i++) d0[i] = d1[i] = 0.f;
      }
      pin<64>(d0); pin<64>(d1);
      if (n > 0) nbar_sync_r(1 + wg, 256);
      const int nk = ty == T_D ? 56 : ty == T_GU || spl ? 16 : 64;
      int prev = 0;
      for (int i = 0; i < nk; i++) {
        mbar_wait(sb + B_FULL + 8 * q.s, q.ph, budget);
        const uint32_t da = desc_base(sb) + q.s * (STAGE_BYTES / 16);
        wg_fence();
        sfor<0, 4>([&](auto K) {
          constexpr int k = K;
          typedef Op<16384 + k * 2048, 8192, 1024, 1, 1> OB;
          wg_ss128<1, Op<k * 32, 16, 1024, 1, 0>, OB>(d0, da, da);
          wg_ss128<1, Op<8192 + k * 32, 16, 1024, 1, 0>, OB>(d1, da, da);
        });
        wg_commit();
        wg_wait<1>();
        arrive_cl_if_eq(eb + 8 * prev, lane, i ? rl : -1);
        prev = q.s;
        q.next();
      }
      nbar_arrive_r(1 + (wg ^ 1), 256);
      wg_wait<0>();
      pin<64>(d0); pin<64>(d1);
      arrive_cl_if_eq(eb + 8 * prev, lane, rl);
      if (ty == T_GU) {
#pragma unroll
        for (int m = 0; m < 2; m++)
#pragma unroll
          for (int c = 0; c < 4; c++) {
            const float* d = (m ? d1 : d0) + 8 * c;
            uint32_t r[4];
#pragma unroll
            for (int i = 0; i < 4; i++) r[i] = pack_bf16(geglu(d[2*i], d[32+2*i]), geglu(d[2*i+1], d[32+2*i+1]));
            stsm4(so + m * 8192 + (sw ^ (c << 5)), r[0], r[1], r[2], r[3]);
          }
        fence_proxy_async();
        nbar_sync_r(3 + wg, 128);
        if (lead) {
          e_tma_store_2d(&M.hs, so, j * 64, l * SEQ + cb * 128);
          bulk_commit(); bulk_wait<0>();
          e_flag_add(g_fl.dep + grp(T_D, l, cb), 1 << (j / 14 * 8));
        }
      } else {
        const CUtensorMap* const mo = spl ? &M.pt : ty == T_O ? &M.x1 : l ? &M.out : &M.x2;
        const int row = spl ? ((cb - 16 + NSPL) * KS + (j >> 3)) * 128 : (ty == T_O ? l * SEQ : 0) + cb * 128;
#pragma unroll
        for (int hf = 0; hf < 2; hf++) {
          if (hf) nbar_sync_r(3 + wg, 128);
#pragma unroll
          for (int m = 0; m < 2; m++)
#pragma unroll
            for (int c = 0; c < 4; c++) {
              const float* d = (m ? d1 : d0) + 32 * hf + 8 * c;
              stsm4(so + m * 8192 + (sw ^ (c << 5)), pack_bf16(d[0], d[1]), pack_bf16(d[2], d[3]), pack_bf16(d[4], d[5]), pack_bf16(d[6], d[7]));
            }
          fence_proxy_async();
          nbar_sync_r(3 + wg, 128);
          if (lead) {
            e_tma_store_2d(mo, so, (j & 7) * 128 + hf * 64, row);
            bulk_commit();
            if (hf == 0) bulk_wait_read<0>();
            else {
              bulk_wait<0>();
              if (ty == T_O || !l) e_flag_add(g_fl.part + (ty == T_O ? l ^ 1 : 2) * 16 + cb);
            }
          }
        }
      }
    }
    cluster_arrive(); cluster_wait();
  }
}

typedef CUresult (*PFN_encodeTiled)(CUtensorMap*, CUtensorMapDataType, cuuint32_t, void*, const cuuint64_t*, const cuuint64_t*,
                                    const cuuint32_t*, const cuuint32_t*, CUtensorMapInterleave, CUtensorMapSwizzle,
                                    CUtensorMapL2promotion, CUtensorMapFloatOOBfill);
static PFN_encodeTiled g_encode = nullptr;
static int g_sms = 0;
static CUtensorMap encode(const void* ptr, int rank, const cuuint64_t* dims, const cuuint64_t* strides, const cuuint32_t* box) {
  CUtensorMap m;
  const cuuint32_t es[5] = {1, 1, 1, 1, 1};
  g_encode(&m, CU_TENSOR_MAP_DATA_TYPE_BFLOAT16, rank, (void*)ptr, dims, strides, box, es, CU_TENSOR_MAP_INTERLEAVE_NONE,
           CU_TENSOR_MAP_SWIZZLE_128B, CU_TENSOR_MAP_L2_PROMOTION_L2_256B, CU_TENSOR_MAP_FLOAT_OOB_FILL_NONE);
  return m;
}
static CUtensorMap make_map(const void* ptr, uint64_t rows, uint64_t cols, uint32_t box_rows) {
  const cuuint64_t dims[2] = {cols, rows}, strides[1] = {cols * 2};
  const cuuint32_t box[2] = {64, box_rows};
  return encode(ptr, 2, dims, strides, box);
}
static CUtensorMap make_map_x(const void* ptr) {
  const cuuint64_t dims[3] = {DM, NSTEP * 32, 2}, strides[2] = {DM * 2, (cuuint64_t)NSTEP * 32 * DM * 2};
  const cuuint32_t box[3] = {64, 32, 2};
  return encode(ptr, 3, dims, strides, box);
}
static CUtensorMap make_map_x1(const void* ptr) {
  const cuuint64_t dims[3] = {64, 2 * NSTEP * 32, DM / 64}, strides[2] = {DM * 2, 128};
  const cuuint32_t box[3] = {64, 32, 2};
  return encode(ptr, 3, dims, strides, box);
}
static CUtensorMap make_map_wo(const void* ptr) {
  const cuuint64_t dims[5] = {DM, 2, 4, 4, NH * DH / 32}, strides[4] = {DM * 2, 8 * DM * 2, 2 * DM * 2, 32 * DM * 2};
  const cuuint32_t box[5] = {64, 2, 4, 4, 2};
  return encode(ptr, 5, dims, strides, box);
}

extern "C" void kernel_launch(void* const* d_in, const int* in_sizes, int n_in, void* d_out, int out_size) {
  const bf16 *x = (const bf16*)d_in[0], *mem0 = (const bf16*)d_in[1], *Wo = (const bf16*)d_in[5];
  if (!g_encode) {
    void* p = nullptr; cudaDriverEntryPointQueryResult q;
    cudaGetDriverEntryPoint("cuTensorMapEncodeTiled", &p, cudaEnableDefault, &q);
    g_encode = (PFN_encodeTiled)p;
    int dev = 0;
    cudaGetDevice(&dev);
    cudaDeviceGetAttribute(&g_sms, cudaDevAttrMultiProcessorCount, dev);
    cudaFuncSetAttribute(rec_kernel, cudaFuncAttributeMaxDynamicSharedMemorySize, rec::SMEM);
    cudaFuncSetAttribute(gemm_kernel, cudaFuncAttributeMaxDynamicSharedMemorySize, gm::SMEM);
  }
  void *xn, *o, *x1, *xm, *x2, *pt, *hh;
  cudaGetSymbolAddress(&xn, g_xn); cudaGetSymbolAddress(&o, g_o); cudaGetSymbolAddress(&x1, g_x1);
  cudaGetSymbolAddress(&xm, g_xm); cudaGetSymbolAddress(&pt, g_pt); cudaGetSymbolAddress(&x2, g_x2); cudaGetSymbolAddress(&hh, g_h);
  RecMaps R;
  for (int i = 0; i < 3; i++) R.w[i] = make_map(d_in[2 + i], DM, NH * DH, 16);
  R.wo = make_map(Wo, NH * DH, DM, 64); R.x[0] = make_map_x(xn); R.x[1] = make_map_x1(xn);
  rec_kernel<<<96, 512, rec::SMEM>>>(R, Wo, mem0, 0);
  GemmMaps G;
  G.o = make_map(o, 2 * SEQ, NH * DH, 64); G.wo = make_map_wo(Wo);
  G.x1 = make_map(x1, 2 * SEQ, DM, 128); G.xm = make_map(xm, 2 * SEQ, DM, 64);
  G.wg = make_map(d_in[8], DM, DF, 64); G.wu = make_map(d_in[9], DM, DF, 64); G.wd = make_map(d_in[10], DF, DM, 64);
  G.h = make_map(hh, 2 * SEQ, DF, 64); G.hs = make_map(hh, 2 * SEQ, DF, 128); G.pt = make_map(pt, NSPL * KS * 128, DM, 128);
  G.x = make_map(x, SEQ, DM, 128); G.x2 = make_map(x2, SEQ, DM, 128); G.out = make_map(d_out, SEQ, DM, 128);
  cudaLaunchConfig_t cfg = {};
  cfg.gridDim = dim3(g_sms & ~1); cfg.blockDim = dim3(512); cfg.dynamicSmemBytes = gm::SMEM; cfg.stream = cudaStreamPerThread;
  cudaLaunchAttribute at;
  at.id = cudaLaunchAttributeProgrammaticStreamSerialization; at.val.programmaticStreamSerializationAllowed = 1;
  cfg.attrs = &at; cfg.numAttrs = 1;
  cudaLaunchKernelEx(&cfg, gemm_kernel, G, x);
}
```

```cpp
#include <cuda_runtime.h>
#include <cuda_bf16.h>
#include <cuda.h>
#include <stdint.h>

#define DEVI __device__ __forceinline__
typedef __nv_bfloat16 bf16;

#define LAG 16
constexpr int SEQ = 2048, DM = 1024, NH = 32, DH = 128, DF = 3584, NSEG = 64, NSTEP = NSEG + LAG;
static_assert(NSTEP % 2 == 0, "tags and slots of the exchange buffers return to their initial state");

__device__ __align__(1024) bf16 g_xn[2][NSTEP * 32 * DM];
__device__ __align__(1024) bf16 g_o[2][SEQ * NH * DH];
__device__ __align__(1024) bf16 g_x1[2][SEQ * DM];
__device__ __align__(1024) bf16 g_xm[2][SEQ * DM];
__device__ __align__(1024) bf16 g_x2[SEQ * DM];
__device__ __align__(1024) bf16 g_h[2][SEQ * DF];
__device__ __align__(1024) uint4 g_part[256 * 32 * 8];
__device__ __align__(1024) uint32_t g_ann[2][32][64];
__device__ __align__(1024) uint4 g_mem[2][2048];
__host__ __device__ constexpr int grp(int type, int layer, int blk) { return (layer ? 0 : 48) + 16 * type + blk; }
struct Flags {
  int xn[2][16][32];
  int dep[96];
  int taken[64];
  int part[64];
  int ticket[32];
};
__device__ __align__(128) Flags g_fl;

DEVI uint32_t smem_u32(const void* p) { return (uint32_t)__cvta_generic_to_shared(p); }
DEVI void mbar_init(uint32_t bar, uint32_t cnt) { asm volatile("mbarrier.init.shared::cta.b64 [%0], %1;" :: "r"(bar), "r"(cnt) : "memory"); }
DEVI void mbar_expect_tx(uint32_t bar, uint32_t bytes) { asm volatile("mbarrier.arrive.expect_tx.shared::cta.b64 _, [%0], %1;" :: "r"(bar), "r"(bytes) : "memory"); }
DEVI void mbar_arrive(uint32_t bar) { asm volatile("mbarrier.arrive.shared::cta.b64 _, [%0];" :: "r"(bar) : "memory"); }
DEVI bool mbar_try(uint32_t bar, uint32_t parity) {
  uint32_t p;
  asm volatile("{.reg .pred p; mbarrier.try_wait.parity.shared::cta.b64 p, [%1], %2; selp.u32 %0, 1, 0, p;}" : "=r"(p) : "r"(bar), "r"(parity) : "memory");
  return p;
}
DEVI bool mbar_test(uint32_t bar, uint32_t parity) {
  uint32_t p;
  asm volatile("{.reg .pred p; mbarrier.test_wait.parity.shared::cta.b64 p, [%1], %2; selp.u32 %0, 1, 0, p;}" : "=r"(p) : "r"(bar), "r"(parity) : "memory");
  return p;
}
constexpr int SPIN_BUDGET = 1 << 20;
DEVI void mbar_wait(uint32_t bar, uint32_t parity, int& budget) {
  while (!mbar_try(bar, parity)) { if (--budget < 0) break; }
}
DEVI void trap_if_spent(int budget) { asm volatile("{.reg .pred p; setp.le.s32 p, %0, 0; @p trap;}" :: "r"(budget) : "memory"); }
DEVI void fault_if_spent(int budget) { asm volatile("{.reg .pred p; setp.le.s32 p, %0, 0; @p st.global.u32 [%1], 0;}" :: "r"(budget), "l"(0ull) : "memory"); }
DEVI uint32_t mapa(uint32_t addr, uint32_t rank) { uint32_t r; asm("mapa.shared::cluster.u32 %0, %1, %2;" : "=r"(r) : "r"(addr), "r"(rank)); return r; }
DEVI void cluster_arrive() { asm volatile("barrier.cluster.arrive.release.aligned;" ::: "memory"); }
DEVI void cluster_wait() { asm volatile("barrier.cluster.wait.acquire.aligned;" ::: "memory"); }
DEVI void fence_mbar_init() { asm volatile("fence.mbarrier_init.release.cluster;" ::: "memory"); }
DEVI void fence_proxy_async() { asm volatile("fence.proxy.async.shared::cta;" ::: "memory"); }
DEVI void tma_load_2d(uint32_t dst, const CUtensorMap* m, int c0, int c1, uint32_t bar) {
  asm volatile("cp.async.bulk.tensor.2d.shared::cluster.global.mbarrier::complete_tx::bytes [%0], [%1, {%3, %4}], [%2];"
    :: "r"(dst), "l"(m), "r"(bar), "r"(c0), "r"(c1) : "memory");
}
DEVI void tma_load_5d(uint32_t dst, const CUtensorMap* m, int c0, int c4, uint32_t bar) {
  asm volatile("cp.async.bulk.tensor.5d.shared::cluster.global.mbarrier::complete_tx::bytes [%0], [%1, {%3, %5, %5, %5, %4}], [%2];"
    :: "r"(dst), "l"(m), "r"(bar), "r"(c0), "r"(c4), "r"(0) : "memory");
}
DEVI void tma_prefetch_2d(const CUtensorMap* m, int c0, int c1) {
  asm volatile("cp.async.bulk.prefetch.tensor.2d.L2.global [%0, {%1, %2}];" :: "l"(m), "r"(c0), "r"(c1) : "memory");
}
DEVI void tma_prefetch_5d(const CUtensorMap* m, int c0, int c4) {
  asm volatile("cp.async.bulk.prefetch.tensor.5d.L2.global [%0, {%1, %3, %3, %3, %2}];" :: "l"(m), "r"(c0), "r"(c4), "r"(0) : "memory");
}
#define ELECT "{.reg .pred p; elect.sync _|p, 0xffffffff;\n @p "
DEVI void e_expect_tx(uint32_t bar, uint32_t bytes) { asm volatile(ELECT "mbarrier.arrive.expect_tx.shared::cta.b64 _, [%0], %1;}" :: "r"(bar), "r"(bytes) : "memory"); }
DEVI void e_arrive(uint32_t bar) { asm volatile(ELECT "mbarrier.arrive.shared::cta.b64 _, [%0];}" :: "r"(bar) : "memory"); }
DEVI void e_arrive_cl(uint32_t bar) { asm volatile(ELECT "mbarrier.arrive.shared::cluster.b64 _, [%0];}" :: "r"(bar) : "memory"); }
DEVI void e_tma_2d(uint32_t dst, const CUtensorMap* m, int c0, int c1, uint32_t bar) {
  asm volatile(ELECT "cp.async.bulk.tensor.2d.shared::cluster.global.mbarrier::complete_tx::bytes [%0], [%1, {%3, %4}], [%2];}"
    :: "r"(dst), "l"(m), "r"(bar), "r"(c0), "r"(c1) : "memory");
}
DEVI void e_tma_2d_mc(uint32_t dst, const CUtensorMap* m, int c0, int c1, uint32_t bar) {
  asm volatile(ELECT "cp.async.bulk.tensor.2d.shared::cluster.global.mbarrier::complete_tx::bytes.multicast::cluster [%0], [%1, {%3, %4}], [%2], %5;}"
    :: "r"(dst), "l"(m), "r"(bar), "r"(c0), "r"(c1), "h"((unsigned short)3) : "memory");
}
DEVI void e_st_async32(uint32_t a, uint32_t x, uint32_t bar) {
  asm volatile(ELECT "st.async.weak.shared::cluster.mbarrier::complete_tx::bytes.b32 [%0], %1, [%2];}" :: "r"(a), "r"(x), "r"(bar) : "memory");
}
DEVI void e_tma_store_2d(const CUtensorMap* m, uint32_t src, int c0, int c1) {
  asm volatile(ELECT "cp.async.bulk.tensor.2d.global.shared::cta.bulk_group [%0, {%2, %3}], [%1];}" :: "l"(m), "r"(src), "r"(c0), "r"(c1) : "memory");
}
DEVI void e_flag_add(int* p, int v = 1) {
  asm volatile("{.reg .pred p; elect.sync _|p, 0xffffffff;\n fence.proxy.async.global; @p red.release.gpu.global.add.s32 [%0], %1;}" :: "l"(p), "r"(v) : "memory");
}
DEVI int e_ticket(int* p) { int v = 0; asm volatile(ELECT "atom.relaxed.gpu.global.add.s32 %0, [%1], 1;}" : "+r"(v) : "l"(p) : "memory"); __syncwarp(); return v; }
DEVI int bcast(int v) { return __reduce_max_sync(0xffffffffu, v); }
DEVI int ld_relaxed(const int* p) { int v; asm volatile("ld.relaxed.gpu.global.s32 %0, [%1];" : "=r"(v) : "l"(p) : "memory"); return v; }
DEVI int ld_acquire(const int* p) { int v; asm volatile("ld.acquire.gpu.global.s32 %0, [%1];" : "=r"(v) : "l"(p) : "memory"); return __shfl_sync(0xffffffffu, v, 0); }
DEVI void e_tma_3d(uint32_t dst, const CUtensorMap* m, int c0, int c1, int c2, uint32_t bar) {
  asm volatile(ELECT "cp.async.bulk.tensor.3d.shared::cluster.global.mbarrier::complete_tx::bytes [%0], [%1, {%3, %4, %5}], [%2];}"
    :: "r"(dst), "l"(m), "r"(bar), "r"(c0), "r"(c1), "r"(c2) : "memory");
}
DEVI void e_tma_5d(uint32_t dst, const CUtensorMap* m, int c0, int c4, uint32_t bar) {
  asm volatile(ELECT "cp.async.bulk.tensor.5d.shared::cluster.global.mbarrier::complete_tx::bytes [%0], [%1, {%3, %5, %5, %5, %4}], [%2];}"
    :: "r"(dst), "l"(m), "r"(bar), "r"(c0), "r"(c4), "r"(0) : "memory");
}
DEVI void e_bulk_g2s(uint32_t dst, const void* src, uint32_t bytes, uint32_t bar) {
  asm volatile(ELECT "cp.async.bulk.shared::cluster.global.mbarrier::complete_tx::bytes [%0], [%1], %2, [%3];}" :: "r"(dst), "l"(src), "r"(bytes), "r"(bar) : "memory");
}
DEVI void e_prefetch(const void* src, uint32_t bytes) {
  asm volatile(ELECT "cp.async.bulk.prefetch.L2.global [%0], %1;}" :: "l"(src), "r"(bytes) : "memory");
}
DEVI void bulk_commit() { asm volatile("cp.async.bulk.commit_group;" ::: "memory"); }
template<int N> DEVI void bulk_wait_read() { asm volatile("cp.async.bulk.wait_group.read %0;" :: "n"(N) : "memory"); }
template<int N> DEVI void bulk_wait() { asm volatile("cp.async.bulk.wait_group %0;" :: "n"(N) : "memory"); }
template<int ID, int N> DEVI void nbar_sync() { asm volatile("bar.sync %0, %1;" :: "n"(ID), "n"(N) : "memory"); }
template<int ID, int N> DEVI void nbar_arrive() { asm volatile("bar.arrive %0, %1;" :: "n"(ID), "n"(N) : "memory"); }
DEVI void nbar_sync_r(int id, int n) { asm volatile("bar.sync %0, %1;" :: "r"(id), "r"(n) : "memory"); }
DEVI void nbar_arrive_r(int id, int n) { asm volatile("bar.arrive %0, %1;" :: "r"(id), "r"(n) : "memory"); }
template<int R> DEVI void reg_inc() { asm volatile("setmaxnreg.inc.sync.aligned.u32 %0;" :: "n"(R)); }
template<int R> DEVI void reg_dec() { asm volatile("setmaxnreg.dec.sync.aligned.u32 %0;" :: "n"(R)); }
DEVI void wg_fence() { asm volatile("wgmma.fence.sync.aligned;" ::: "memory"); }
DEVI void wg_commit() { asm volatile("wgmma.commit_group.sync.aligned;" ::: "memory"); }
template<int N> DEVI void wg_wait() { asm volatile("wgmma.wait_group.sync.aligned %0;" :: "n"(N) : "memory"); }
DEVI uint32_t pack_bf16(float lo, float hi) { uint32_t r; asm("cvt.rn.bf16x2.f32 %0, %1, %2;" : "=r"(r) : "f"(hi), "f"(lo)); return r; }
DEVI float bf_lo(uint32_t v) { return __uint_as_float(v << 16); }
DEVI float bf_hi(uint32_t v) { return __uint_as_float(v & 0xffff0000u); }
DEVI uint32_t movmat(uint32_t a) { uint32_t r; asm volatile("movmatrix.sync.aligned.m8n8.trans.b16 %0, %1;" : "=r"(r) : "r"(a)); return r; }
DEVI void ldsm4(uint32_t addr, uint32_t& r0, uint32_t& r1, uint32_t& r2, uint32_t& r3) {
  asm volatile("ldmatrix.sync.aligned.m8n8.x4.shared.b16 {%0,%1,%2,%3}, [%4];" : "=r"(r0), "=r"(r1), "=r"(r2), "=r"(r3) : "r"(addr) : "memory");
}
DEVI void ldsm4t(uint32_t addr, uint32_t& r0, uint32_t& r1, uint32_t& r2, uint32_t& r3) {
  asm volatile("ldmatrix.sync.aligned.m8n8.x4.trans.shared.b16 {%0,%1,%2,%3}, [%4];" : "=r"(r0), "=r"(r1), "=r"(r2), "=r"(r3) : "r"(addr) : "memory");
}
DEVI void stsm4(uint32_t addr, uint32_t r0, uint32_t r1, uint32_t r2, uint32_t r3) {
  asm volatile("stmatrix.sync.aligned.m8n8.x4.shared.b16 [%0], {%1,%2,%3,%4};" :: "r"(addr), "r"(r0), "r"(r1), "r"(r2), "r"(r3) : "memory");
}
DEVI uint4 lds128(uint32_t a) { uint4 v; asm volatile("ld.shared.v4.u32 {%0,%1,%2,%3}, [%4];" : "=r"(v.x), "=r"(v.y), "=r"(v.z), "=r"(v.w) : "r"(a) : "memory"); return v; }
DEVI uint32_t lds32v(uint32_t a) { uint32_t v; asm volatile("ld.volatile.shared.u32 %0, [%1];" : "=r"(v) : "r"(a) : "memory"); return v; }
DEVI void sts32v(uint32_t a, uint32_t v) { asm volatile("st.volatile.shared.u32 [%0], %1;" :: "r"(a), "r"(v) : "memory"); }
DEVI void st_async128(uint32_t a, uint32_t x, uint32_t y, uint32_t z, uint32_t w, uint32_t bar) {
  asm volatile("st.async.weak.shared::cluster.mbarrier::complete_tx::bytes.v4.b32 [%0], {%1,%2,%3,%4}, [%5];" :: "r"(a), "r"(x), "r"(y), "r"(z), "r"(w), "r"(bar) : "memory");
}
DEVI void st_async32(uint32_t a, uint32_t x, uint32_t bar) {
  asm volatile("st.async.weak.shared::cluster.mbarrier::complete_tx::bytes.b32 [%0], %1, [%2];" :: "r"(a), "r"(x), "r"(bar) : "memory");
}
DEVI void st_cl128(bool own, uint32_t a, uint32_t x, uint32_t y, uint32_t z, uint32_t w, uint32_t bar) {
  asm volatile("{.reg .pred p; setp.ne.u32 p, %6, 0; @p st.shared.v4.b32 [%0], {%1,%2,%3,%4};\n"
               "@!p st.async.weak.shared::cluster.mbarrier::complete_tx::bytes.v4.b32 [%0], {%1,%2,%3,%4}, [%5];}"
               :: "r"(a), "r"(x), "r"(y), "r"(z), "r"(w), "r"(bar), "r"((uint32_t)own) : "memory");
}
DEVI void st_cl32(bool own, uint32_t a, uint32_t x, uint32_t bar) {
  asm volatile("{.reg .pred p; setp.ne.u32 p, %3, 0; @p st.shared.b32 [%0], %1;\n"
               "@!p st.async.weak.shared::cluster.mbarrier::complete_tx::bytes.b32 [%0], %1, [%2];}" :: "r"(a), "r"(x), "r"(bar), "r"((uint32_t)own) : "memory");
}
DEVI uint4 ldg_rlx128(const void* p) {
  uint4 v;
  asm volatile("ld.relaxed.gpu.global.v4.b32 {%0,%1,%2,%3}, [%4];" : "=r"(v.x), "=r"(v.y), "=r"(v.z), "=r"(v.w) : "l"(p) : "memory");
  return v;
}
DEVI void stg_rlx128(void* p, uint32_t x, uint32_t y, uint32_t z, uint32_t w) {
  asm volatile("st.relaxed.gpu.global.v4.b32 [%0], {%1,%2,%3,%4};" :: "l"(p), "r"(x), "r"(y), "r"(z), "r"(w) : "memory");
}
DEVI void stg128(void* p, uint32_t x, uint32_t y, uint32_t z, uint32_t w) {
  asm volatile("st.global.v4.b32 [%0], {%1,%2,%3,%4};" :: "l"(p), "r"(x), "r"(y), "r"(z), "r"(w) : "memory");
}
DEVI void stg_rlx32(void* p, uint32_t x) { asm volatile("st.relaxed.gpu.global.b32 [%0], %1;" :: "l"(p), "r"(x) : "memory"); }
DEVI uint32_t clock32() { uint32_t c; asm volatile("mov.u32 %0, %%clock;" : "=r"(c) :: "memory"); return c; }
DEVI uint32_t gtime() { uint32_t c; asm volatile("mov.u32 %0, %%globaltimer_lo;" : "=r"(c) :: "memory"); return c; }
DEVI void wait_time(uint32_t t, int& budget) { while ((int)(gtime() - t) < 0 && --budget > 0) {} }
DEVI uint2 ldg_rlx64(const void* p) { uint2 v; asm volatile("ld.relaxed.gpu.global.v2.b32 {%0,%1}, [%2];" : "=r"(v.x), "=r"(v.y) : "l"(p) : "memory"); return v; }
DEVI void sts16(uint32_t a, uint32_t x) { asm volatile("st.shared.b16 [%0], %1;" :: "r"(a), "h"((unsigned short)x) : "memory"); }
DEVI void sts128(uint32_t a, uint32_t x) { asm volatile("st.shared.v4.b32 [%0], {%1,%1,%1,%1};" :: "r"(a), "r"(x) : "memory"); }
DEVI void arrive_if_eq(uint32_t bar, int a, int b) { asm volatile("{.reg .pred p; setp.eq.s32 p, %1, %2; @p mbarrier.arrive.shared::cta.b64 _, [%0];}" :: "r"(bar), "r"(a), "r"(b) : "memory"); }
DEVI void arrive_cl_if_eq(uint32_t bar, int a, int b) { asm volatile("{.reg .pred p; setp.eq.s32 p, %1, %2; @p mbarrier.arrive.shared::cluster.b64 _, [%0];}" :: "r"(bar), "r"(a), "r"(b) : "memory"); }
template<int ID, int N> DEVI bool nbar_or(bool x) {
  uint32_t r;
  asm volatile("{.reg .pred p, q; setp.ne.u32 p, %1, 0; bar.red.or.pred q, %2, %3, p; selp.u32 %0, 1, 0, q;}" : "=r"(r) : "r"((uint32_t)x), "n"(ID), "n"(N) : "memory");
  return __any_sync(0xffffffffu, r);
}
DEVI void spin_until(uint32_t t0, int d) { while ((int)(clock32() - t0) < d) {} }
DEVI void flag_wait(const int* p, int n, int& budget) {
  while (ld_acquire(p) < n && --budget > 0) __nanosleep(32);
  asm volatile("fence.proxy.async.global;" ::: "memory");
}

#define F4(C, o)  C(d[o+0]), C(d[o+1]), C(d[o+2]), C(d[o+3])
#define F8(C, o)  F4(C, o), F4(C, o+4)
#define F32(C, o) F8(C, o), F8(C, o+8), F8(C, o+16), F8(C, o+24)
#define R4  "{%0,%1,%2,%3}"
#define R8  "{%0,%1,%2,%3,%4,%5,%6,%7}"
#define R16 "{%0,%1,%2,%3,%4,%5,%6,%7,%8,%9,%10,%11,%12,%13,%14,%15}"
#define R20 "{%0,%1,%2,%3,%4,%5,%6,%7,%8,%9,%10,%11,%12,%13,%14,%15,%16,%17,%18,%19}"
#define R32 "{%0,%1,%2,%3,%4,%5,%6,%7,%8,%9,%10,%11,%12,%13,%14,%15,%16,%17,%18,%19,%20,%21,%22,%23,%24,%25,%26,%27,%28,%29,%30,%31}"
#define R64 "{%0,%1,%2,%3,%4,%5,%6,%7,%8,%9,%10,%11,%12,%13,%14,%15,%16,%17,%18,%19,%20,%21,%22,%23,%24,%25,%26,%27,%28,%29,%30,%31," \
  "%32,%33,%34,%35,%36,%37,%38,%39,%40,%41,%42,%43,%44,%45,%46,%47,%48,%49,%50,%51,%52,%53,%54,%55,%56,%57,%58,%59,%60,%61,%62,%63}"
template<uint32_t OFF, uint32_t LBO, uint32_t SBO, uint32_t SW, int T> struct Op {
  static constexpr uint32_t lo = (OFF >> 4) | ((LBO >> 4) << 16), hi = (SBO >> 4) | (SW << 30);
  static constexpr int t = T;
};
DEVI uint32_t desc_base(uint32_t addr) { return (addr & 0x3FFFF) >> 4; }
#define RS_ASM(SHAPE, REGS, A0, A1, A2, A3, B, LO, HI, T, SD) \
  "{.reg .b64 tb; .reg .b32 lb; add.u32 lb, " B ", " LO "; mov.b64 tb, {lb, " HI "};\n" \
  "wgmma.mma_async.sync.aligned." SHAPE ".f32.bf16.bf16 " REGS ", {" A0 "," A1 "," A2 "," A3 "}, tb, " SD ", 1, 1, " T ";}"
#define WG_RS(NAME, SHAPE, REGS, LIST, ...) \
  template<int ACC, class OB> DEVI void NAME(float* d, const uint32_t* a, uint32_t b) { \
    if (ACC) asm volatile(RS_ASM(SHAPE, REGS, __VA_ARGS__) \
      : LIST("+f") : "r"(a[0]), "r"(a[1]), "r"(a[2]), "r"(a[3]), "r"(b), "n"(OB::lo), "n"(OB::hi), "n"(OB::t), "n"(ACC & 1)); \
    else asm volatile(RS_ASM(SHAPE, REGS, __VA_ARGS__) \
      : LIST("=f") : "r"(a[0]), "r"(a[1]), "r"(a[2]), "r"(a[3]), "r"(b), "n"(OB::lo), "n"(OB::hi), "n"(OB::t), "n"(0)); \
  }
#define SS_ASM(SHAPE, REGS, A, B, LA, HA, TA, LB, HB, TB, SD) \
  "{.reg .b64 ta, tb; .reg .b32 la, lb; add.u32 la, " A ", " LA "; mov.b64 ta, {la, " HA "}; add.u32 lb, " B ", " LB "; mov.b64 tb, {lb, " HB "};\n" \
  "wgmma.mma_async.sync.aligned." SHAPE ".f32.bf16.bf16 " REGS ", ta, tb, " SD ", 1, 1, " TA ", " TB ";}"
#define WG_SS(NAME, SHAPE, REGS, LIST, ...) \
  template<int ACC, class OA, class OB> DEVI void NAME(float* d, uint32_t a, uint32_t b) { \
    if (ACC) asm volatile(SS_ASM(SHAPE, REGS, __VA_ARGS__) \
      : LIST("+f") : "r"(a), "r"(b), "n"(OA::lo), "n"(OA::hi), "n"(OA::t), "n"(OB::lo), "n"(OB::hi), "n"(OB::t), "n"(ACC & 1)); \
    else asm volatile(SS_ASM(SHAPE, REGS, __VA_ARGS__) \
      : LIST("=f") : "r"(a), "r"(b), "n"(OA::lo), "n"(OA::hi), "n"(OA::t), "n"(OB::lo), "n"(OB::hi), "n"(OB::t), "n"(0)); \
  }
#define L4(C)  F4(C, 0)
#define L8(C)  F8(C, 0)
#define L16(C) F8(C, 0), F8(C, 8)
#define L20(C) F8(C, 0), F8(C, 8), F4(C, 16)
#define L32(C) F32(C, 0)
WG_RS(wg_rs8, "m64n8k16", R4, L4, "%4", "%5", "%6", "%7", "%8", "%9", "%10", "%11", "%12")
WG_RS(wg_rs16, "m64n16k16", R8, L8, "%8", "%9", "%10", "%11", "%12", "%13", "%14", "%15", "%16")
WG_RS(wg_rs32, "m64n32k16", R16, L16, "%16", "%17", "%18", "%19", "%20", "%21", "%22", "%23", "%24")
WG_SS(wg_ss32, "m64n32k16", R16, L16, "%16", "%17", "%18", "%19", "%20", "%21", "%22", "%23", "%24")
WG_RS(wg_rs64, "m64n64k16", R32, L32, "%32", "%33", "%34", "%35", "%36", "%37", "%38", "%39", "%40")
WG_SS(wg_ss8, "m64n8k16", R4, L4, "%4", "%5", "%6", "%7", "%8", "%9", "%10", "%11", "%12")
WG_SS(wg_ss16, "m64n16k16", R8, L8, "%8", "%9", "%10", "%11", "%12", "%13", "%14", "%15", "%16")
WG_SS(wg_ss40, "m64n40k16", R20, L20, "%20", "%21", "%22", "%23", "%24", "%25", "%26", "%27", "%28")
WG_SS(wg_ss64, "m64n64k16", R32, L32, "%32", "%33", "%34", "%35", "%36", "%37", "%38", "%39", "%40")
#define L64(C) F32(C, 0), F32(C, 32)
WG_SS(wg_ss128, "m64n128k16", R64, L64, "%64", "%65", "%66", "%67", "%68", "%69", "%70", "%71", "%72")
template<int I> struct IC { __host__ __device__ constexpr operator int() const { return I; } };
template<int I, int N, class F> DEVI void sfor(F&& f) {
  if constexpr (I < N) { f(IC<I>{}); sfor<I + 1, N>(f); }
}

#define R_CL 6
namespace rec {
constexpr int NHI = 36, NLO = 5, NRS = NHI + NLO, NSS = 64 - NRS;
constexpr uint32_t WS = 0;
constexpr uint32_t WO = 2 * NSS * 2048;
constexpr uint32_t RING = WO + 65536;
constexpr uint32_t QB = RING + 40960, RG = 2080, POSQ = 0x64210, POSK = 0xB9753, POSV = 0xEDCA8;
#define JA 2
constexpr uint32_t WA = QB;
constexpr uint32_t OM = QB + 9 * RG, OMS = 2 * RG;
constexpr uint32_t OM2 = QB + 16384, OM2S = 2048;
constexpr uint32_t WH = QB + 20480;
constexpr uint32_t B_PART = QB + 15 * RG - 32;
constexpr uint32_t PM0 = QB + 16384, PM1 = QB + 15 * RG, PM2 = PM1 + 256;
constexpr uint32_t BARS = PM2 + 128;
constexpr uint32_t B_FULL = BARS, B_EMPTY = BARS + 40, B_MLAND = BARS + 80, B_QK = BARS + 112, B_V = BARS + 120, B_OM = BARS + 128,
                   B_WA = BARS + 136, B_SDONE = BARS + 144, B_BFREE = BARS + 152, B_W1 = PM1, B_W2 = PM1 + 8, B_WO = PM1 + 16;
constexpr uint32_t SMEM = BARS + 160;
static_assert(SMEM <= 232448 && QB % 1024 == 0, "smem map");
constexpr int R1 = (PM1 - WO) / 4096;
constexpr int NB_WO = 1, NB_ST = 2, NB_P = 3, NB_TR = 4, NB_X = 5, NB_G = 6, NB_G1 = 7, NB_G2 = 8, NB_G4 = 9, NB_S = 10;
__host__ __device__ constexpr bool is_lo(int j) { return j % 12 == 8; }
__host__ __device__ constexpr int lo_before(int j) { return (j + 3) / 12; }
__host__ __device__ constexpr int ss_before(int j) { return (j - lo_before(j)) * NSS / (64 - NLO); }
__host__ __device__ constexpr bool is_ss(int j) { return ss_before(j + 1) != ss_before(j); }
__host__ __device__ constexpr int reg_idx(int j) { return is_lo(j) ? NHI + lo_before(j) : j - ss_before(j) - lo_before(j); }
#define LOQ(i) ((0x12010 >> (4 * (i))) & 3)
template<int j> using OpW = Op<WS + ss_before(j) * 2048, 16, 1024, 1, 1>;
#define P_G1 1
#define P_G2 3
#define P_G2L 0
#define P_OS 1
#define P_NA 6
#define P_G4 10
#define P_G5 12
#define P_FW 0
#define P_SEND 0xff3f2f10u
#define P_WB 2
#define P_WOL 0
#define P_G4L 0
#define P_S1 1
#define P_S2 2
#define P_S0 3
#define P_MB 0
#define P_S4 5
#define P_S5 6
constexpr uint32_t SLOT1 = 0x32410324, USE1 = 0x22111110;
DEVI bool single(int s) { return s < LAG - 1 || s >= NSEG - 1; }
#define TUN(i, v) (v)
}
#define PROFW(wq, i)
DEVI uint32_t mapr(int h, uint32_t addr, int rank) { return mapa(addr, rank + (R_CL == 6 ? (h & 1) * 3 : 0)); }
template<int N> DEVI void pin(float* d) {
#pragma unroll
  for (int i = 0; i < N; i++) asm volatile("" : "+f"(d[i]) :: "memory");
}
DEVI void keep(const void* a) { asm volatile("{.reg .pred p; setp.eq.u64 p, %0, 0; vote.sync.any.pred p, p, 0xffffffff; @p exit;}" :: "l"(a) : "memory"); }
DEVI int lane_reg() { return __shfl_sync(0xffffffffu, threadIdx.x & 31, threadIdx.x & 31); }
#define LANE_NOW [[maybe_unused]] const int lane = lane0 + ((uint32_t)budget >> 30), g = lane >> 2, c = lane & 3

DEVI void rec_proj(const uint32_t sb, const int h, const int rank, const int w, const CUtensorMap* mW, const CUtensorMap* mWo, const uint32_t zero) {
  using namespace rec;
  const int lane0 = lane_reg(), wg = w >> 2, ww = w & 3;
  int budget = SPIN_BUDGET;
  uint32_t wr[NRS * 4];
  {
    LANE_NOW;
    const uint32_t wsw = ((lane & 7) + (lane >> 4) * 8) * 128 + (((ww * 2 + ((lane >> 3) & 1)) ^ (lane & 7)) << 4);
    mbar_wait(sb + B_W1, 0, budget);
#pragma unroll
    for (int r = 0; r < R1; r++) ldsm4t(sb + WO + (wg * R1 + r) * 2048 + wsw, wr[4*r], wr[4*r+1], wr[4*r+2], wr[4*r+3]);
    fence_proxy_async();
    nbar_sync<NB_ST, 256>();
    if (w == 0) {
      if (lane == 0) { mbar_expect_tx(sb + B_W2, (NRS - R1) * 4096); mbar_expect_tx(sb + B_WO, rank == 2 ? 65536 + 16384 + 8192 : 65536); }
      __syncwarp();
      for (int i = lane; i < 128; i += 32) {
        const int j = i & 63, t = i >> 6, r = reg_idx(j);
        if (!is_ss(j) && r >= R1) tma_load_2d(sb + RING + (t * (NRS - R1) + r - R1) * 2048, mW, h * DH + t * 64, j * 16, sb + B_W2);
      }
      const int t0 = (rank + 1) % 3;
      if (lane < 8) tma_load_2d(sb + WO + lane * 8192, mWo, (3 * ((lane >> 1) + (lane >> 1 >= JA)) + t0) * 64, h * DH + (lane & 1) * 64, sb + B_WO);
      else if (rank == 2 && lane < 11) tma_load_2d(lane < 10 ? sb + WA + (lane - 8) * 8192 : sb + WH, mWo, lane < 10 ? 3 * JA * 64 : 15 * 64, h * DH + (lane > 8) * 64, sb + B_WO);
    }
    mbar_wait(sb + B_W2, 0, budget);
#pragma unroll
    for (int r = R1; r < NRS; r++) ldsm4t(sb + RING + (wg * (NRS - R1) + r - R1) * 2048 + wsw, wr[4*r], wr[4*r+1], wr[4*r+2], wr[4*r+3]);
    fence_proxy_async();
    cluster_arrive(); cluster_wait();
  }
  const uint32_t d0 = desc_base(sb), da = d0 + wg * (NSS * 128);
  const uint32_t pos = rank == 0 ? POSQ : rank == 1 ? POSK : POSV, bar = rank == 2 ? B_V : B_QK;
  uint32_t stg[3][4] = {}, pk[16] = {};
  auto stage = [&](uint32_t* t, int r) {
#pragma unroll
    for (int i = 0; i < 4; i++) asm volatile("xor.b32 %0, %1, %2;" : "+r"(t[i]) : "r"(wr[4 * r + i]), "r"(zero));
  };
#pragma unroll 1
  for (int s = -1; s < NSTEP; s++) {
    const uint32_t fl = single(s) ? (s + 1) & 1 : 0;
    if (s >= 0) {
      float d[8];
      stage(stg[0], NHI);
      mbar_wait(sb + B_FULL, 0, budget);
      PROFW(0, 16);
      sfor<0, 8>([&](auto E) {
        constexpr int e = E, q = e >> 1;
        wg_fence();
        sfor<8 * e, 8 * e + 8>([&](auto J) {
          constexpr int j = J;
          typedef Op<RING + j * 512, 256, 128, 0, 1> OB;
          if constexpr (is_ss(j)) wg_ss16<j != 0, OpW<j>, OB>(d, da, d0);
          else wg_rs16<j != 0, OB>(d, is_lo(j) ? stg[LOQ(lo_before(j))] : wr + 4 * reg_idx(j), d0);
        });
        wg_commit();
        if constexpr (e == 0) { if (s > 0) mbar_wait(sb + B_BFREE, (s & 1) ^ 1, budget); }
        if constexpr (e > 0 && !(e & 1)) {
          wg_wait<1>();
          arrive_if_eq(sb + B_EMPTY + 8 * (q - 1), lane0, ww * 32);
        }
        if constexpr (e < 6 && !(e & 1)) sfor<lo_before(16 * q + 16), lo_before(16 * q + 32)>([&](auto I) { constexpr int i = I; stage(stg[LOQ(i)], NHI + i); });
        if constexpr (e < 6 && (e & 1) == P_FW) mbar_wait(sb + B_FULL + 8 * (q + 1), q ? fl : 0, budget);
        if constexpr (((P_SEND >> (4 * e)) & 15) < 4) {
          constexpr int n = (P_SEND >> (4 * e)) & 15;
          LANE_NOW;
          const uint32_t r = mapr(h, sb, n >> 1);
          uint32_t t[4];
#pragma unroll
          for (int i = 0; i < 4; i++) { if (n == 0) t[i] = pk[i]; else asm volatile("xor.b32 %0, %1, %2;" : "=r"(t[i]) : "r"(pk[4*n+i]), "r"(zero)); }
          st_cl128(rank == n >> 1, r + QB + ((pos >> (4 + 4 * c)) & 15) * RG + w * 256 + (n & 1) * 128 + g * 16, t[0], t[1], t[2], t[3], r + bar);
        }
      });
      LANE_NOW;
      const uint32_t dst = QB + (pos & 15) * RG + w * 256 + lane * 4;
      wg_wait<0>();
      pin<8>(d);
      {
        const uint32_t x0 = pack_bf16(d[0], d[1]), x1 = pack_bf16(d[2], d[3]), y0 = pack_bf16(d[4], d[5]), y1 = pack_bf16(d[6], d[7]);
        const uint32_t r = mapr(h, sb, rank == 0);
        if (rank < 2) { sts32v(sb + dst, rank ? y0 : x0); sts32v(sb + dst + 128, rank ? y1 : x1); fence_proxy_async(); }
        st_async32(r + dst, rank ? x0 : y0, r + bar); st_async32(r + dst + 128, rank ? x1 : y1, r + bar);
        if (rank < 2) e_arrive(sb + B_QK);
        else { const uint32_t r1 = mapr(h, sb, 1); st_async32(r1 + dst, y0, r1 + bar); st_async32(r1 + dst + 128, y1, r1 + bar); }
      }
      PROFW(0, 17);
      if (s == NSTEP - 1) break;
      arrive_if_eq(sb + B_EMPTY + 24, lane0, ww * 32);
    } else e_arrive(sb + B_EMPTY + 8 * ww);
    const bool gate = rank < 2 && s >= 0;
    if (single(s)) {
      float d[16];
      sfor<0, 8>([&](auto C) {
        constexpr int cc = C, sl = (SLOT1 >> (4 * cc)) & 15;
        if constexpr (cc == 0) mbar_wait(sb + B_FULL + 8 * sl, 0, budget);
        if constexpr (cc == P_S1) { if (gate) nbar_sync<NB_G1, 384>(); }
        if constexpr (cc == P_S2) { if (gate) nbar_sync<NB_G2, 384>(); }
        if constexpr (cc == P_S0) nbar_sync<NB_WO, 384>();
        if constexpr (cc == P_S4 || cc == P_S5) { if (gate && cc == (rank ? P_S5 : P_S4)) nbar_sync<NB_G4, 384>(); }
        if constexpr (lo_before(cc * 8 + 8) != lo_before(cc * 8)) stage(stg[0], NHI + lo_before(cc * 8));
        wg_fence();
        sfor<0, 8>([&](auto I) {
          constexpr int i = I, j = cc * 8 + i;
          typedef Op<RING + sl * 8192 + (i >> 2) * 4096 + (i & 3) * 32, 16, 1024, 1, 0> OB;
          if constexpr (is_ss(j)) wg_ss32<j != 0, OpW<j>, OB>(d, da, d0);
          else wg_rs32<j != 0, OB>(d, is_lo(j) ? stg[0] : wr + 4 * reg_idx(j), d0);
        });
        wg_commit();
        if constexpr (cc < 7) {
          constexpr int sn = (SLOT1 >> (4 * cc + 4)) & 15;
          mbar_wait(sb + B_FULL + 8 * sn, ((USE1 >> (4 * cc + 4)) & 1) ^ (sn >> 1 == 1 ? fl : 0), budget);
        }
        wg_wait<0>();
        arrive_if_eq(sb + B_EMPTY + 8 * sl, lane0, ww * 32);
      });
      pin<16>(d);
      PROFW(0, 20);
#pragma unroll
      for (int i = 0; i < 8; i++) pk[i] = pk[8 + i] = pack_bf16(d[4 * (i & 3) + ((i >> 1) & 2)], d[4 * (i & 3) + ((i >> 1) & 2) + 1]);
      continue;
    }
    float d[32];
    sfor<0, 16>([&](auto C) {
      constexpr int cc = C, sl = (cc + 4) % 5;
      if constexpr (cc == 0) mbar_wait(sb + B_FULL + 8 * sl, 0, budget);
      if constexpr (cc == P_G1) { if (gate) nbar_sync<NB_G1, 384>(); }
      if constexpr (cc == P_G2) { if (gate) nbar_sync<NB_G2, 384>(); }
      if constexpr (cc == P_NA) {
        PROFW(0, 18);
        nbar_sync<NB_WO, 384>();
      }
      if constexpr (cc == P_G4 || cc == P_G5) { if (gate && cc == (rank ? P_G5 : P_G4)) nbar_sync<NB_G4, 384>(); }
      wg_fence();
      sfor<0, 4>([&](auto I) {
        constexpr int i = I, j = cc * 4 + i;
        typedef Op<RING + sl * 8192 + i * 32, 16, 1024, 1, 0> OB;
        if constexpr (is_ss(j)) wg_ss64<j != 0, OpW<j>, OB>(d, da, d0);
        else wg_rs64<j != 0, OB>(d, is_lo(j) ? stg[0] : wr + 4 * reg_idx(j), d0);
      });
      wg_commit();
      if constexpr (cc == P_NA) PROFW(0, 19);
      if constexpr (cc < 15) {
        if constexpr (is_lo(cc * 4 + 4)) stage(stg[0], reg_idx(cc * 4 + 4));
        mbar_wait(sb + B_FULL + 8 * ((sl + 1) % 5), ((cc + 5) / 5) & 1, budget);
      }
      wg_wait<0>();
      arrive_if_eq(sb + B_EMPTY + 8 * sl, lane0, ww * 32);
    });
    pin<32>(d);
    PROFW(0, 20);
#pragma unroll
    for (int i = 0; i < 16; i++) pk[i] = pack_bf16(d[16 * (i >> 3) + 4 * (i & 3) + ((i >> 1) & 2)], d[16 * (i >> 3) + 4 * (i & 3) + ((i >> 1) & 2) + 1]);
  }
}

DEVI float softmax_row(float* v, uint32_t* p) {
  constexpr float SC = 0.08838834764831845f * 1.4426950408889634f;
  float m = fmaxf(fmaxf(fmaxf(fmaxf(v[0], v[1]), fmaxf(v[2], v[3])), fmaxf(fmaxf(v[4], v[5]), fmaxf(v[6], v[7]))), fmaxf(v[8], v[9]));
  m = fmaxf(m, __shfl_xor_sync(0xffffffffu, m, 1));
  m = fmaxf(m, __shfl_xor_sync(0xffffffffu, m, 2));
  const float ms = -m * SC, mh = fmaf(m, -SC, -1.f);
#pragma unroll
  for (int i = 0; i < 10; i++) asm("ex2.approx.ftz.f32 %0, %1;" : "=f"(v[i]) : "f"(fmaf(v[i], SC, i < 8 ? ms : mh)));
#pragma unroll
  for (int n = 0; n < 5; n++) p[n] = pack_bf16(v[2*n], v[2*n+1]);
  return fmaf(v[8] + v[9], 2.f, ((v[0] + v[1]) + (v[2] + v[3])) + ((v[4] + v[5]) + (v[6] + v[7])));
}

template<bool ATT>
DEVI void rec_attn(const uint32_t sb, int h, int rank, int w, const bf16* __restrict__ Wo, const bf16* __restrict__ mem0) {
  using namespace rec;
  const int lane0 = lane_reg();
  int budget = SPIN_BUDGET;
  constexpr int NT = ATT ? 5 : 6;
  uint32_t wl[16];
  if (!ATT) {
    LANE_NOW;
#pragma unroll
    for (int i = 0; i < 16; i++) {
      const int dh = 8 * (i >> 1) + 2 * c;
      const unsigned short* p = (const unsigned short*)Wo + (size_t)(h * DH + dh) * DM + 15 * 64 + 16 * w + 8 * (i & 1) + g;
      wl[i] = p[0] | (uint32_t)p[DM] << 16;
    }
  }
  mbar_wait(sb + B_WO, 0, budget);
  cluster_arrive(); cluster_wait();
  const uint32_t d0 = desc_base(sb);
  uint32_t pph = 0;
#pragma unroll 1
  for (int s = -1; s < NSTEP; s++) {
    asm volatile("" : "+r"(h), "+r"(rank), "+r"(w));
    const uint32_t sp = s & 1;
    const int t0 = ATT ? rank + 1 : 0;
    const bool more = s + 1 < NSTEP;
    float hold[10] = {0, 0, 0, 0, 0, 0, 0, 0, 0, 0};
    if (ATT && s >= 0) {
      float sc[20];
      LANE_NOW;
      mbar_wait(sb + B_QK, sp, budget);
      PROFW(0, 1);
      fence_proxy_async();
      wg_fence();
      sfor<0, 8>([&](auto K) { constexpr int k = K; wg_ss40<k != 0, Op<QB + k * 256, 128, RG, 0, 1>, Op<QB + 3 * RG + k * 256, 128, 2 * RG, 0, 1>>(sc, d0, d0); });
      wg_commit();
      if (P_G1 < 16 && more) nbar_arrive<NB_G1, 384>();
      mbar_wait(sb + B_V, sp, budget);
      wg_wait<0>();
      pin<20>(sc);
      if (w == 3 && more) nbar_arrive<NB_S, 64>();
      PROFW(1, 2);
      if (w == 0) {
        uint32_t p[5];
        float v[10];
#pragma unroll
        for (int i = 0; i < 10; i++) v[i] = sc[4 * (i >> 1) + (i & 1)];
        softmax_row(v, p);
        const uint32_t a = sb + lane * 4;
        sts32v(a + PM0, p[0]); sts32v(a + PM0 + 128, p[1]); sts32v(a + PM1, p[2]); sts32v(a + PM1 + 128, p[3]); sts32v(a + PM2, p[4]);
      }
      if (more) {
        float rs[4], ot[2][4];
        uint32_t one[4];
#pragma unroll
        for (int i = 0; i < 4; i++) one[i] = 0x3F803F80u + ((uint32_t)budget >> (31 - i));
        typedef Op<PM0, 128, 128, 0, 0> P0; typedef Op<PM1, 128, 128, 0, 0> P1; typedef Op<PM2, 0, 128, 0, 0> P2;
        fence_proxy_async();
        nbar_sync<NB_P, 128>();
        PROFW(0, 3);
        wg_fence();
        wg_rs8<0, P0>(rs, one, d0); wg_rs8<1, P1>(rs, one, d0); wg_rs8<1, P2>(rs, one, d0);
        wg_commit();
        sfor<0, 2>([&](auto T) {
          constexpr int t = T;
          wg_ss8<0, Op<QB + 8 * RG + t * 1024, 2 * RG, 128, 0, 0>, P0>(ot[t], d0, d0);
          wg_ss8<1, Op<QB + 12 * RG + t * 1024, RG, 128, 0, 0>, P1>(ot[t], d0, d0);
          wg_ss8<1, Op<QB + 14 * RG + t * 1024, 0, 128, 0, 0>, P2>(ot[t], d0, d0);
        });
        wg_commit();
        if (P_G2 < 16 && !P_G2L) nbar_arrive<NB_G2, 384>();
        const uint32_t oa = w * 256 + lane * 4, r1 = mapr(h, sb, rank ^ 1), r2 = mapr(h, sb, 2);
        mbar_wait(sb + B_SDONE, sp, budget);
        wg_wait<1>();
        pin<4>(rs);
        float i0, i1;
        asm volatile("rcp.approx.ftz.f32 %0, %1;" : "=f"(i0) : "f"(rs[0]));
        asm volatile("rcp.approx.ftz.f32 %0, %1;" : "=f"(i1) : "f"(rs[1]));
        wg_wait<0>();
        pin<4>(ot[0]); pin<4>(ot[1]);
        uint32_t x[4];
#pragma unroll
        for (int j = 0; j < 4; j++) {
          x[j] = pack_bf16(ot[j >> 1][2 * (j & 1)] * i0, ot[j >> 1][2 * (j & 1) + 1] * i1);
          sts32v(sb + OM + rank * OMS + oa + (j >> 1) * 1024 + (j & 1) * 128, x[j]);
        }
        fence_proxy_async();
#pragma unroll
        for (int j = 0; j < 8; j++) {
          const int i = P_OS ? j >> 1 : j & 3;
          if (P_OS ? j & 1 : j >> 2) st_async32(r1 + OM + rank * OMS + oa + (i >> 1) * 1024 + (i & 1) * 128, x[i], r1 + B_OM);
          else st_async32(r2 + OM2 + rank * OM2S + oa + (i >> 1) * 1024 + (i & 1) * 128, x[i], r2 + B_OM);
        }
        e_arrive(sb + B_OM);
        if (P_G2 < 16 && P_G2L) nbar_arrive<NB_G2, 384>();
        PROFW(0, 4);
      }
#pragma unroll
      for (int i = 0; i < 10; i++) hold[i] = w ? sc[4 * (i >> 1) + (i & 1)] : sc[4 * (i >> 1) + 2 + (i & 1)];
    }
    if (more && s >= 0) {
      LANE_NOW;
      char* const pw = (char*)g_part + (uint32_t)((t0 * 16 + w * 4 + (lane >> 3)) * 4096 + h * 128 + ((lane ^ h) & 7) * 16);
      mbar_wait(sb + B_OM, sp, budget);
      if (w == 0) nbar_arrive<NB_G, 128>();
      PROFW(1, 5);
      if (!ATT) fence_proxy_async();
      float acc[3][8];
      auto store = [&](auto J) {
        constexpr int j = J;
        float* d = acc[j % 3];
        pin<8>(d);
        uint32_t x[4];
#pragma unroll
        for (int i = 0; i < 4; i++) { const uint32_t m = (h >> 3) == i; x[i] = (pack_bf16(d[2*i], d[2*i+1]) & ~m) | (m & ~sp); }
        stg_rlx128(pw + j * (48 * 4096), x[0], x[1], x[2], x[3]);
        if constexpr (ATT && j == JA) nbar_arrive<NB_TR, 160>();
        if constexpr (j == 2) PROFW(3, 26);
      };
      sfor<0, NT>([&](auto J) {
        constexpr int j = J;
        if constexpr (ATT && j == JA) { mbar_wait(sb + B_WA, sp, budget); PROFW(2, 0); }
        wg_fence();
        sfor<0, 8>([&](auto K) {
          constexpr int k = K;
          typedef Op<(ATT ? OM : OM2) + k * 256, 128, ATT ? OMS : OM2S, 0, 1> OB;
          if constexpr (j == 5 && k < 4) wg_rs16<k ? 1 : 2, OB>(acc[j % 3], wl + 4 * k, d0);
          else wg_ss16<k ? 1 : j < 3 ? 0 : 2, Op<(j == JA ? WA : j < 5 ? WO + (j - (j > JA)) * 16384 : WH - 8192) + k * 2048, 16, 1024, 1, 1>, OB>(acc[j % 3], d0, d0);
        });
        wg_commit();
        if constexpr (j == 0) { if (w == 3) e_expect_tx(sb + B_OM, ATT ? 2048 : 4096); }
        if constexpr (j == NT - 1 && !P_WOL) nbar_arrive<NB_WO, 384>();
        if constexpr (j > 0 && j != P_WB + 1) { wg_wait<1>(); store(IC<j - 1>{}); }
        if constexpr (j == P_WB || j == NT - 1) { wg_wait<0>(); store(IC<j>{}); }
        if constexpr (j == P_WB) {
          const uint32_t t = clock32();
          if (ATT) {
            if (w == 3 && lane < 14) sts128(sb + PM1 + lane * 16, (lane >> 1) == 3 ? 0x3F803F80u : 0);
            if (w == 3 || P_MB) fence_proxy_async();
            nbar_sync<NB_P, 128>();
          } else if (P_MB) fence_proxy_async();
          spin_until(t, TUN(8, 100));
        }
      });
      if (P_WOL) { spin_until(clock32(), TUN(9, 0)); nbar_arrive<NB_WO, 384>(); }
    } else if (more) nbar_arrive<NB_WO, 384>();
    PROFW(0, 6);
    asm volatile("" : "+r"(h), "+r"(rank), "+r"(w));
#pragma unroll 1
    for (int pass = 0; ATT && pass < 2; pass++)
    if (pass != rank) {
      LANE_NOW;
      const int lim = 8 * (g >> 1) + (g & 1) + 2 * w - 8 * c;
      uint32_t p[5];
#pragma unroll
      for (int i = 0; i < 8; i++) hold[2+i] = i <= lim ? hold[2+i] : -INFINITY;
      const float psum = softmax_row(hold, p);
#pragma unroll
      for (int i = 0; i < 5; i++) hold[i] = __uint_as_float(p[i]);
      hold[5] = psum;
    } else if (more) {
      LANE_NOW;
      const int blk = rank * 32 + h;
      char* const mw = (char*)g_mem + (uint32_t)(sp * 32768 + blk * 512 + w * 128 + lane * 4);
      uint32_t v0 = 0;
      if (s == -1 || (s == LAG - 1 && (w & 1))) {
        const unsigned short* q = (const unsigned short*)mem0 + c * 2 * DM + blk * 16 + (w >> 1) * 8 + g;
        v0 = q[0] | (uint32_t)q[DM] << 16;
        if (v0 == 0) v0 = 0x8000u;
      }
      keep(mw);
      if (s >= 0) {
        const uint32_t ca = sb + WA + lane * 128 + (((2 * w) ^ lane) & 7) * 16 + (lane >> 3) * 4;
        const uint32_t sa = sb + OM + (((g >> 1) & 1) * 2 + (g >> 2)) * 128 + (2 * c + (w >> 1)) * 16 + (w & 1) * 8 + (g & 1) * 2;
        for (bool first = true; ; first = false) {
          float r[4];
          mbar_wait(sb + B_PART, pph, budget);
          PROFW(0, 11);
          pph ^= 1;
          wg_fence();
          sfor<0, 8>([&](auto K) { constexpr int k = K; wg_ss8<k != 0, Op<WA + k * 2048, 16, 1024, 1, 1>, Op<PM1 + (6 - (k & 6)) * 16, 0, 128, 0, 0>>(r, d0, d0); });
          wg_commit();
          if (P_G4 < 16 && !P_G4L && first) nbar_arrive<NB_G4, 384>();
          const uint32_t x0 = lds32v(ca), x1 = lds32v(ca + 4096), x2 = lds32v(ca + 8192), x3 = lds32v(ca + 12288);
          bool bad = __any_sync(0xffffffffu, (sp ? x0 | x1 | x2 | x3 : ~(x0 & x1 & x2 & x3)) & 1) && budget > 0;
          wg_wait<0>();
          pin<4>(r);
          uint32_t y = pack_bf16(r[0], r[2]);
          y |= (y & 0xffffu) ? 0 : 0x8000u;
          y |= (y >> 16) ? 0 : 0x80000000u;
          if (bad) y = 0;
          sts16(sa, y); sts16(sa + 4, y >> 16);
          nbar_sync<NB_P, 128>();
          y = lds32v(sb + OM + w * 128 + lane * 4);
          const bool ok = !__any_sync(0xffffffffu, y == 0);
          if (ok) stg_rlx32(mw, v0 ? v0 : y);
          if (P_G4 < 16 && P_G4L && first) nbar_arrive<NB_G4, 384>();
          if (ok) break;
          nbar_sync<NB_P, 128>();
          budget--;
          if (w == 0) { e_expect_tx(sb + B_PART, 16384); e_bulk_g2s(sb + WA, (const char*)g_part + blk * 16384, 16384, sb + B_PART); }
          __syncwarp();
        }
      } else stg_rlx32(mw, v0);
      stg_rlx32(mw + (sp ? -32768 : 32768), 0);
      PROFW(1, 8);
    }
    if (ATT && s >= 0) {
      const int seg = s - (rank ? LAG : 0);
      const bool act = (unsigned)seg < NSEG;
      LANE_NOW;
      uint32_t a[12];
#pragma unroll
      for (int i = 0; i < 12; i++) a[i] = __float_as_uint(hold[i < 10 ? i >> 1 : 4]) + ((uint32_t)budget >> (31 - (i & 3)));
      float o[32], inv, psum = hold[5];
      char* const ob = (char*)g_o[rank] + ((size_t)(seg * 32 + 8 * (g >> 1) + (g & 1) + 2 * w) * (NH * DH) + h * DH + c * 8) * 2;
      sfor<0, 2>([&](auto HF) {
        constexpr int hf = HF;
        wg_fence();
        wg_rs64<hf * 2, Op<QB + 8 * RG + hf * 1024, 2 * RG, 128, 0, 0>>(o, a, d0);
        wg_rs64<1, Op<QB + 12 * RG + hf * 1024, RG, 128, 0, 0>>(o, a + 4, d0);
        wg_rs64<1, Op<QB + 14 * RG + hf * 1024, 0, 128, 0, 0>>(o, a + 8, d0);
        wg_commit();
        if constexpr (hf == 0) {
          psum += __shfl_xor_sync(0xffffffffu, psum, 1);
          psum += __shfl_xor_sync(0xffffffffu, psum, 2);
          asm("rcp.approx.ftz.f32 %0, %1;" : "=f"(inv) : "f"(psum));
        }
        wg_wait<0>();
        pin<32>(o);
        if constexpr (hf == 1) { if (w < 3 && more) e_arrive_cl(mapr(h, sb + B_BFREE, w)); }
        if (act) {
#pragma unroll
          for (int i = 0; i < 2; i++)
            stg128(ob + (hf * 2 + i) * 64, pack_bf16(o[16*i] * inv, o[16*i+1] * inv), pack_bf16(o[16*i+4] * inv, o[16*i+5] * inv),
                   pack_bf16(o[16*i+8] * inv, o[16*i+9] * inv), pack_bf16(o[16*i+12] * inv, o[16*i+13] * inv));
        }
      });
      PROFW(0, 7);
      if (act && (seg & 3) == 3) {
        __syncwarp();
        e_flag_add(g_fl.dep + grp(0, rank, seg >> 2));
      }
    } else if (!ATT && w == 3) {
      if (s + 4 < NSEG) e_prefetch(g_xn[0] + (size_t)((s + 4) * 32 + h) * DM, 2048);
    }
  }
  cluster_arrive(); cluster_wait();
  char* const pw = (char*)g_part + (size_t)((ATT ? rank + 1 : 0) * 16 + w * 4 + (lane0 >> 3)) * 4096 + h * 128 + (lane0 & 7) * 16;
#pragma unroll
  for (int j = 0; j < NT; j++) stg_rlx128(pw + j * (48 * 4096), 0, 0, 0, 0);
}

DEVI void rec_load(const uint32_t sb, const int h, const int rank, const int w, const CUtensorMap* mX, const CUtensorMap* mWo) {
  using namespace rec;
  static_assert(((NSTEP - 1) & 31) != 1 && ((NSTEP - 2) & 31) != 2, "stale time stamps of the previous launch never match");
  const int lane0 = lane_reg(), mq = (w + 3) & 3;
  int budget = SPIN_BUDGET;
  cluster_arrive(); cluster_wait();
  if (w == 0) { if (lane0 < 4) mbar_arrive(sb + B_FULL + 8 * lane0); __syncwarp(); }
  uint32_t lph = 0;
#pragma unroll 1
  for (int s = -1; s < NSTEP - 1; s++) {
    if (w == 0) {
      const int sa = s + 1, sn = sa - LAG;
      if ((sa & 3) == 0 && sa < NSEG) flag_wait(g_fl.xn[0][sa >> 2], 128, budget);
      if ((sn & 3) == 0 && (unsigned)sn < NSEG) flag_wait(g_fl.xn[1][sn >> 2], 128, budget);
      if (single(s)) {
#pragma unroll 1
        for (int i = 0; i < 8; i++) {
          const int k = i < 5 ? (0x21430 >> (4 * i)) & 15 : i;
          const int sl = (SLOT1 >> (4 * k)) & 15;
          mbar_wait(sb + B_EMPTY + 8 * sl, (((USE1 >> (4 * k)) ^ (sl >> 1 == 1 ? s + 1 : 0)) & 1) ^ 1, budget);
          e_expect_tx(sb + B_FULL + 8 * sl, 8192);
          e_tma_3d(sb + RING + sl * 8192, mX + 1, 0, (s + 1 + (s < LAG ? 0 : NSTEP)) * 32, k * 2, sb + B_FULL + 8 * sl);
        }
      } else {
        int sl = 4, ph = 1;
#pragma unroll 1
        for (int i = 0; i < 16; i++) {
          mbar_wait(sb + B_EMPTY + 8 * sl, ph, budget);
          e_expect_tx(sb + B_FULL + 8 * sl, 8192);
          e_tma_3d(sb + RING + sl * 8192, mX, i * 64, (s + 1) * 32, 0, sb + B_FULL + 8 * sl);
          if (++sl == 5) { sl = 0; ph ^= 1; }
        }
      }
      nbar_arrive<NB_X, 128>();
    }
    uint32_t t = gtime();
    if (s >= 0) {
      uint2 a;
      if (w == 2 && rank < 2) {
        nbar_sync<NB_S, 64>();
        e_expect_tx(sb + B_WA, 16384);
        e_tma_2d(sb + WA, mWo, (3 * JA + 1 + rank) * 64, h * DH, sb + B_WA);
        e_tma_2d(sb + WA + 8192, mWo, (3 * JA + 1 + rank) * 64, h * DH + 64, sb + B_WA);
        e_arrive_cl(mapr(h, sb + B_SDONE, rank ^ 1));
        stg_rlx32(&g_ann[s & 1][lane0][h * 2 + rank], (gtime() & ~31u) | ((s + 1) & 31));
        e_expect_tx(sb + B_QK, 10240);
        e_expect_tx(sb + B_V, 10240);
      }
      if (w) nbar_sync<NB_G, 128>();
      do { a = ldg_rlx64(&g_ann[s & 1][h][lane0 * 2]); } while (__any_sync(0xffffffffu, ((a.x ^ (s + 1)) | (a.y ^ (s + 1))) & 31) && --budget > 0);
      t += __reduce_max_sync(0xffffffffu, max((int)(a.x - t), (int)(a.y - t)));
      t = (t & ~31u) - (single(s) ? TUN(6, 200) : 0);
      PROFW(1, 12);
      if (w == 1 && rank < 2) {
        nbar_sync<NB_TR, 160>();
        wait_time(t + (rank ? TUN(1, 1750) : TUN(0, 1400)), budget);
        e_expect_tx(sb + B_PART, 16384);
        e_bulk_g2s(sb + WA, (const char*)g_part + (rank * 32 + h) * 16384, 16384, sb + B_PART);
        PROFW(1, 21);
      }
      t -= single(s) ? TUN(7, 100) : 0;
      t += mq == 0 ? TUN(2, 2450) : mq == 1 ? TUN(3, 2500) : mq == 2 ? TUN(4, 2800) : TUN(5, 2850);
    }
    if (w) nbar_sync<NB_X, 128>();
    mbar_wait(sb + B_EMPTY + 8 * mq, mq >= 2 && single(s) ? (s + 1) & 1 : 1, budget);
    PROFW(1, 9);
    wait_time(t, budget);
    PROFW(1, 22); PROFW(3, 23);
    while (true) {
      e_expect_tx(sb + B_MLAND + 8 * mq, 8192);
      e_bulk_g2s(sb + RING + mq * 8192, (const char*)g_mem + (s & 1) * 32768 + mq * 8192, 8192, sb + B_MLAND + 8 * mq);
      const uint32_t a = sb + RING + mq * 8192 + lane0 * 32 + (lane0 >> 2) * 4;
      mbar_wait(sb + B_MLAND + 8 * mq, lph, budget);
      lph ^= 1;
      PROFW(1, 24);
      uint32_t mn = 0xffffffffu;
#pragma unroll
      for (int i = 0; i < 8; i++) mn = min(mn, lds32v(a + i * 1024));
      if (!__any_sync(0xffffffffu, mn == 0) || --budget <= 0) break;
    }
    e_arrive(sb + B_FULL + 8 * mq);
    PROFW(1, 10); PROFW(2, 13); PROFW(3, 14); PROFW(0, 15);
  }
}

struct RecMaps { CUtensorMap w[3], wo, x[2]; };
__global__ void __cluster_dims__(R_CL, 1, 1) __launch_bounds__(512, 1)
rec_kernel(const __grid_constant__ RecMaps M, const bf16* __restrict__ Wo, const bf16* __restrict__ mem0, uint32_t zero) {
  using namespace rec;
  extern __shared__ __align__(1024) uint8_t smem[];
  const uint32_t sb = smem_u32(smem);
  const int tid = threadIdx.x, warp = __shfl_sync(0xffffffffu, tid >> 5, 0), wg = warp >> 2, lane = tid & 31;
  const int h = blockIdx.x / 3, rank = blockIdx.x % 3;
  if (warp == 0) {
    if (lane < 20) mbar_init(sb + BARS + 8 * lane, (lane >= 5 && lane < 10) || lane == 19 ? 2 : lane == 14 ? 9 : lane == 16 && rank < 2 ? 5 : 1);
    else if (lane < 23) mbar_init(sb + B_W1 + 8 * (lane - 20), 1);
    else if (lane == 23) mbar_init(sb + B_PART, 1);
    fence_mbar_init();
    __syncwarp();
    if (lane == 0) { mbar_expect_tx(sb + B_W1, (NSS + R1) * 4096); mbar_expect_tx(sb + B_QK, 10240); mbar_expect_tx(sb + B_V, 10240); mbar_expect_tx(sb + B_OM, rank < 2 ? 2048 : 4096); }
    __syncwarp();
    for (int i = lane; i < 128; i += 32) {
      const int j = i >> 1, t = i & 1, r = reg_idx(j);
      if (is_ss(j)) tma_load_2d(sb + WS + (t * NSS + ss_before(j)) * 2048, &M.w[rank], h * DH + t * 64, j * 16, sb + B_W1);
      else if (r < R1) tma_load_2d(sb + WO + (t * R1 + r) * 2048, &M.w[rank], h * DH + t * 64, j * 16, sb + B_W1);
      else tma_prefetch_2d(&M.w[rank], h * DH + t * 64, j * 16);
    }
    const int t = 3 * (lane >> 1) + (rank + 1) % 3;
    if (t < 16) tma_prefetch_2d(&M.wo, t * 64, h * DH + (lane & 1) * 64);
  } else if (warp == 1) {
    constexpr int N = (sizeof(Flags) - sizeof(g_fl.xn)) / 16;
    if (lane == 0 && blockIdx.x < N) ((uint4*)g_fl.dep)[blockIdx.x] = make_uint4(0, 0, 0, 0);
    static_assert(N <= 96, "flag reset");
    __threadfence();
    __syncwarp();
    asm volatile("griddepcontrol.launch_dependents;" ::: "memory");
  }
  __syncthreads();
  if (wg == 3) {
    reg_dec<24>();
    rec_load(sb, h, rank, warp & 3, M.x, &M.wo);
    cluster_arrive(); cluster_wait();
  } else if (wg == 2) {
    reg_dec<72>();
    if (rank < 2) rec_attn<true>(sb, h, rank, warp & 3, Wo, mem0);
    else rec_attn<false>(sb, h, rank, warp & 3, Wo, mem0);
  } else {
    reg_inc<208>();
    rec_proj(sb, h, rank, warp, &M.w[rank], &M.wo, zero);
    cluster_arrive(); cluster_wait();
  }
}

namespace gm {
constexpr int STAGES = 6, STAGE_BYTES = 32768;
constexpr uint32_t SO = STAGES * STAGE_BYTES, B_FULL = SO + 32768, B_TRIG = B_FULL + 56, B_EMPTY = B_FULL + 64, B_JOB = B_FULL + 128,
                   B_MSG = B_FULL + 144, B_XF = B_FULL + 160, B_SF = B_FULL + 176, JOB = B_FULL + 192, MSG = JOB + 8, SMEM = B_FULL + 256;
constexpr int T_O = 0, T_GU = 1, T_D = 2, T_END = 3, NEARLY = 32;
#define G_LOOK 8
#define G_FILL 3
struct Pipe { int s, ph; DEVI void next() { if (++s == STAGES) { s = 0; ph ^= 1; } } };
}
struct GemmMaps { CUtensorMap o, wo, x, x1, xm, xms, wg, wu, h, hs, wd, x2, out; };

DEVI float geglu(float g, float u) {
  const float z = g * (0.7978845608028654f + 0.035677408136300125f * g * g);
  float t; asm("tanh.approx.f32 %0, %1;" : "=f"(t) : "f"(z));
  const float hg = 0.5f * g;
  return fmaf(hg, t, hg) * u;
}
DEVI int h_ready(int v) { const int t = v ^ 0x101414; return t ? ((__ffs(t) - 1) >> 3) * 20 : 56; }
DEVI int a_ready(int ty, int l, int cb) {
  const int v = ld_acquire(g_fl.dep + grp(ty, l, cb));
  asm volatile("fence.proxy.async.global;" ::: "memory");
  return ty == gm::T_D ? h_ready(v) : v >= 128 ? 64 : 0;
}
DEVI void ln_row(const bf16* src, bf16* dst, int lane) {
  uint4 u[4];
  const uint32_t* x = (const uint32_t*)u;
#pragma unroll
  for (int i = 0; i < 4; i++) u[i] = __ldcg((const uint4*)src + i * 32 + lane);
  float mean = 0, q = 0;
#pragma unroll
  for (int i = 0; i < 16; i++) mean += bf_lo(x[i]) + bf_hi(x[i]);
  mean *= 1.f / 32;
#pragma unroll
  for (int i = 0; i < 16; i++) { const float a = bf_lo(x[i]) - mean, b = bf_hi(x[i]) - mean; q = fmaf(a, a, fmaf(b, b, q)); }
#pragma unroll
  for (int o = 1; o < 32; o *= 2) {
    const float m2 = __shfl_xor_sync(0xffffffffu, mean, o), q2 = __shfl_xor_sync(0xffffffffu, q, o), dl = m2 - mean;
    q = fmaf(dl * dl, 16.f * o, q + q2);
    mean = 0.5f * (mean + m2);
  }
  const float rs = rsqrtf(q * (1.f / DM) + 1e-5f), mr = -mean * rs;
#pragma unroll
  for (int i = 0; i < 4; i++) {
    uint32_t y[4];
#pragma unroll
    for (int k = 0; k < 4; k++) y[k] = pack_bf16(fmaf(bf_lo(x[4*i+k]), rs, mr), fmaf(bf_hi(x[4*i+k]), rs, mr));
    stg128((uint4*)dst + i * 32 + lane, y[0], y[1], y[2], y[3]);
  }
}

__global__ void __cluster_dims__(2, 1, 1) __launch_bounds__(512, 1) gemm_kernel(const __grid_constant__ GemmMaps M, const bf16* __restrict__ x) {
  using namespace gm;
  extern __shared__ __align__(1024) uint8_t smem[];
  const uint32_t sb = smem_u32(smem);
  const int tid = threadIdx.x, wid = __shfl_sync(0xffffffffu, tid >> 5, 0), wg = wid >> 2, warp = wid & 3;
  int budget = SPIN_BUDGET;
  const int rank = blockIdx.x & 1;
  const uint32_t peer = mapa(sb, rank ^ 1);
  if (tid < 24) mbar_init(sb + B_FULL + 8 * tid, tid >> 3 == 1 ? 2 : 1);
  fence_mbar_init();
  if (wid == 1 && rank == 0) sts32v(sb + JOB + 16, bcast(e_ticket(g_fl.ticket)));
  cluster_arrive(); cluster_wait();
  int pair;
  asm volatile("ld.shared::cluster.u32 %0, [%1];" : "=r"(pair) : "r"(mapa(sb + JOB + 16, 0)) : "memory");
  pair = __shfl_sync(0xffffffffu, pair, 0);
  const int cta = pair * 2 + rank, lane = lane_reg();
  if (wg >= 2) {
    reg_dec<72>();
    if (wid == 8 || wid == 10) {
      Pipe p; p.s = 0; p.ph = 1;
      for (int n = 0; ; n++) {
        if (wid == 8) e_expect_tx(sb + B_MSG + 8 * (n & 1), 4);
        mbar_wait(sb + B_MSG + 8 * (n & 1), (n >> 1) & 1, budget);
        const int msg = __shfl_sync(0xffffffffu, lds32v(sb + MSG + 4 * (n & 1)), 0);
        const int ty = (msg >> 11) & 3, l = (msg >> 10) & 1;
        const bool shb = ty == T_GU && l, spl = ty == T_O || (ty == T_D && !l);
        const int cb = ((msg >> 6) & 15) + (shb ? rank : 0), j = (msg & 63) + (ty == T_END || shb ? 0 : rank);
        const int ke = ty == T_O ? 64 : ty == T_GU ? 16 : 56, k0 = spl ? rank : 0, dk = spl ? 2 : 1;
        const int c0 = spl || ty == T_GU ? j * 64 : j * 128, c1 = spl ? c0 ^ 64 : ty == T_GU ? c0 : c0 + 64;
        mbar_wait(sb + B_EMPTY + 8 * p.s, p.ph, budget);
        trap_if_spent(budget);
        auto stages = [&](auto f) {
#pragma unroll 1
          for (int k = k0; k < ke; k += dk) {
            mbar_wait(sb + B_EMPTY + 8 * p.s, p.ph, budget);
            f(k, sb + p.s * STAGE_BYTES, sb + B_FULL + 8 * p.s);
            p.next();
          }
        };
        if (wid == 8) {
          const int job = ty << 11 | l << 10 | cb << 6 | j;
          sts32v(sb + JOB + 4 * (n & 1), job | p.s << 16 | (p.ph ^ 1) << 20);
          e_arrive(sb + B_JOB + 8 * (n & 1));
          if (ty == T_END) break;
          if (ty != T_GU) { e_expect_tx(sb + B_FULL + 8 * p.s, spl ? 16384 : STAGE_BYTES); p.next(); }
          const CUtensorMap* const m0 = ty == T_D ? &M.wd : shb && rank ? &M.wu : &M.wg, * const m1 = ty == T_D ? &M.wd : &M.wu;
          if (ty == T_O) stages([&](int k, uint32_t a, uint32_t fb) { e_expect_tx(fb, STAGE_BYTES); e_tma_5d(a + 16384, &M.wo, c0, k * 2, fb); e_tma_5d(a + 24576, &M.wo, c1, k * 2, fb); });
          else if (shb) stages([&](int k, uint32_t a, uint32_t fb) { e_expect_tx(fb, STAGE_BYTES); e_tma_2d_mc(a + 16384 + rank * 8192, m0, c0, k * 64, fb); });
          else stages([&](int k, uint32_t a, uint32_t fb) { e_expect_tx(fb, STAGE_BYTES); e_tma_2d(a + 16384, m0, c0, k * 64, fb); e_tma_2d(a + 24576, m1, c1, k * 64, fb); });
        } else {
          if (ty == T_END) break;
          const int row = l * SEQ + cb * 128, kt = ke + k0 - G_LOOK * dk;
          int rdy = msg >> 16;
          auto need = [&](int k) {
            if (k == kt) e_arrive(sb + B_TRIG);
            while (k >= rdy) { rdy = a_ready(ty, l, cb); trap_if_spent(--budget); }
          };
          if (ty != T_GU) {
            need(0);
            const uint32_t a = sb + p.s * STAGE_BYTES, fb = sb + B_FULL + 8 * p.s;
            const CUtensorMap* const m = ty == T_D ? &M.x1 : l ? &M.x2 : &M.x;
            e_tma_2d(a, m, c0, ty == T_D ? row : cb * 128, fb);
            if (!spl) e_tma_2d(a + 16384, m, c1, row, fb);
            p.next();
          }
          if (shb || spl) {
            const CUtensorMap* const ma = ty == T_O ? &M.o : ty == T_GU ? &M.xms : &M.hs;
            stages([&](int k, uint32_t a, uint32_t fb) { need(k); e_tma_2d(a, ma, k * 64, row, fb); });
          } else {
            const CUtensorMap* const ma = ty == T_GU ? &M.xm : &M.h;
            stages([&](int k, uint32_t a, uint32_t fb) { need(k); e_tma_2d_mc(a + rank * 8192, ma, k * 64, row + rank * 64, fb); });
          }
        }
      }
    } else if (wid == 9 && rank == 0) {
      int k1 = pair < 18 ? 0 : 68;
      bool late = false;
      for (int n = 0, ty = 0; ty != T_END; n++) {
        mbar_wait(sb + B_TRIG, (n & 1) ^ 1, budget);
        int l, cb, j, rdy = 64;
        while (true) {
          const int ph = k1 & 3;
          const bool gap = ph == 3;
          if (k1 < 68) {
            cb = (k1++ >> 2) - (pair < 8 ? ph : 0);
            if ((unsigned)cb >= 16 || (ph == 2 && pair >> 3 != 1) || (gap && (pair < 8 || late || !(G_FILL & (pair >> 3))))) continue;
            if (!gap) {
              l = 0;
              ty = pair < 8 ? (ph ? T_D : T_O) : T_GU;
              j = 2 * (pair < 8 ? pair : pair - 8 + 10 * ph);
              rdy = a_ready(ty, 0, cb);
              if (ph == 0) late = rdy != 0;
              break;
            }
          }
          int d0 = ld_relaxed(g_fl.dep + lane), d1 = ld_relaxed(g_fl.dep + 32 + lane);
          const int t0 = ld_relaxed(g_fl.taken + lane), t1 = ld_relaxed(g_fl.taken + 32 + lane);
          const bool l0 = t0 < (lane < 16 ? 8 : lane & 1 ? 0 : 56), l1 = lane < 16 && t1 < 4;
          const uint32_t rd = __ballot_sync(0xffffffffu, d0 >= 128);
          uint32_t ok0 = __ballot_sync(0xffffffffu, l0) & rd & (rd >> 1 | 0xffff), ok1 = __ballot_sync(0xffffffffu, l1 && h_ready(d1) > 0);
          if (gap) { ok1 = 0; if (pair < 16 && !(G_FILL & 4)) ok0 &= 0xffff0000u; }
          ty = T_END; l = 1; cb = j = 0;
          if (!gap && !__any_sync(0xffffffffu, l0 || l1)) break;
          uint32_t m = ok0 ? ok0 : ok1;
          if (!m && !gap) __nanosleep(100);
          while (m) {
            const int nth = ok0 ? 0 : pair % __popc(m);
            const int b = __ffs(__ballot_sync(0xffffffffu, __popc(m << (31 - lane)) > nth)) - 1, gn = b + (ok0 ? 0 : 32);
            const int t = bcast(e_ticket(g_fl.taken + gn));
            if (t < (gn < 16 ? 8 : gn < 32 ? 56 : 4)) { ty = gn >> 4; cb = gn & 15; j = ty == T_GU ? t : 2 * t; break; }
            m &= ~(1u << b);
          }
          if (ty != T_END) {
            rdy = a_ready(ty, 1, cb);
            if (ty == T_GU) a_ready(ty, 1, cb + 1);
            break;
          }
          trap_if_spent(--budget);
        }
        const int msg = rdy << 16 | ty << 11 | l << 10 | cb << 6 | j;
        e_st_async32(peer + MSG + 4 * (n & 1), msg, peer + B_MSG + 8 * (n & 1));
        e_st_async32(sb + MSG + 4 * (n & 1), msg, sb + B_MSG + 8 * (n & 1));
      }
    } else if (wg == 3) {
      int nb = lane < 16 ? lane : lane < 18 && cta < NEARLY ? 0 : 16;
      while (__any_sync(0xffffffffu, nb < 16)) {
        int v = 0;
        if (lane < 16 && nb < 16 && ld_relaxed(g_fl.taken + 48 + lane) >= 128) nb = 16;
        if (nb < 16) asm volatile("ld.acquire.gpu.global.s32 %0, [%1];" : "=r"(v) : "l"(g_fl.part + max(lane - 15, 0) * 16 + nb) : "memory");
        const uint32_t ok = __ballot_sync(0xffffffffu, v >= 16);
        if (!ok) {
          if (--budget <= 0) break;
          __nanosleep(64);
          continue;
        }
        const int sel = ok >> 16 ? 31 - __clz(ok) : __ffs(__ballot_sync(0xffffffffu, __popc(ok << (31 - lane)) > (cta >> 5) % __popc(ok))) - 1;
        const int st = max(sel - 15, 0), cb = __shfl_sync(0xffffffffu, nb, sel);
        int r = cta * 4 + warp;
        if (st) nb += lane == sel;
        else if ((r = bcast(e_ticket(g_fl.taken + 48 + cb))) >= 128) continue;
        const size_t o = (size_t)(cb * 128 + r) * DM;
        ln_row((st == 2 ? g_x2 : g_x1[st ^ 1]) + o, (st == 2 ? g_xn[1] + LAG * 32 * DM : g_xm[st ^ 1]) + o, lane);
        __syncwarp();
        e_flag_add(st == 2 ? g_fl.xn[1][cb] : g_fl.dep + grp(T_GU, st ^ 1, cb));
      }
      if (cta == 0 && wid == 12) {
        asm volatile("griddepcontrol.wait;" ::: "memory");
        g_fl.xn[lane >> 4][lane & 15][0] = 0;
      }
    }
    cluster_arrive(); cluster_wait();
  } else {
    reg_inc<184>();
    if (cta < NEARLY) {
#pragma unroll 1
      for (int r = 2 * (cta * 8 + wid); r < SEQ; r += 16 * NEARLY) {
        ln_row(x + (size_t)r * DM, g_xn[0] + (size_t)r * DM, lane);
        ln_row(x + (size_t)(r + 1) * DM, g_xn[0] + (size_t)(r + 1) * DM, lane);
        __syncwarp();
        e_flag_add(g_fl.xn[0][r >> 7], 2);
      }
    }
    const bool lead = warp == 0;
    const uint32_t eb = (warp == 1 ? peer : sb) + B_EMPTY;
    const int rl = warp < 2 ? 0 : -1;
    const uint32_t so = sb + SO + wg * 16384;
    const int r0 = warp * 16 + (lane & 7) + ((lane >> 3) & 1) * 8;
    const uint32_t sw = r0 * 128 + (((lane >> 4) ^ (r0 & 7)) << 4);
    int xph = 0;
    for (int n = wg; ; n += 2) {
      float d0[64], d1[64];
      mbar_wait(sb + B_JOB + 8 * wg, (n >> 1) & 1, budget);
      fault_if_spent(budget);
      const int job = __shfl_sync(0xffffffffu, lds32v(sb + JOB + 4 * wg), 0);
      const int ty = (job >> 11) & 3, l = (job >> 10) & 1, cb = (job >> 6) & 15, j = job & 63;
      if (ty == T_END) {
        if (n > 0) nbar_sync_r(1 + wg, 256);
        if (lead && !(job & 1)) { sts32v(sb + JOB + 4 * (wg ^ 1), job | 1); e_arrive(sb + B_JOB + 8 * (wg ^ 1)); }
        if (!(job & 1)) nbar_arrive_r(1 + (wg ^ 1), 256);
        break;
      }
      Pipe q; q.s = (job >> 16) & 15; q.ph = job >> 20;
      const bool spl = ty == T_O || (ty == T_D && !l);
      if (ty != T_GU) mbar_wait(sb + B_FULL + 8 * q.s, q.ph, budget);
#pragma unroll
      for (int hf = 0; hf < 2; hf++) {
        if (ty != T_GU && !(hf && spl)) {
#pragma unroll
          for (int m = 0; m < 2; m++)
#pragma unroll
            for (int c = 0; c < 4; c++) {
              float* d = (m ? d1 : d0) + 32 * hf + 8 * c;
              uint32_t r[4];
              ldsm4(sb + q.s * STAGE_BYTES + hf * 16384 + m * 8192 + (sw ^ (c << 5)), r[0], r[1], r[2], r[3]);
#pragma unroll
              for (int i = 0; i < 4; i++) { d[2*i] = bf_lo(r[i]); d[2*i+1] = bf_hi(r[i]); }
            }
        } else {
#pragma unroll
          for (int i = 0; i < 32; i++) d0[32 * hf + i] = d1[32 * hf + i] = 0.f;
        }
      }
      if (ty != T_GU) {
        fence_proxy_async();
        nbar_sync_r(3 + wg, 128);
        arrive_cl_if_eq(eb + 8 * q.s, lane, rl);
        q.next();
      }
      pin<64>(d0); pin<64>(d1);
      if (n > 0) nbar_sync_r(1 + wg, 256);
      const int nk = ty == T_O ? 32 : ty == T_GU ? 16 : l ? 56 : 28;
      int prev = 0;
      for (int i = 0; i < nk; i++) {
        mbar_wait(sb + B_FULL + 8 * q.s, q.ph, budget);
        const uint32_t da = desc_base(sb) + q.s * (STAGE_BYTES / 16);
        wg_fence();
        sfor<0, 4>([&](auto K) {
          constexpr int k = K;
          typedef Op<16384 + k * 2048, 8192, 1024, 1, 1> OB;
          wg_ss128<1, Op<k * 32, 16, 1024, 1, 0>, OB>(d0, da, da);
          wg_ss128<1, Op<8192 + k * 32, 16, 1024, 1, 0>, OB>(d1, da, da);
        });
        wg_commit();
        wg_wait<1>();
        arrive_cl_if_eq(eb + 8 * prev, lane, i ? rl : -1);
        prev = q.s;
        q.next();
      }
      nbar_arrive_r(1 + (wg ^ 1), 256);
      wg_wait<0>();
      pin<64>(d0); pin<64>(d1);
      arrive_cl_if_eq(eb + 8 * prev, lane, rl);
      if (ty == T_GU) {
#pragma unroll
        for (int i = 0; i < 32; i++) { d0[i] = geglu(d0[i], d0[32 + i]); d1[i] = geglu(d1[i], d1[32 + i]); }
      } else if (spl) {
        const uint32_t xa = SO + wg * 16384 + warp * 512 + lane * 16;
        if (lead) e_expect_tx(sb + B_XF + 8 * wg, 16384);
        mbar_wait(sb + B_SF + 8 * wg, ((n >> 1) & 1) ^ 1, budget);
#pragma unroll
        for (int i = 0; i < 8; i++) {
          const float* d = (i >> 2 ? d1 : d0) + 32 + 8 * (i & 3);
          st_async128(peer + xa + i * 2048, pack_bf16(d[0], d[1]), pack_bf16(d[2], d[3]), pack_bf16(d[4], d[5]), pack_bf16(d[6], d[7]), peer + B_XF + 8 * wg);
        }
        mbar_wait(sb + B_XF + 8 * wg, xph, budget);
        xph ^= 1;
#pragma unroll
        for (int i = 0; i < 8; i++) {
          float* d = (i >> 2 ? d1 : d0) + 8 * (i & 3);
          const uint4 v = lds128(sb + xa + i * 2048);
          d[0] += bf_lo(v.x); d[1] += bf_hi(v.x); d[2] += bf_lo(v.y); d[3] += bf_hi(v.y);
          d[4] += bf_lo(v.z); d[5] += bf_hi(v.z); d[6] += bf_lo(v.w); d[7] += bf_hi(v.w);
        }
        nbar_sync_r(3 + wg, 128);
      }
      const bool two = ty == T_D && l;
      const CUtensorMap* const mo = ty == T_GU ? &M.hs : ty == T_O ? &M.x1 : l ? &M.out : &M.x2;
      const int row = (ty == T_D ? 0 : l * SEQ) + cb * 128;
#pragma unroll
      for (int hf = 0; hf < 2; hf++) {
        if (hf) {
          if (!two) break;
          if (lead) bulk_wait_read<0>();
          nbar_sync_r(3 + wg, 128);
        }
#pragma unroll
        for (int m = 0; m < 2; m++)
#pragma unroll
          for (int c = 0; c < 4; c++) {
            const float* d = (m ? d1 : d0) + 32 * hf + 8 * c;
            stsm4(so + m * 8192 + (sw ^ (c << 5)), pack_bf16(d[0], d[1]), pack_bf16(d[2], d[3]), pack_bf16(d[4], d[5]), pack_bf16(d[6], d[7]));
          }
        fence_proxy_async();
        nbar_sync_r(3 + wg, 128);
        if (lead) { e_tma_store_2d(mo, so, two ? j * 128 + hf * 64 : j * 64, row); bulk_commit(); }
      }
      if (lead) {
        bulk_wait<0>();
        e_arrive_cl(peer + B_SF + 8 * wg);
        if (ty == T_GU) e_flag_add(g_fl.dep + grp(T_D, l, cb), 1 << (j / 20 * 8));
        else if (spl) e_flag_add(g_fl.part + (ty == T_O ? l ^ 1 : 2) * 16 + cb);
      }
    }
    cluster_arrive(); cluster_wait();
  }
}

typedef CUresult (*PFN_encodeTiled)(CUtensorMap*, CUtensorMapDataType, cuuint32_t, void*, const cuuint64_t*, const cuuint64_t*,
                                    const cuuint32_t*, const cuuint32_t*, CUtensorMapInterleave, CUtensorMapSwizzle,
                                    CUtensorMapL2promotion, CUtensorMapFloatOOBfill);
static PFN_encodeTiled g_encode = nullptr;
static int g_sms = 0;
static CUtensorMap encode(const void* ptr, int rank, const cuuint64_t* dims, const cuuint64_t* strides, const cuuint32_t* box) {
  CUtensorMap m;
  const cuuint32_t es[5] = {1, 1, 1, 1, 1};
  g_encode(&m, CU_TENSOR_MAP_DATA_TYPE_BFLOAT16, rank, (void*)ptr, dims, strides, box, es, CU_TENSOR_MAP_INTERLEAVE_NONE,
           CU_TENSOR_MAP_SWIZZLE_128B, CU_TENSOR_MAP_L2_PROMOTION_L2_256B, CU_TENSOR_MAP_FLOAT_OOB_FILL_NONE);
  return m;
}
static CUtensorMap make_map(const void* ptr, uint64_t rows, uint64_t cols, uint32_t box_rows) {
  const cuuint64_t dims[2] = {cols, rows}, strides[1] = {cols * 2};
  const cuuint32_t box[2] = {64, box_rows};
  return encode(ptr, 2, dims, strides, box);
}
static CUtensorMap make_map_x(const void* ptr) {
  const cuuint64_t dims[3] = {DM, NSTEP * 32, 2}, strides[2] = {DM * 2, (cuuint64_t)NSTEP * 32 * DM * 2};
  const cuuint32_t box[3] = {64, 32, 2};
  return encode(ptr, 3, dims, strides, box);
}
static CUtensorMap make_map_x1(const void* ptr) {
  const cuuint64_t dims[3] = {64, 2 * NSTEP * 32, DM / 64}, strides[2] = {DM * 2, 128};
  const cuuint32_t box[3] = {64, 32, 2};
  return encode(ptr, 3, dims, strides, box);
}
static CUtensorMap make_map_wo(const void* ptr) {
  const cuuint64_t dims[5] = {DM, 2, 4, 4, NH * DH / 32}, strides[4] = {DM * 2, 8 * DM * 2, 2 * DM * 2, 32 * DM * 2};
  const cuuint32_t box[5] = {64, 2, 4, 4, 2};
  return encode(ptr, 5, dims, strides, box);
}

extern "C" void kernel_launch(void* const* d_in, const int* in_sizes, int n_in, void* d_out, int out_size) {
  const bf16 *x = (const bf16*)d_in[0], *mem0 = (const bf16*)d_in[1], *Wo = (const bf16*)d_in[5];
  if (!g_encode) {
    void* p = nullptr; cudaDriverEntryPointQueryResult q;
    cudaGetDriverEntryPoint("cuTensorMapEncodeTiled", &p, cudaEnableDefault, &q);
    g_encode = (PFN_encodeTiled)p;
    int dev = 0;
    cudaGetDevice(&dev);
    cudaDeviceGetAttribute(&g_sms, cudaDevAttrMultiProcessorCount, dev);
    cudaFuncSetAttribute(rec_kernel, cudaFuncAttributeMaxDynamicSharedMemorySize, rec::SMEM);
    cudaFuncSetAttribute(gemm_kernel, cudaFuncAttributeMaxDynamicSharedMemorySize, gm::SMEM);
  }
  void *xn, *o, *x1, *xm, *x2, *hh;
  cudaGetSymbolAddress(&xn, g_xn); cudaGetSymbolAddress(&o, g_o); cudaGetSymbolAddress(&x1, g_x1);
  cudaGetSymbolAddress(&xm, g_xm); cudaGetSymbolAddress(&x2, g_x2); cudaGetSymbolAddress(&hh, g_h);
  RecMaps R;
  for (int i = 0; i < 3; i++) R.w[i] = make_map(d_in[2 + i], DM, NH * DH, 16);
  R.wo = make_map(Wo, NH * DH, DM, 64); R.x[0] = make_map_x(xn); R.x[1] = make_map_x1(xn);
  rec_kernel<<<96, 512, rec::SMEM>>>(R, Wo, mem0, 0);
  GemmMaps G;
  G.o = make_map(o, 2 * SEQ, NH * DH, 128); G.wo = make_map_wo(Wo);
  G.x1 = make_map(x1, 2 * SEQ, DM, 128); G.xm = make_map(xm, 2 * SEQ, DM, 64); G.xms = make_map(xm, 2 * SEQ, DM, 128);
  G.wg = make_map(d_in[8], DM, DF, 64); G.wu = make_map(d_in[9], DM, DF, 64); G.wd = make_map(d_in[10], DF, DM, 64);
  G.h = make_map(hh, 2 * SEQ, DF, 64); G.hs = make_map(hh, 2 * SEQ, DF, 128);
  G.x = make_map(x, SEQ, DM, 128); G.x2 = make_map(x2, SEQ, DM, 128); G.out = make_map(d_out, SEQ, DM, 128);
  cudaLaunchConfig_t cfg = {};
  cfg.gridDim = dim3(g_sms & ~1); cfg.blockDim = dim3(512); cfg.dynamicSmemBytes = gm::SMEM; cfg.stream = cudaStreamPerThread;
  cudaLaunchAttribute at;
  at.id = cudaLaunchAttributeProgrammaticStreamSerialization; at.val.programmaticStreamSerializationAllowed = 1;
  cfg.attrs = &at; cfg.numAttrs = 1;
  cudaLaunchKernelEx(&cfg, gemm_kernel, G, x);
}
```

```cpp
#include <cuda_runtime.h>
#include <cuda_bf16.h>
#include <cuda.h>
#include <stdint.h>

#define DEVI __device__ __forceinline__
typedef __nv_bfloat16 bf16;

#define LAG 14
constexpr int SEQ = 2048, DM = 1024, NH = 32, DH = 128, DF = 3584, NSEG = 64, NSTEP = NSEG + LAG;
static_assert(NSTEP % 2 == 0, "tags and slots of the exchange buffers return to their initial state");

__device__ __align__(1024) bf16 g_xn[2][NSTEP * 32 * DM];
__device__ __align__(1024) bf16 g_o[2][SEQ * NH * DH];
__device__ __align__(1024) bf16 g_x1[2][SEQ * DM];
__device__ __align__(1024) bf16 g_xm[2][SEQ * DM];
__device__ __align__(1024) bf16 g_x2[SEQ * DM];
__device__ __align__(1024) bf16 g_h[2][SEQ * DF];
__device__ __align__(1024) uint4 g_part[256 * 32 * 8];
__device__ __align__(1024) uint32_t g_ann[2][32][64];
__device__ __align__(1024) uint4 g_mem[2][2048];
__device__ __align__(128) float2 g_stat[2][2][8][128];
__host__ __device__ constexpr int grp(int type, int layer, int blk) { return layer ? 16 * type + blk : 64 + (16 * type + blk) * 32; }
struct Flags {
  int xn[2][16][32];
  int dep[64 + 48 * 32];
  int taken[64];
  int rows[32];
  int part[32];
  int ticket[32];
};
__device__ __align__(128) Flags g_fl;

DEVI uint32_t smem_u32(const void* p) { return (uint32_t)__cvta_generic_to_shared(p); }
DEVI void mbar_init(uint32_t bar, uint32_t cnt) { asm volatile("mbarrier.init.shared::cta.b64 [%0], %1;" :: "r"(bar), "r"(cnt) : "memory"); }
DEVI void mbar_expect_tx(uint32_t bar, uint32_t bytes) { asm volatile("mbarrier.arrive.expect_tx.shared::cta.b64 _, [%0], %1;" :: "r"(bar), "r"(bytes) : "memory"); }
DEVI void mbar_arrive(uint32_t bar) { asm volatile("mbarrier.arrive.shared::cta.b64 _, [%0];" :: "r"(bar) : "memory"); }
DEVI bool mbar_try(uint32_t bar, uint32_t parity) {
  uint32_t p;
  asm volatile("{.reg .pred p; mbarrier.try_wait.parity.shared::cta.b64 p, [%1], %2; selp.u32 %0, 1, 0, p;}" : "=r"(p) : "r"(bar), "r"(parity) : "memory");
  return p;
}
DEVI bool mbar_test(uint32_t bar, uint32_t parity) {
  uint32_t p;
  asm volatile("{.reg .pred p; mbarrier.test_wait.parity.shared::cta.b64 p, [%1], %2; selp.u32 %0, 1, 0, p;}" : "=r"(p) : "r"(bar), "r"(parity) : "memory");
  return p;
}
constexpr int SPIN_BUDGET = 1 << 20;
DEVI void mbar_wait(uint32_t bar, uint32_t parity, int& budget) {
  while (!mbar_try(bar, parity)) { if (--budget < 0) break; }
}
DEVI void trap_if_spent(int budget) { asm volatile("{.reg .pred p; setp.le.s32 p, %0, 0; @p trap;}" :: "r"(budget) : "memory"); }
DEVI void fault_if_spent(int budget) { asm volatile("{.reg .pred p; setp.le.s32 p, %0, 0; @p st.global.u32 [%1], 0;}" :: "r"(budget), "l"(0ull) : "memory"); }
DEVI uint32_t mapa(uint32_t addr, uint32_t rank) { uint32_t r; asm("mapa.shared::cluster.u32 %0, %1, %2;" : "=r"(r) : "r"(addr), "r"(rank)); return r; }
DEVI void cluster_arrive() { asm volatile("barrier.cluster.arrive.release.aligned;" ::: "memory"); }
DEVI void cluster_wait() { asm volatile("barrier.cluster.wait.acquire.aligned;" ::: "memory"); }
DEVI void fence_mbar_init() { asm volatile("fence.mbarrier_init.release.cluster;" ::: "memory"); }
DEVI void fence_proxy_async() { asm volatile("fence.proxy.async.shared::cta;" ::: "memory"); }
DEVI void tma_load_2d(uint32_t dst, const CUtensorMap* m, int c0, int c1, uint32_t bar) {
  asm volatile("cp.async.bulk.tensor.2d.shared::cluster.global.mbarrier::complete_tx::bytes [%0], [%1, {%3, %4}], [%2];"
    :: "r"(dst), "l"(m), "r"(bar), "r"(c0), "r"(c1) : "memory");
}
DEVI void tma_load_5d(uint32_t dst, const CUtensorMap* m, int c0, int c4, uint32_t bar) {
  asm volatile("cp.async.bulk.tensor.5d.shared::cluster.global.mbarrier::complete_tx::bytes [%0], [%1, {%3, %5, %5, %5, %4}], [%2];"
    :: "r"(dst), "l"(m), "r"(bar), "r"(c0), "r"(c4), "r"(0) : "memory");
}
DEVI void tma_prefetch_2d(const CUtensorMap* m, int c0, int c1) {
  asm volatile("cp.async.bulk.prefetch.tensor.2d.L2.global [%0, {%1, %2}];" :: "l"(m), "r"(c0), "r"(c1) : "memory");
}
DEVI void tma_prefetch_5d(const CUtensorMap* m, int c0, int c4) {
  asm volatile("cp.async.bulk.prefetch.tensor.5d.L2.global [%0, {%1, %3, %3, %3, %2}];" :: "l"(m), "r"(c0), "r"(c4), "r"(0) : "memory");
}
#define ELECT "{.reg .pred p; elect.sync _|p, 0xffffffff;\n @p "
DEVI void e_expect_tx(uint32_t bar, uint32_t bytes) { asm volatile(ELECT "mbarrier.arrive.expect_tx.shared::cta.b64 _, [%0], %1;}" :: "r"(bar), "r"(bytes) : "memory"); }
DEVI void e_arrive(uint32_t bar) { asm volatile(ELECT "mbarrier.arrive.shared::cta.b64 _, [%0];}" :: "r"(bar) : "memory"); }
DEVI void e_arrive_cl(uint32_t bar) { asm volatile(ELECT "mbarrier.arrive.shared::cluster.b64 _, [%0];}" :: "r"(bar) : "memory"); }
DEVI void e_tma_2d(uint32_t dst, const CUtensorMap* m, int c0, int c1, uint32_t bar) {
  asm volatile(ELECT "cp.async.bulk.tensor.2d.shared::cluster.global.mbarrier::complete_tx::bytes [%0], [%1, {%3, %4}], [%2];}"
    :: "r"(dst), "l"(m), "r"(bar), "r"(c0), "r"(c1) : "memory");
}
DEVI void e_tma_2d_mc(uint32_t dst, const CUtensorMap* m, int c0, int c1, uint32_t bar) {
  asm volatile(ELECT "cp.async.bulk.tensor.2d.shared::cluster.global.mbarrier::complete_tx::bytes.multicast::cluster [%0], [%1, {%3, %4}], [%2], %5;}"
    :: "r"(dst), "l"(m), "r"(bar), "r"(c0), "r"(c1), "h"((unsigned short)3) : "memory");
}
DEVI void e_st_async32(uint32_t a, uint32_t x, uint32_t bar) {
  asm volatile(ELECT "st.async.weak.shared::cluster.mbarrier::complete_tx::bytes.b32 [%0], %1, [%2];}" :: "r"(a), "r"(x), "r"(bar) : "memory");
}
DEVI void e_tma_store_2d(const CUtensorMap* m, uint32_t src, int c0, int c1) {
  asm volatile(ELECT "cp.async.bulk.tensor.2d.global.shared::cta.bulk_group [%0, {%2, %3}], [%1];}" :: "l"(m), "r"(src), "r"(c0), "r"(c1) : "memory");
}
DEVI void e_flag_add(int* p, int v = 1) {
  asm volatile("{.reg .pred p; elect.sync _|p, 0xffffffff;\n fence.proxy.async.global; @p red.release.gpu.global.add.s32 [%0], %1;}" :: "l"(p), "r"(v) : "memory");
}
DEVI int e_ticket(int* p) { int v = 0; asm volatile(ELECT "atom.relaxed.gpu.global.add.s32 %0, [%1], 1;}" : "+r"(v) : "l"(p) : "memory"); __syncwarp(); return v; }
DEVI int bcast(int v) { return __reduce_max_sync(0xffffffffu, v); }
DEVI int ld_relaxed(const int* p) { int v; asm volatile("ld.relaxed.gpu.global.s32 %0, [%1];" : "=r"(v) : "l"(p) : "memory"); return v; }
DEVI int ld_acquire(const int* p) { int v; asm volatile("ld.acquire.gpu.global.s32 %0, [%1];" : "=r"(v) : "l"(p) : "memory"); return __shfl_sync(0xffffffffu, v, 0); }
DEVI void e_tma_3d(uint32_t dst, const CUtensorMap* m, int c0, int c1, int c2, uint32_t bar) {
  asm volatile(ELECT "cp.async.bulk.tensor.3d.shared::cluster.global.mbarrier::complete_tx::bytes [%0], [%1, {%3, %4, %5}], [%2];}"
    :: "r"(dst), "l"(m), "r"(bar), "r"(c0), "r"(c1), "r"(c2) : "memory");
}
DEVI void e_tma_5d(uint32_t dst, const CUtensorMap* m, int c0, int c4, uint32_t bar) {
  asm volatile(ELECT "cp.async.bulk.tensor.5d.shared::cluster.global.mbarrier::complete_tx::bytes [%0], [%1, {%3, %5, %5, %5, %4}], [%2];}"
    :: "r"(dst), "l"(m), "r"(bar), "r"(c0), "r"(c4), "r"(0) : "memory");
}
DEVI void e_bulk_g2s(uint32_t dst, const void* src, uint32_t bytes, uint32_t bar) {
  asm volatile(ELECT "cp.async.bulk.shared::cluster.global.mbarrier::complete_tx::bytes [%0], [%1], %2, [%3];}" :: "r"(dst), "l"(src), "r"(bytes), "r"(bar) : "memory");
}
DEVI void e_prefetch(const void* src, uint32_t bytes) {
  asm volatile(ELECT "cp.async.bulk.prefetch.L2.global [%0], %1;}" :: "l"(src), "r"(bytes) : "memory");
}
DEVI void bulk_commit() { asm volatile("cp.async.bulk.commit_group;" ::: "memory"); }
template<int N> DEVI void bulk_wait_read() { asm volatile("cp.async.bulk.wait_group.read %0;" :: "n"(N) : "memory"); }
template<int N> DEVI void bulk_wait() { asm volatile("cp.async.bulk.wait_group %0;" :: "n"(N) : "memory"); }
template<int ID, int N> DEVI void nbar_sync() { asm volatile("bar.sync %0, %1;" :: "n"(ID), "n"(N) : "memory"); }
template<int ID, int N> DEVI void nbar_arrive() { asm volatile("bar.arrive %0, %1;" :: "n"(ID), "n"(N) : "memory"); }
DEVI void nbar_sync_r(int id, int n) { asm volatile("bar.sync %0, %1;" :: "r"(id), "r"(n) : "memory"); }
DEVI void nbar_arrive_r(int id, int n) { asm volatile("bar.arrive %0, %1;" :: "r"(id), "r"(n) : "memory"); }
template<int R> DEVI void reg_inc() { asm volatile("setmaxnreg.inc.sync.aligned.u32 %0;" :: "n"(R)); }
template<int R> DEVI void reg_dec() { asm volatile("setmaxnreg.dec.sync.aligned.u32 %0;" :: "n"(R)); }
DEVI void wg_fence() { asm volatile("wgmma.fence.sync.aligned;" ::: "memory"); }
DEVI void wg_commit() { asm volatile("wgmma.commit_group.sync.aligned;" ::: "memory"); }
template<int N> DEVI void wg_wait() { asm volatile("wgmma.wait_group.sync.aligned %0;" :: "n"(N) : "memory"); }
DEVI uint32_t pack_bf16(float lo, float hi) { uint32_t r; asm("cvt.rn.bf16x2.f32 %0, %1, %2;" : "=r"(r) : "f"(hi), "f"(lo)); return r; }
DEVI float bf_lo(uint32_t v) { return __uint_as_float(v << 16); }
DEVI float bf_hi(uint32_t v) { return __uint_as_float(v & 0xffff0000u); }
DEVI uint32_t movmat(uint32_t a) { uint32_t r; asm volatile("movmatrix.sync.aligned.m8n8.trans.b16 %0, %1;" : "=r"(r) : "r"(a)); return r; }
DEVI void ldsm4(uint32_t addr, uint32_t& r0, uint32_t& r1, uint32_t& r2, uint32_t& r3) {
  asm volatile("ldmatrix.sync.aligned.m8n8.x4.shared.b16 {%0,%1,%2,%3}, [%4];" : "=r"(r0), "=r"(r1), "=r"(r2), "=r"(r3) : "r"(addr) : "memory");
}
DEVI void ldsm4t(uint32_t addr, uint32_t& r0, uint32_t& r1, uint32_t& r2, uint32_t& r3) {
  asm volatile("ldmatrix.sync.aligned.m8n8.x4.trans.shared.b16 {%0,%1,%2,%3}, [%4];" : "=r"(r0), "=r"(r1), "=r"(r2), "=r"(r3) : "r"(addr) : "memory");
}
DEVI void stsm4(uint32_t addr, uint32_t r0, uint32_t r1, uint32_t r2, uint32_t r3) {
  asm volatile("stmatrix.sync.aligned.m8n8.x4.shared.b16 [%0], {%1,%2,%3,%4};" :: "r"(addr), "r"(r0), "r"(r1), "r"(r2), "r"(r3) : "memory");
}
DEVI uint4 lds128(uint32_t a) { uint4 v; asm volatile("ld.shared.v4.u32 {%0,%1,%2,%3}, [%4];" : "=r"(v.x), "=r"(v.y), "=r"(v.z), "=r"(v.w) : "r"(a) : "memory"); return v; }
DEVI uint32_t lds32v(uint32_t a) { uint32_t v; asm volatile("ld.volatile.shared.u32 %0, [%1];" : "=r"(v) : "r"(a) : "memory"); return v; }
DEVI void sts32v(uint32_t a, uint32_t v) { asm volatile("st.volatile.shared.u32 [%0], %1;" :: "r"(a), "r"(v) : "memory"); }
DEVI void st_async128(uint32_t a, uint32_t x, uint32_t y, uint32_t z, uint32_t w, uint32_t bar) {
  asm volatile("st.async.weak.shared::cluster.mbarrier::complete_tx::bytes.v4.b32 [%0], {%1,%2,%3,%4}, [%5];" :: "r"(a), "r"(x), "r"(y), "r"(z), "r"(w), "r"(bar) : "memory");
}
DEVI void st_async32(uint32_t a, uint32_t x, uint32_t bar) {
  asm volatile("st.async.weak.shared::cluster.mbarrier::complete_tx::bytes.b32 [%0], %1, [%2];" :: "r"(a), "r"(x), "r"(bar) : "memory");
}
DEVI void st_cl128(bool own, uint32_t a, uint32_t x, uint32_t y, uint32_t z, uint32_t w, uint32_t bar) {
  asm volatile("{.reg .pred p; setp.ne.u32 p, %6, 0; @p st.shared.v4.b32 [%0], {%1,%2,%3,%4};\n"
               "@!p st.async.weak.shared::cluster.mbarrier::complete_tx::bytes.v4.b32 [%0], {%1,%2,%3,%4}, [%5];}"
               :: "r"(a), "r"(x), "r"(y), "r"(z), "r"(w), "r"(bar), "r"((uint32_t)own) : "memory");
}
DEVI void st_cl32(bool own, uint32_t a, uint32_t x, uint32_t bar) {
  asm volatile("{.reg .pred p; setp.ne.u32 p, %3, 0; @p st.shared.b32 [%0], %1;\n"
               "@!p st.async.weak.shared::cluster.mbarrier::complete_tx::bytes.b32 [%0], %1, [%2];}" :: "r"(a), "r"(x), "r"(bar), "r"((uint32_t)own) : "memory");
}
DEVI uint4 ldg_rlx128(const void* p) {
  uint4 v;
  asm volatile("ld.relaxed.gpu.global.v4.b32 {%0,%1,%2,%3}, [%4];" : "=r"(v.x), "=r"(v.y), "=r"(v.z), "=r"(v.w) : "l"(p) : "memory");
  return v;
}
DEVI void stg_rlx128(void* p, uint32_t x, uint32_t y, uint32_t z, uint32_t w) {
  asm volatile("st.relaxed.gpu.global.v4.b32 [%0], {%1,%2,%3,%4};" :: "l"(p), "r"(x), "r"(y), "r"(z), "r"(w) : "memory");
}
DEVI void stg128(void* p, uint32_t x, uint32_t y, uint32_t z, uint32_t w) {
  asm volatile("st.global.v4.b32 [%0], {%1,%2,%3,%4};" :: "l"(p), "r"(x), "r"(y), "r"(z), "r"(w) : "memory");
}
DEVI void stg_rlx64(void* p, uint32_t x, uint32_t y) { asm volatile("st.relaxed.gpu.global.v2.b32 [%0], {%1,%2};" :: "l"(p), "r"(x), "r"(y) : "memory"); }
DEVI void stg_rlx32(void* p, uint32_t x) { asm volatile("st.relaxed.gpu.global.b32 [%0], %1;" :: "l"(p), "r"(x) : "memory"); }
DEVI uint32_t clock32() { uint32_t c; asm volatile("mov.u32 %0, %%clock;" : "=r"(c) :: "memory"); return c; }
DEVI uint32_t gtime() { uint32_t c; asm volatile("mov.u32 %0, %%globaltimer_lo;" : "=r"(c) :: "memory"); return c; }
DEVI void wait_time(uint32_t t, int& budget) { while ((int)(gtime() - t) < 0 && --budget > 0) {} }
DEVI uint2 ldg_rlx64(const void* p) { uint2 v; asm volatile("ld.relaxed.gpu.global.v2.b32 {%0,%1}, [%2];" : "=r"(v.x), "=r"(v.y) : "l"(p) : "memory"); return v; }
DEVI void sts16(uint32_t a, uint32_t x) { asm volatile("st.shared.b16 [%0], %1;" :: "r"(a), "h"((unsigned short)x) : "memory"); }
DEVI void sts128(uint32_t a, uint32_t x) { asm volatile("st.shared.v4.b32 [%0], {%1,%1,%1,%1};" :: "r"(a), "r"(x) : "memory"); }
DEVI void arrive_if_eq(uint32_t bar, int a, int b) { asm volatile("{.reg .pred p; setp.eq.s32 p, %1, %2; @p mbarrier.arrive.shared::cta.b64 _, [%0];}" :: "r"(bar), "r"(a), "r"(b) : "memory"); }
DEVI void arrive_cl_if_eq(uint32_t bar, int a, int b) { asm volatile("{.reg .pred p; setp.eq.s32 p, %1, %2; @p mbarrier.arrive.shared::cluster.b64 _, [%0];}" :: "r"(bar), "r"(a), "r"(b) : "memory"); }
template<int ID, int N> DEVI bool nbar_or(bool x) {
  uint32_t r;
  asm volatile("{.reg .pred p, q; setp.ne.u32 p, %1, 0; bar.red.or.pred q, %2, %3, p; selp.u32 %0, 1, 0, q;}" : "=r"(r) : "r"((uint32_t)x), "n"(ID), "n"(N) : "memory");
  return __any_sync(0xffffffffu, r);
}
DEVI void spin_until(uint32_t t0, int d) { while ((int)(clock32() - t0) < d) {} }
DEVI void flag_wait(const int* p, int n, int& budget) {
  while (ld_acquire(p) < n && --budget > 0) __nanosleep(32);
  asm volatile("fence.proxy.async.global;" ::: "memory");
}

#define F4(C, o)  C(d[o+0]), C(d[o+1]), C(d[o+2]), C(d[o+3])
#define F8(C, o)  F4(C, o), F4(C, o+4)
#define F32(C, o) F8(C, o), F8(C, o+8), F8(C, o+16), F8(C, o+24)
#define R4  "{%0,%1,%2,%3}"
#define R8  "{%0,%1,%2,%3,%4,%5,%6,%7}"
#define R16 "{%0,%1,%2,%3,%4,%5,%6,%7,%8,%9,%10,%11,%12,%13,%14,%15}"
#define R20 "{%0,%1,%2,%3,%4,%5,%6,%7,%8,%9,%10,%11,%12,%13,%14,%15,%16,%17,%18,%19}"
#define R32 "{%0,%1,%2,%3,%4,%5,%6,%7,%8,%9,%10,%11,%12,%13,%14,%15,%16,%17,%18,%19,%20,%21,%22,%23,%24,%25,%26,%27,%28,%29,%30,%31}"
#define R64 "{%0,%1,%2,%3,%4,%5,%6,%7,%8,%9,%10,%11,%12,%13,%14,%15,%16,%17,%18,%19,%20,%21,%22,%23,%24,%25,%26,%27,%28,%29,%30,%31," \
  "%32,%33,%34,%35,%36,%37,%38,%39,%40,%41,%42,%43,%44,%45,%46,%47,%48,%49,%50,%51,%52,%53,%54,%55,%56,%57,%58,%59,%60,%61,%62,%63}"
template<uint32_t OFF, uint32_t LBO, uint32_t SBO, uint32_t SW, int T> struct Op {
  static constexpr uint32_t lo = (OFF >> 4) | ((LBO >> 4) << 16), hi = (SBO >> 4) | (SW << 30);
  static constexpr int t = T;
};
DEVI uint32_t desc_base(uint32_t addr) { return (addr & 0x3FFFF) >> 4; }
#define RS_ASM(SHAPE, REGS, A0, A1, A2, A3, B, LO, HI, T, SD) \
  "{.reg .b64 tb; .reg .b32 lb; add.u32 lb, " B ", " LO "; mov.b64 tb, {lb, " HI "};\n" \
  "wgmma.mma_async.sync.aligned." SHAPE ".f32.bf16.bf16 " REGS ", {" A0 "," A1 "," A2 "," A3 "}, tb, " SD ", 1, 1, " T ";}"
#define WG_RS(NAME, SHAPE, REGS, LIST, ...) \
  template<int ACC, class OB> DEVI void NAME(float* d, const uint32_t* a, uint32_t b) { \
    if (ACC) asm volatile(RS_ASM(SHAPE, REGS, __VA_ARGS__) \
      : LIST("+f") : "r"(a[0]), "r"(a[1]), "r"(a[2]), "r"(a[3]), "r"(b), "n"(OB::lo), "n"(OB::hi), "n"(OB::t), "n"(ACC & 1)); \
    else asm volatile(RS_ASM(SHAPE, REGS, __VA_ARGS__) \
      : LIST("=f") : "r"(a[0]), "r"(a[1]), "r"(a[2]), "r"(a[3]), "r"(b), "n"(OB::lo), "n"(OB::hi), "n"(OB::t), "n"(0)); \
  }
#define SS_ASM(SHAPE, REGS, A, B, LA, HA, TA, LB, HB, TB, SD) \
  "{.reg .b64 ta, tb; .reg .b32 la, lb; add.u32 la, " A ", " LA "; mov.b64 ta, {la, " HA "}; add.u32 lb, " B ", " LB "; mov.b64 tb, {lb, " HB "};\n" \
  "wgmma.mma_async.sync.aligned." SHAPE ".f32.bf16.bf16 " REGS ", ta, tb, " SD ", 1, 1, " TA ", " TB ";}"
#define WG_SS(NAME, SHAPE, REGS, LIST, ...) \
  template<int ACC, class OA, class OB> DEVI void NAME(float* d, uint32_t a, uint32_t b) { \
    if (ACC) asm volatile(SS_ASM(SHAPE, REGS, __VA_ARGS__) \
      : LIST("+f") : "r"(a), "r"(b), "n"(OA::lo), "n"(OA::hi), "n"(OA::t), "n"(OB::lo), "n"(OB::hi), "n"(OB::t), "n"(ACC & 1)); \
    else asm volatile(SS_ASM(SHAPE, REGS, __VA_ARGS__) \
      : LIST("=f") : "r"(a), "r"(b), "n"(OA::lo), "n"(OA::hi), "n"(OA::t), "n"(OB::lo), "n"(OB::hi), "n"(OB::t), "n"(0)); \
  }
#define L4(C)  F4(C, 0)
#define L8(C)  F8(C, 0)
#define L16(C) F8(C, 0), F8(C, 8)
#define L20(C) F8(C, 0), F8(C, 8), F4(C, 16)
#define L32(C) F32(C, 0)
WG_RS(wg_rs8, "m64n8k16", R4, L4, "%4", "%5", "%6", "%7", "%8", "%9", "%10", "%11", "%12")
WG_RS(wg_rs16, "m64n16k16", R8, L8, "%8", "%9", "%10", "%11", "%12", "%13", "%14", "%15", "%16")
WG_RS(wg_rs32, "m64n32k16", R16, L16, "%16", "%17", "%18", "%19", "%20", "%21", "%22", "%23", "%24")
WG_SS(wg_ss32, "m64n32k16", R16, L16, "%16", "%17", "%18", "%19", "%20", "%21", "%22", "%23", "%24")
WG_RS(wg_rs64, "m64n64k16", R32, L32, "%32", "%33", "%34", "%35", "%36", "%37", "%38", "%39", "%40")
WG_SS(wg_ss8, "m64n8k16", R4, L4, "%4", "%5", "%6", "%7", "%8", "%9", "%10", "%11", "%12")
WG_SS(wg_ss16, "m64n16k16", R8, L8, "%8", "%9", "%10", "%11", "%12", "%13", "%14", "%15", "%16")
WG_SS(wg_ss40, "m64n40k16", R20, L20, "%20", "%21", "%22", "%23", "%24", "%25", "%26", "%27", "%28")
WG_SS(wg_ss64, "m64n64k16", R32, L32, "%32", "%33", "%34", "%35", "%36", "%37", "%38", "%39", "%40")
#define L64(C) F32(C, 0), F32(C, 32)
WG_SS(wg_ss128, "m64n128k16", R64, L64, "%64", "%65", "%66", "%67", "%68", "%69", "%70", "%71", "%72")
template<int I> struct IC { __host__ __device__ constexpr operator int() const { return I; } };
template<int I, int N, class F> DEVI void sfor(F&& f) {
  if constexpr (I < N) { f(IC<I>{}); sfor<I + 1, N>(f); }
}

#define R_CL 6
namespace rec {
constexpr int NHI = 36, NLO = 5, NRS = NHI + NLO, NSS = 64 - NRS;
constexpr uint32_t WS = 0;
constexpr uint32_t WO = 2 * NSS * 2048;
constexpr uint32_t RING = WO + 65536;
constexpr uint32_t QB = RING + 40960, RG = 2080, POSQ = 0x64210, POSK = 0xB9753, POSV = 0xEDCA8;
#define JA 2
constexpr uint32_t WA = QB;
constexpr uint32_t OM = QB + 9 * RG, OMS = 2 * RG;
constexpr uint32_t OM2 = QB + 16384, OM2S = 2048;
constexpr uint32_t WH = QB + 20480;
constexpr uint32_t B_PART = QB + 15 * RG - 32;
constexpr uint32_t PM0 = QB + 16384, PM1 = QB + 15 * RG, PM2 = PM1 + 256;
constexpr uint32_t BARS = PM2 + 128;
constexpr uint32_t B_FULL = BARS, B_EMPTY = BARS + 40, B_MLAND = BARS + 80, B_QK = BARS + 112, B_V = BARS + 120, B_OM = BARS + 128,
                   B_WA = BARS + 136, B_SDONE = BARS + 144, B_BFREE = BARS + 152, B_W1 = PM1, B_W2 = PM1 + 8, B_WO = PM1 + 16;
constexpr uint32_t SMEM = BARS + 160;
static_assert(SMEM <= 232448 && QB % 1024 == 0, "smem map");
constexpr int R1 = (PM1 - WO) / 4096;
constexpr int NB_WO = 1, NB_ST = 2, NB_P = 3, NB_TR = 4, NB_X = 5, NB_G = 6, NB_G1 = 7, NB_G2 = 8, NB_G4 = 9, NB_S = 10;
__host__ __device__ constexpr bool is_lo(int j) { return j % 12 == 8; }
__host__ __device__ constexpr int lo_before(int j) { return (j + 3) / 12; }
__host__ __device__ constexpr int ss_before(int j) { return (j - lo_before(j)) * NSS / (64 - NLO); }
__host__ __device__ constexpr bool is_ss(int j) { return ss_before(j + 1) != ss_before(j); }
__host__ __device__ constexpr int reg_idx(int j) { return is_lo(j) ? NHI + lo_before(j) : j - ss_before(j) - lo_before(j); }
#define LOQ(i) ((0x12010 >> (4 * (i))) & 3)
template<int j> using OpW = Op<WS + ss_before(j) * 2048, 16, 1024, 1, 1>;
#define P_G1 1
#define P_G2 3
#define P_G2L 0
#define P_OS 1
#define P_NA 6
#define P_G4 10
#define P_G5 12
#define P_FW 0
#define P_SEND 0xff3f2f10u
#define P_WB 2
#define P_WOL 0
#define P_G4L 0
#define P_S1 1
#define P_S2 2
#define P_S0 3
#define P_MB 0
#define P_S4 5
#define P_S5 6
constexpr uint32_t SLOT1 = 0x32410324, USE1 = 0x22111110;
DEVI bool single(int s) { return s < LAG - 1 || s >= NSEG - 1; }
#define TUN(i, v) (v)
}
#define PROFW(wq, i)
DEVI uint32_t mapr(int h, uint32_t addr, int rank) { return mapa(addr, rank + (R_CL == 6 ? (h & 1) * 3 : 0)); }
template<int N> DEVI void pin(float* d) {
#pragma unroll
  for (int i = 0; i < N; i++) asm volatile("" : "+f"(d[i]) :: "memory");
}
DEVI void keep(const void* a) { asm volatile("{.reg .pred p; setp.eq.u64 p, %0, 0; vote.sync.any.pred p, p, 0xffffffff; @p exit;}" :: "l"(a) : "memory"); }
DEVI int lane_reg() { return __shfl_sync(0xffffffffu, threadIdx.x & 31, threadIdx.x & 31); }
#define LANE_NOW [[maybe_unused]] const int lane = lane0 + ((uint32_t)budget >> 30), g = lane >> 2, c = lane & 3

DEVI void rec_proj(const uint32_t sb, const int h, const int rank, const int w, const CUtensorMap* mW, const CUtensorMap* mWo, const uint32_t zero) {
  using namespace rec;
  const int lane0 = lane_reg(), wg = w >> 2, ww = w & 3;
  int budget = SPIN_BUDGET;
  uint32_t wr[NRS * 4];
  {
    LANE_NOW;
    const uint32_t wsw = ((lane & 7) + (lane >> 4) * 8) * 128 + (((ww * 2 + ((lane >> 3) & 1)) ^ (lane & 7)) << 4);
    mbar_wait(sb + B_W1, 0, budget);
#pragma unroll
    for (int r = 0; r < R1; r++) ldsm4t(sb + WO + (wg * R1 + r) * 2048 + wsw, wr[4*r], wr[4*r+1], wr[4*r+2], wr[4*r+3]);
    fence_proxy_async();
    nbar_sync<NB_ST, 256>();
    if (w == 0) {
      if (lane == 0) { mbar_expect_tx(sb + B_W2, (NRS - R1) * 4096); mbar_expect_tx(sb + B_WO, rank == 2 ? 65536 + 16384 + 8192 : 65536); }
      __syncwarp();
      for (int i = lane; i < 128; i += 32) {
        const int j = i & 63, t = i >> 6, r = reg_idx(j);
        if (!is_ss(j) && r >= R1) tma_load_2d(sb + RING + (t * (NRS - R1) + r - R1) * 2048, mW, h * DH + t * 64, j * 16, sb + B_W2);
      }
      const int t0 = (rank + 1) % 3;
      if (lane < 8) tma_load_2d(sb + WO + lane * 8192, mWo, (3 * ((lane >> 1) + (lane >> 1 >= JA)) + t0) * 64, h * DH + (lane & 1) * 64, sb + B_WO);
      else if (rank == 2 && lane < 11) tma_load_2d(lane < 10 ? sb + WA + (lane - 8) * 8192 : sb + WH, mWo, lane < 10 ? 3 * JA * 64 : 15 * 64, h * DH + (lane > 8) * 64, sb + B_WO);
    }
    mbar_wait(sb + B_W2, 0, budget);
#pragma unroll
    for (int r = R1; r < NRS; r++) ldsm4t(sb + RING + (wg * (NRS - R1) + r - R1) * 2048 + wsw, wr[4*r], wr[4*r+1], wr[4*r+2], wr[4*r+3]);
    fence_proxy_async();
    cluster_arrive(); cluster_wait();
  }
  const uint32_t d0 = desc_base(sb), da = d0 + wg * (NSS * 128);
  const uint32_t pos = rank == 0 ? POSQ : rank == 1 ? POSK : POSV, bar = rank == 2 ? B_V : B_QK;
  uint32_t stg[3][4] = {}, pk[16] = {};
  auto stage = [&](uint32_t* t, int r) {
#pragma unroll
    for (int i = 0; i < 4; i++) asm volatile("xor.b32 %0, %1, %2;" : "+r"(t[i]) : "r"(wr[4 * r + i]), "r"(zero));
  };
#pragma unroll 1
  for (int s = -1; s < NSTEP; s++) {
    const uint32_t fl = single(s) ? (s + 1) & 1 : 0;
    if (s >= 0) {
      float d[8];
      stage(stg[0], NHI);
      mbar_wait(sb + B_FULL, 0, budget);
      PROFW(0, 16);
      sfor<0, 8>([&](auto E) {
        constexpr int e = E, q = e >> 1;
        wg_fence();
        sfor<8 * e, 8 * e + 8>([&](auto J) {
          constexpr int j = J;
          typedef Op<RING + j * 512, 256, 128, 0, 1> OB;
          if constexpr (is_ss(j)) wg_ss16<j != 0, OpW<j>, OB>(d, da, d0);
          else wg_rs16<j != 0, OB>(d, is_lo(j) ? stg[LOQ(lo_before(j))] : wr + 4 * reg_idx(j), d0);
        });
        wg_commit();
        if constexpr (e == 0) { if (s > 0) mbar_wait(sb + B_BFREE, (s & 1) ^ 1, budget); }
        if constexpr (e > 0 && !(e & 1)) {
          wg_wait<1>();
          arrive_if_eq(sb + B_EMPTY + 8 * (q - 1), lane0, ww * 32);
        }
        if constexpr (e < 6 && !(e & 1)) sfor<lo_before(16 * q + 16), lo_before(16 * q + 32)>([&](auto I) { constexpr int i = I; stage(stg[LOQ(i)], NHI + i); });
        if constexpr (e < 6 && (e & 1) == P_FW) mbar_wait(sb + B_FULL + 8 * (q + 1), q ? fl : 0, budget);
        if constexpr (((P_SEND >> (4 * e)) & 15) < 4) {
          constexpr int n = (P_SEND >> (4 * e)) & 15;
          LANE_NOW;
          const uint32_t r = mapr(h, sb, n >> 1);
          uint32_t t[4];
#pragma unroll
          for (int i = 0; i < 4; i++) { if (n == 0) t[i] = pk[i]; else asm volatile("xor.b32 %0, %1, %2;" : "=r"(t[i]) : "r"(pk[4*n+i]), "r"(zero)); }
          st_cl128(rank == n >> 1, r + QB + ((pos >> (4 + 4 * c)) & 15) * RG + w * 256 + (n & 1) * 128 + g * 16, t[0], t[1], t[2], t[3], r + bar);
        }
      });
      LANE_NOW;
      const uint32_t dst = QB + (pos & 15) * RG + w * 256 + lane * 4;
      wg_wait<0>();
      pin<8>(d);
      {
        const uint32_t x0 = pack_bf16(d[0], d[1]), x1 = pack_bf16(d[2], d[3]), y0 = pack_bf16(d[4], d[5]), y1 = pack_bf16(d[6], d[7]);
        const uint32_t r = mapr(h, sb, rank == 0);
        if (rank < 2) { sts32v(sb + dst, rank ? y0 : x0); sts32v(sb + dst + 128, rank ? y1 : x1); fence_proxy_async(); }
        st_async32(r + dst, rank ? x0 : y0, r + bar); st_async32(r + dst + 128, rank ? x1 : y1, r + bar);
        if (rank < 2) e_arrive(sb + B_QK);
        else { const uint32_t r1 = mapr(h, sb, 1); st_async32(r1 + dst, y0, r1 + bar); st_async32(r1 + dst + 128, y1, r1 + bar); }
      }
      PROFW(0, 17);
      if (s == NSTEP - 1) break;
      arrive_if_eq(sb + B_EMPTY + 24, lane0, ww * 32);
    } else e_arrive(sb + B_EMPTY + 8 * ww);
    const bool gate = rank < 2 && s >= 0;
    if (single(s)) {
      float d[16];
      sfor<0, 8>([&](auto C) {
        constexpr int cc = C, sl = (SLOT1 >> (4 * cc)) & 15;
        if constexpr (cc == 0) mbar_wait(sb + B_FULL + 8 * sl, 0, budget);
        if constexpr (cc == P_S1) { if (gate) nbar_sync<NB_G1, 384>(); }
        if constexpr (cc == P_S2) { if (gate) nbar_sync<NB_G2, 384>(); }
        if constexpr (cc == P_S0) nbar_sync<NB_WO, 384>();
        if constexpr (cc == P_S4 || cc == P_S5) { if (gate && cc == (rank ? P_S5 : P_S4)) nbar_sync<NB_G4, 384>(); }
        if constexpr (lo_before(cc * 8 + 8) != lo_before(cc * 8)) stage(stg[0], NHI + lo_before(cc * 8));
        wg_fence();
        sfor<0, 8>([&](auto I) {
          constexpr int i = I, j = cc * 8 + i;
          typedef Op<RING + sl * 8192 + (i >> 2) * 4096 + (i & 3) * 32, 16, 1024, 1, 0> OB;
          if constexpr (is_ss(j)) wg_ss32<j != 0, OpW<j>, OB>(d, da, d0);
          else wg_rs32<j != 0, OB>(d, is_lo(j) ? stg[0] : wr + 4 * reg_idx(j), d0);
        });
        wg_commit();
        if constexpr (cc < 7) {
          constexpr int sn = (SLOT1 >> (4 * cc + 4)) & 15;
          mbar_wait(sb + B_FULL + 8 * sn, ((USE1 >> (4 * cc + 4)) & 1) ^ (sn >> 1 == 1 ? fl : 0), budget);
        }
        wg_wait<0>();
        arrive_if_eq(sb + B_EMPTY + 8 * sl, lane0, ww * 32);
      });
      pin<16>(d);
      PROFW(0, 20);
#pragma unroll
      for (int i = 0; i < 8; i++) pk[i] = pk[8 + i] = pack_bf16(d[4 * (i & 3) + ((i >> 1) & 2)], d[4 * (i & 3) + ((i >> 1) & 2) + 1]);
      continue;
    }
    float d[32];
    sfor<0, 16>([&](auto C) {
      constexpr int cc = C, sl = (cc + 4) % 5;
      if constexpr (cc == 0) mbar_wait(sb + B_FULL + 8 * sl, 0, budget);
      if constexpr (cc == P_G1) { if (gate) nbar_sync<NB_G1, 384>(); }
      if constexpr (cc == P_G2) { if (gate) nbar_sync<NB_G2, 384>(); }
      if constexpr (cc == P_NA) {
        PROFW(0, 18);
        nbar_sync<NB_WO, 384>();
      }
      if constexpr (cc == P_G4 || cc == P_G5) { if (gate && cc == (rank ? P_G5 : P_G4)) nbar_sync<NB_G4, 384>(); }
      wg_fence();
      sfor<0, 4>([&](auto I) {
        constexpr int i = I, j = cc * 4 + i;
        typedef Op<RING + sl * 8192 + i * 32, 16, 1024, 1, 0> OB;
        if constexpr (is_ss(j)) wg_ss64<j != 0, OpW<j>, OB>(d, da, d0);
        else wg_rs64<j != 0, OB>(d, is_lo(j) ? stg[0] : wr + 4 * reg_idx(j), d0);
      });
      wg_commit();
      if constexpr (cc == P_NA) PROFW(0, 19);
      if constexpr (cc < 15) {
        if constexpr (is_lo(cc * 4 + 4)) stage(stg[0], reg_idx(cc * 4 + 4));
        mbar_wait(sb + B_FULL + 8 * ((sl + 1) % 5), ((cc + 5) / 5) & 1, budget);
      }
      wg_wait<0>();
      arrive_if_eq(sb + B_EMPTY + 8 * sl, lane0, ww * 32);
    });
    pin<32>(d);
    PROFW(0, 20);
#pragma unroll
    for (int i = 0; i < 16; i++) pk[i] = pack_bf16(d[16 * (i >> 3) + 4 * (i & 3) + ((i >> 1) & 2)], d[16 * (i >> 3) + 4 * (i & 3) + ((i >> 1) & 2) + 1]);
  }
}

DEVI float softmax_row(float* v, uint32_t* p) {
  constexpr float SC = 0.08838834764831845f * 1.4426950408889634f;
  float m = fmaxf(fmaxf(fmaxf(fmaxf(v[0], v[1]), fmaxf(v[2], v[3])), fmaxf(fmaxf(v[4], v[5]), fmaxf(v[6], v[7]))), fmaxf(v[8], v[9]));
  m = fmaxf(m, __shfl_xor_sync(0xffffffffu, m, 1));
  m = fmaxf(m, __shfl_xor_sync(0xffffffffu, m, 2));
  const float ms = -m * SC, mh = fmaf(m, -SC, -1.f);
#pragma unroll
  for (int i = 0; i < 10; i++) asm("ex2.approx.ftz.f32 %0, %1;" : "=f"(v[i]) : "f"(fmaf(v[i], SC, i < 8 ? ms : mh)));
#pragma unroll
  for (int n = 0; n < 5; n++) p[n] = pack_bf16(v[2*n], v[2*n+1]);
  return fmaf(v[8] + v[9], 2.f, ((v[0] + v[1]) + (v[2] + v[3])) + ((v[4] + v[5]) + (v[6] + v[7])));
}

template<bool ATT>
DEVI void rec_attn(const uint32_t sb, int h, int rank, int w, const bf16* __restrict__ Wo, const bf16* __restrict__ mem0) {
  using namespace rec;
  const int lane0 = lane_reg();
  int budget = SPIN_BUDGET;
  constexpr int NT = ATT ? 5 : 6;
  uint32_t wl[16];
  if (!ATT) {
    LANE_NOW;
#pragma unroll
    for (int i = 0; i < 16; i++) {
      const int dh = 8 * (i >> 1) + 2 * c;
      const unsigned short* p = (const unsigned short*)Wo + (size_t)(h * DH + dh) * DM + 15 * 64 + 16 * w + 8 * (i & 1) + g;
      wl[i] = p[0] | (uint32_t)p[DM] << 16;
    }
  }
  mbar_wait(sb + B_WO, 0, budget);
  cluster_arrive(); cluster_wait();
  const uint32_t d0 = desc_base(sb);
  uint32_t pph = 0;
#pragma unroll 1
  for (int s = -1; s < NSTEP; s++) {
    asm volatile("" : "+r"(h), "+r"(rank), "+r"(w));
    const uint32_t sp = s & 1;
    const int t0 = ATT ? rank + 1 : 0;
    const bool more = s + 1 < NSTEP;
    float hold[10] = {0, 0, 0, 0, 0, 0, 0, 0, 0, 0};
    if (ATT && s >= 0) {
      float sc[20];
      LANE_NOW;
      mbar_wait(sb + B_QK, sp, budget);
      PROFW(0, 1);
      fence_proxy_async();
      wg_fence();
      sfor<0, 8>([&](auto K) { constexpr int k = K; wg_ss40<k != 0, Op<QB + k * 256, 128, RG, 0, 1>, Op<QB + 3 * RG + k * 256, 128, 2 * RG, 0, 1>>(sc, d0, d0); });
      wg_commit();
      if (P_G1 < 16 && more) nbar_arrive<NB_G1, 384>();
      mbar_wait(sb + B_V, sp, budget);
      wg_wait<0>();
      pin<20>(sc);
      if (w == 3 && more) nbar_arrive<NB_S, 64>();
      PROFW(1, 2);
      if (w == 0) {
        uint32_t p[5];
        float v[10];
#pragma unroll
        for (int i = 0; i < 10; i++) v[i] = sc[4 * (i >> 1) + (i & 1)];
        softmax_row(v, p);
        const uint32_t a = sb + lane * 4;
        sts32v(a + PM0, p[0]); sts32v(a + PM0 + 128, p[1]); sts32v(a + PM1, p[2]); sts32v(a + PM1 + 128, p[3]); sts32v(a + PM2, p[4]);
      }
      if (more) {
        float rs[4], ot[2][4];
        uint32_t one[4];
#pragma unroll
        for (int i = 0; i < 4; i++) one[i] = 0x3F803F80u + ((uint32_t)budget >> (31 - i));
        typedef Op<PM0, 128, 128, 0, 0> P0; typedef Op<PM1, 128, 128, 0, 0> P1; typedef Op<PM2, 0, 128, 0, 0> P2;
        fence_proxy_async();
        nbar_sync<NB_P, 128>();
        PROFW(0, 3);
        wg_fence();
        wg_rs8<0, P0>(rs, one, d0); wg_rs8<1, P1>(rs, one, d0); wg_rs8<1, P2>(rs, one, d0);
        wg_commit();
        sfor<0, 2>([&](auto T) {
          constexpr int t = T;
          wg_ss8<0, Op<QB + 8 * RG + t * 1024, 2 * RG, 128, 0, 0>, P0>(ot[t], d0, d0);
          wg_ss8<1, Op<QB + 12 * RG + t * 1024, RG, 128, 0, 0>, P1>(ot[t], d0, d0);
          wg_ss8<1, Op<QB + 14 * RG + t * 1024, 0, 128, 0, 0>, P2>(ot[t], d0, d0);
        });
        wg_commit();
        if (P_G2 < 16 && !P_G2L) nbar_arrive<NB_G2, 384>();
        const uint32_t oa = w * 256 + lane * 4, r1 = mapr(h, sb, rank ^ 1), r2 = mapr(h, sb, 2);
        mbar_wait(sb + B_SDONE, sp, budget);
        wg_wait<1>();
        pin<4>(rs);
        float i0, i1;
        asm volatile("rcp.approx.ftz.f32 %0, %1;" : "=f"(i0) : "f"(rs[0]));
        asm volatile("rcp.approx.ftz.f32 %0, %1;" : "=f"(i1) : "f"(rs[1]));
        wg_wait<0>();
        pin<4>(ot[0]); pin<4>(ot[1]);
        uint32_t x[4];
#pragma unroll
        for (int j = 0; j < 4; j++) {
          x[j] = pack_bf16(ot[j >> 1][2 * (j & 1)] * i0, ot[j >> 1][2 * (j & 1) + 1] * i1);
          sts32v(sb + OM + rank * OMS + oa + (j >> 1) * 1024 + (j & 1) * 128, x[j]);
        }
        fence_proxy_async();
#pragma unroll
        for (int j = 0; j < 8; j++) {
          const int i = P_OS ? j >> 1 : j & 3;
          if (P_OS ? j & 1 : j >> 2) st_async32(r1 + OM + rank * OMS + oa + (i >> 1) * 1024 + (i & 1) * 128, x[i], r1 + B_OM);
          else st_async32(r2 + OM2 + rank * OM2S + oa + (i >> 1) * 1024 + (i & 1) * 128, x[i], r2 + B_OM);
        }
        e_arrive(sb + B_OM);
        if (P_G2 < 16 && P_G2L) nbar_arrive<NB_G2, 384>();
        PROFW(0, 4);
      }
#pragma unroll
      for (int i = 0; i < 10; i++) hold[i] = w ? sc[4 * (i >> 1) + (i & 1)] : sc[4 * (i >> 1) + 2 + (i & 1)];
    }
    if (more && s >= 0) {
      LANE_NOW;
      char* const pw = (char*)g_part + (uint32_t)((t0 * 16 + w * 4 + (lane >> 3)) * 4096 + h * 128 + ((lane ^ h) & 7) * 16);
      mbar_wait(sb + B_OM, sp, budget);
      if (w == 0) nbar_arrive<NB_G, 128>();
      PROFW(1, 5);
      if (!ATT) fence_proxy_async();
      float acc[3][8];
      auto store = [&](auto J) {
        constexpr int j = J;
        float* d = acc[j % 3];
        pin<8>(d);
        uint32_t x[4];
#pragma unroll
        for (int i = 0; i < 4; i++) { const uint32_t m = (h >> 3) == i; x[i] = (pack_bf16(d[2*i], d[2*i+1]) & ~m) | (m & ~sp); }
        stg_rlx128(pw + j * (48 * 4096), x[0], x[1], x[2], x[3]);
        if constexpr (ATT && j == JA) nbar_arrive<NB_TR, 160>();
        if constexpr (j == 2) PROFW(3, 26);
      };
      sfor<0, NT>([&](auto J) {
        constexpr int j = J;
        if constexpr (ATT && j == JA) { mbar_wait(sb + B_WA, sp, budget); PROFW(2, 0); }
        wg_fence();
        sfor<0, 8>([&](auto K) {
          constexpr int k = K;
          typedef Op<(ATT ? OM : OM2) + k * 256, 128, ATT ? OMS : OM2S, 0, 1> OB;
          if constexpr (j == 5 && k < 4) wg_rs16<k ? 1 : 2, OB>(acc[j % 3], wl + 4 * k, d0);
          else wg_ss16<k ? 1 : j < 3 ? 0 : 2, Op<(j == JA ? WA : j < 5 ? WO + (j - (j > JA)) * 16384 : WH - 8192) + k * 2048, 16, 1024, 1, 1>, OB>(acc[j % 3], d0, d0);
        });
        wg_commit();
        if constexpr (j == 0) { if (w == 3) e_expect_tx(sb + B_OM, ATT ? 2048 : 4096); }
        if constexpr (j == NT - 1 && !P_WOL) nbar_arrive<NB_WO, 384>();
        if constexpr (j > 0 && j != P_WB + 1) { wg_wait<1>(); store(IC<j - 1>{}); }
        if constexpr (j == P_WB || j == NT - 1) { wg_wait<0>(); store(IC<j>{}); }
        if constexpr (j == P_WB) {
          const uint32_t t = clock32();
          if (ATT) {
            if (w == 3 && lane < 14) sts128(sb + PM1 + lane * 16, (lane >> 1) == 3 ? 0x3F803F80u : 0);
            if (w == 3 || P_MB) fence_proxy_async();
            nbar_sync<NB_P, 128>();
          } else if (P_MB) fence_proxy_async();
          spin_until(t, TUN(8, 100));
        }
      });
      if (P_WOL) { spin_until(clock32(), TUN(9, 0)); nbar_arrive<NB_WO, 384>(); }
    } else if (more) nbar_arrive<NB_WO, 384>();
    PROFW(0, 6);
    asm volatile("" : "+r"(h), "+r"(rank), "+r"(w));
#pragma unroll 1
    for (int pass = 0; ATT && pass < 2; pass++)
    if (pass != rank) {
      LANE_NOW;
      const int lim = 8 * (g >> 1) + (g & 1) + 2 * w - 8 * c;
      uint32_t p[5];
#pragma unroll
      for (int i = 0; i < 8; i++) hold[2+i] = i <= lim ? hold[2+i] : -INFINITY;
      const float psum = softmax_row(hold, p);
#pragma unroll
      for (int i = 0; i < 5; i++) hold[i] = __uint_as_float(p[i]);
      hold[5] = psum;
    } else if (more) {
      LANE_NOW;
      const int blk = rank * 32 + h;
      char* const mw = (char*)g_mem + (uint32_t)(sp * 32768 + blk * 512 + w * 128 + lane * 4);
      uint32_t v0 = 0;
      if (s == -1 || (s == LAG - 1 && (w & 1))) {
        const unsigned short* q = (const unsigned short*)mem0 + c * 2 * DM + blk * 16 + (w >> 1) * 8 + g;
        v0 = q[0] | (uint32_t)q[DM] << 16;
        if (v0 == 0) v0 = 0x8000u;
      }
      keep(mw);
      if (s >= 0) {
        const uint32_t ca = sb + WA + lane * 128 + (((2 * w) ^ lane) & 7) * 16 + (lane >> 3) * 4;
        const uint32_t sa = sb + OM + (((g >> 1) & 1) * 2 + (g >> 2)) * 128 + (2 * c + (w >> 1)) * 16 + (w & 1) * 8 + (g & 1) * 2;
        for (bool first = true; ; first = false) {
          float r[4];
          mbar_wait(sb + B_PART, pph, budget);
          PROFW(0, 11);
          pph ^= 1;
          wg_fence();
          sfor<0, 8>([&](auto K) { constexpr int k = K; wg_ss8<k != 0, Op<WA + k * 2048, 16, 1024, 1, 1>, Op<PM1 + (6 - (k & 6)) * 16, 0, 128, 0, 0>>(r, d0, d0); });
          wg_commit();
          if (P_G4 < 16 && !P_G4L && first) nbar_arrive<NB_G4, 384>();
          const uint32_t x0 = lds32v(ca), x1 = lds32v(ca + 4096), x2 = lds32v(ca + 8192), x3 = lds32v(ca + 12288);
          bool bad = __any_sync(0xffffffffu, (sp ? x0 | x1 | x2 | x3 : ~(x0 & x1 & x2 & x3)) & 1) && budget > 0;
          wg_wait<0>();
          pin<4>(r);
          uint32_t y = pack_bf16(r[0], r[2]);
          y |= (y & 0xffffu) ? 0 : 0x8000u;
          y |= (y >> 16) ? 0 : 0x80000000u;
          if (bad) y = 0;
          sts16(sa, y); sts16(sa + 4, y >> 16);
          nbar_sync<NB_P, 128>();
          y = lds32v(sb + OM + w * 128 + lane * 4);
          const bool ok = !__any_sync(0xffffffffu, y == 0);
          if (ok) stg_rlx32(mw, v0 ? v0 : y);
          if (P_G4 < 16 && P_G4L && first) nbar_arrive<NB_G4, 384>();
          if (ok) break;
          nbar_sync<NB_P, 128>();
          budget--;
          if (w == 0) { e_expect_tx(sb + B_PART, 16384); e_bulk_g2s(sb + WA, (const char*)g_part + blk * 16384, 16384, sb + B_PART); }
          __syncwarp();
        }
      } else stg_rlx32(mw, v0);
      stg_rlx32(mw + (sp ? -32768 : 32768), 0);
      PROFW(1, 8);
    }
    if (ATT && s >= 0) {
      const int seg = s - (rank ? LAG : 0);
      const bool act = (unsigned)seg < NSEG;
      LANE_NOW;
      uint32_t a[12];
#pragma unroll
      for (int i = 0; i < 12; i++) a[i] = __float_as_uint(hold[i < 10 ? i >> 1 : 4]) + ((uint32_t)budget >> (31 - (i & 3)));
      float o[32], inv, psum = hold[5];
      char* const ob = (char*)g_o[rank] + ((size_t)(seg * 32 + 8 * (g >> 1) + (g & 1) + 2 * w) * (NH * DH) + h * DH + c * 8) * 2;
      sfor<0, 2>([&](auto HF) {
        constexpr int hf = HF;
        wg_fence();
        wg_rs64<hf * 2, Op<QB + 8 * RG + hf * 1024, 2 * RG, 128, 0, 0>>(o, a, d0);
        wg_rs64<1, Op<QB + 12 * RG + hf * 1024, RG, 128, 0, 0>>(o, a + 4, d0);
        wg_rs64<1, Op<QB + 14 * RG + hf * 1024, 0, 128, 0, 0>>(o, a + 8, d0);
        wg_commit();
        if constexpr (hf == 0) {
          psum += __shfl_xor_sync(0xffffffffu, psum, 1);
          psum += __shfl_xor_sync(0xffffffffu, psum, 2);
          asm("rcp.approx.ftz.f32 %0, %1;" : "=f"(inv) : "f"(psum));
        }
        wg_wait<0>();
        pin<32>(o);
        if constexpr (hf == 1) { if (w < 3 && more) e_arrive_cl(mapr(h, sb + B_BFREE, w)); }
        if (act) {
#pragma unroll
          for (int i = 0; i < 2; i++)
            stg128(ob + (hf * 2 + i) * 64, pack_bf16(o[16*i] * inv, o[16*i+1] * inv), pack_bf16(o[16*i+4] * inv, o[16*i+5] * inv),
                   pack_bf16(o[16*i+8] * inv, o[16*i+9] * inv), pack_bf16(o[16*i+12] * inv, o[16*i+13] * inv));
        }
      });
      PROFW(0, 7);
      if (act && (seg & 3) == 3) {
        nbar_sync<NB_P, 128>();
        if (w == 0) e_flag_add(g_fl.dep + grp(0, rank, seg >> 2), 4);
      }
    } else if (!ATT && w == 3) {
      if (s + 4 < NSEG) e_prefetch(g_xn[0] + (size_t)((s + 4) * 32 + h) * DM, 2048);
    }
  }
  cluster_arrive(); cluster_wait();
  char* const pw = (char*)g_part + (size_t)((ATT ? rank + 1 : 0) * 16 + w * 4 + (lane0 >> 3)) * 4096 + h * 128 + (lane0 & 7) * 16;
#pragma unroll
  for (int j = 0; j < NT; j++) stg_rlx128(pw + j * (48 * 4096), 0, 0, 0, 0);
}

DEVI void rec_load(const uint32_t sb, const int h, const int rank, const int w, const CUtensorMap* mX, const CUtensorMap* mWo) {
  using namespace rec;
  static_assert(((NSTEP - 1) & 31) != 1 && ((NSTEP - 2) & 31) != 2, "stale time stamps of the previous launch never match");
  const int lane0 = lane_reg(), mq = (w + 3) & 3;
  int budget = SPIN_BUDGET;
  cluster_arrive(); cluster_wait();
  if (w == 0) { if (lane0 < 4) mbar_arrive(sb + B_FULL + 8 * lane0); __syncwarp(); }
  uint32_t lph = 0;
#pragma unroll 1
  for (int s = -1; s < NSTEP - 1; s++) {
    if (w == 0) {
      const int sa = s + 1, sn = sa - LAG;
      if ((sa & 3) == 0 && sa < NSEG) flag_wait(g_fl.xn[0][sa >> 2], 128, budget);
      if ((sn & 3) == 0 && (unsigned)sn < NSEG) flag_wait(g_fl.xn[1][sn >> 2], 128, budget);
      if (single(s)) {
#pragma unroll 1
        for (int i = 0; i < 8; i++) {
          const int k = i < 5 ? (0x21430 >> (4 * i)) & 15 : i;
          const int sl = (SLOT1 >> (4 * k)) & 15;
          mbar_wait(sb + B_EMPTY + 8 * sl, (((USE1 >> (4 * k)) ^ (sl >> 1 == 1 ? s + 1 : 0)) & 1) ^ 1, budget);
          e_expect_tx(sb + B_FULL + 8 * sl, 8192);
          e_tma_3d(sb + RING + sl * 8192, mX + 1, 0, (s + 1 + (s < LAG ? 0 : NSTEP)) * 32, k * 2, sb + B_FULL + 8 * sl);
        }
      } else {
        int sl = 4, ph = 1;
#pragma unroll 1
        for (int i = 0; i < 16; i++) {
          mbar_wait(sb + B_EMPTY + 8 * sl, ph, budget);
          e_expect_tx(sb + B_FULL + 8 * sl, 8192);
          e_tma_3d(sb + RING + sl * 8192, mX, i * 64, (s + 1) * 32, 0, sb + B_FULL + 8 * sl);
          if (++sl == 5) { sl = 0; ph ^= 1; }
        }
      }
      nbar_arrive<NB_X, 128>();
    }
    uint32_t t = gtime();
    if (s >= 0) {
      uint2 a;
      if (w == 2 && rank < 2) {
        nbar_sync<NB_S, 64>();
        e_expect_tx(sb + B_WA, 16384);
        e_tma_2d(sb + WA, mWo, (3 * JA + 1 + rank) * 64, h * DH, sb + B_WA);
        e_tma_2d(sb + WA + 8192, mWo, (3 * JA + 1 + rank) * 64, h * DH + 64, sb + B_WA);
        e_arrive_cl(mapr(h, sb + B_SDONE, rank ^ 1));
        stg_rlx32(&g_ann[s & 1][lane0][h * 2 + rank], (gtime() & ~31u) | ((s + 1) & 31));
        e_expect_tx(sb + B_QK, 10240);
        e_expect_tx(sb + B_V, 10240);
      }
      if (w) nbar_sync<NB_G, 128>();
      do { a = ldg_rlx64(&g_ann[s & 1][h][lane0 * 2]); } while (__any_sync(0xffffffffu, ((a.x ^ (s + 1)) | (a.y ^ (s + 1))) & 31) && --budget > 0);
      t += __reduce_max_sync(0xffffffffu, max((int)(a.x - t), (int)(a.y - t)));
      t = (t & ~31u) - (single(s) ? TUN(6, 200) : 0);
      PROFW(1, 12);
      if (w == 1 && rank < 2) {
        nbar_sync<NB_TR, 160>();
        wait_time(t + (rank ? TUN(1, 1750) : TUN(0, 1400)), budget);
        e_expect_tx(sb + B_PART, 16384);
        e_bulk_g2s(sb + WA, (const char*)g_part + (rank * 32 + h) * 16384, 16384, sb + B_PART);
        PROFW(1, 21);
      }
      t -= single(s) ? TUN(7, 100) : 0;
      t += mq == 0 ? TUN(2, 2450) : mq == 1 ? TUN(3, 2500) : mq == 2 ? TUN(4, 2800) : TUN(5, 2850);
    }
    if (w) nbar_sync<NB_X, 128>();
    mbar_wait(sb + B_EMPTY + 8 * mq, mq >= 2 && single(s) ? (s + 1) & 1 : 1, budget);
    PROFW(1, 9);
    wait_time(t, budget);
    PROFW(1, 22); PROFW(3, 23);
    while (true) {
      e_expect_tx(sb + B_MLAND + 8 * mq, 8192);
      e_bulk_g2s(sb + RING + mq * 8192, (const char*)g_mem + (s & 1) * 32768 + mq * 8192, 8192, sb + B_MLAND + 8 * mq);
      const uint32_t a = sb + RING + mq * 8192 + lane0 * 32 + (lane0 >> 2) * 4;
      mbar_wait(sb + B_MLAND + 8 * mq, lph, budget);
      lph ^= 1;
      PROFW(1, 24);
      uint32_t mn = 0xffffffffu;
#pragma unroll
      for (int i = 0; i < 8; i++) mn = min(mn, lds32v(a + i * 1024));
      if (!__any_sync(0xffffffffu, mn == 0) || --budget <= 0) break;
    }
    e_arrive(sb + B_FULL + 8 * mq);
    PROFW(1, 10); PROFW(2, 13); PROFW(3, 14); PROFW(0, 15);
  }
}

struct RecMaps { CUtensorMap w[3], wo, x[2]; };
__global__ void __cluster_dims__(R_CL, 1, 1) __launch_bounds__(512, 1)
rec_kernel(const __grid_constant__ RecMaps M, const bf16* __restrict__ Wo, const bf16* __restrict__ mem0, uint32_t zero) {
  using namespace rec;
  extern __shared__ __align__(1024) uint8_t smem[];
  const uint32_t sb = smem_u32(smem);
  const int tid = threadIdx.x, warp = __shfl_sync(0xffffffffu, tid >> 5, 0), wg = warp >> 2, lane = tid & 31;
  const int h = blockIdx.x / 3, rank = blockIdx.x % 3;
  if (warp == 0) {
    if (lane < 20) mbar_init(sb + BARS + 8 * lane, (lane >= 5 && lane < 10) || lane == 19 ? 2 : lane == 14 ? 9 : lane == 16 && rank < 2 ? 5 : 1);
    else if (lane < 23) mbar_init(sb + B_W1 + 8 * (lane - 20), 1);
    else if (lane == 23) mbar_init(sb + B_PART, 1);
    fence_mbar_init();
    __syncwarp();
    if (lane == 0) { mbar_expect_tx(sb + B_W1, (NSS + R1) * 4096); mbar_expect_tx(sb + B_QK, 10240); mbar_expect_tx(sb + B_V, 10240); mbar_expect_tx(sb + B_OM, rank < 2 ? 2048 : 4096); }
    __syncwarp();
    for (int i = lane; i < 128; i += 32) {
      const int j = i >> 1, t = i & 1, r = reg_idx(j);
      if (is_ss(j)) tma_load_2d(sb + WS + (t * NSS + ss_before(j)) * 2048, &M.w[rank], h * DH + t * 64, j * 16, sb + B_W1);
      else if (r < R1) tma_load_2d(sb + WO + (t * R1 + r) * 2048, &M.w[rank], h * DH + t * 64, j * 16, sb + B_W1);
      else tma_prefetch_2d(&M.w[rank], h * DH + t * 64, j * 16);
    }
    const int t = 3 * (lane >> 1) + (rank + 1) % 3;
    if (t < 16) tma_prefetch_2d(&M.wo, t * 64, h * DH + (lane & 1) * 64);
  } else if (warp == 1) {
    constexpr int N = (sizeof(Flags) - sizeof(g_fl.xn)) / 16;
    if (lane < 8 && blockIdx.x * 8 + lane < N) ((uint4*)g_fl.dep)[blockIdx.x * 8 + lane] = make_uint4(0, 0, 0, 0);
    static_assert(N <= 96 * 8, "flag reset");
    __threadfence();
    __syncwarp();
    asm volatile("griddepcontrol.launch_dependents;" ::: "memory");
  }
  __syncthreads();
  if (wg == 3) {
    reg_dec<24>();
    rec_load(sb, h, rank, warp & 3, M.x, &M.wo);
    cluster_arrive(); cluster_wait();
  } else if (wg == 2) {
    reg_dec<72>();
    if (rank < 2) rec_attn<true>(sb, h, rank, warp & 3, Wo, mem0);
    else rec_attn<false>(sb, h, rank, warp & 3, Wo, mem0);
  } else {
    reg_inc<208>();
    rec_proj(sb, h, rank, warp, &M.w[rank], &M.wo, zero);
    cluster_arrive(); cluster_wait();
  }
}

namespace gm {
constexpr int STAGES = 6, STAGE_BYTES = 32768;
constexpr uint32_t SO = STAGES * STAGE_BYTES, B_FULL = SO + 32768, B_TRIG = B_FULL + 56, B_EMPTY = B_FULL + 64, B_JOB = B_FULL + 128,
                   B_MSG = B_FULL + 144, B_XF = B_FULL + 160, B_SF = B_FULL + 176, JOB = B_FULL + 192, MSG = JOB + 8, SMEM = B_FULL + 256;
constexpr int T_O = 0, T_GU = 1, T_D = 2, T_END = 3, NEARLY = 32;
#define G_LOOK 8
#define G_FILL 7
#define G_SLEEP 200
#define G_SLEEP2 500
#define G_SLEEP3 200
#define G_DS 12
DEVI bool is_split(int ty, int l, int cb) { return ty == T_O || (ty == T_D && (!l || cb >= G_DS)); }
struct Pipe { int s, ph; DEVI void next() { if (++s == STAGES) { s = 0; ph ^= 1; } } };
}
struct GemmMaps { CUtensorMap o, wo, x, x1, x1s, xm, xms, xn, wg, wu, h, hs, wd, x2, out, outs; };

DEVI float geglu(float g, float u) {
  const float z = g * (0.7978845608028654f + 0.035677408136300125f * g * g);
  float t; asm("tanh.approx.f32 %0, %1;" : "=f"(t) : "f"(z));
  const float hg = 0.5f * g;
  return fmaf(hg, t, hg) * u;
}
DEVI int h_ready(int v) { const int t = v ^ 0x101414; return t ? ((__ffs(t) - 1) >> 3) * 20 : 56; }
DEVI int a_ready(int ty, int l, int cb) {
  const int v = ld_acquire(g_fl.dep + grp(ty, l, cb));
  asm volatile("fence.proxy.async.global;" ::: "memory");
  return ty == gm::T_D ? h_ready(v) : v >= 128 ? 64 : 0;
}
DEVI void ln_row(const bf16* src, bf16* dst, int lane) {
  uint4 u[4];
  const uint32_t* x = (const uint32_t*)u;
#pragma unroll
  for (int i = 0; i < 4; i++) u[i] = __ldcg((const uint4*)src + i * 32 + lane);
  float mean = 0, q = 0;
#pragma unroll
  for (int i = 0; i < 16; i++) mean += bf_lo(x[i]) + bf_hi(x[i]);
  mean *= 1.f / 32;
#pragma unroll
  for (int i = 0; i < 16; i++) { const float a = bf_lo(x[i]) - mean, b = bf_hi(x[i]) - mean; q = fmaf(a, a, fmaf(b, b, q)); }
#pragma unroll
  for (int o = 1; o < 32; o *= 2) {
    const float m2 = __shfl_xor_sync(0xffffffffu, mean, o), q2 = __shfl_xor_sync(0xffffffffu, q, o), dl = m2 - mean;
    q = fmaf(dl * dl, 16.f * o, q + q2);
    mean = 0.5f * (mean + m2);
  }
  const float rs = rsqrtf(q * (1.f / DM) + 1e-5f), mr = -mean * rs;
#pragma unroll
  for (int i = 0; i < 4; i++) {
    uint32_t y[4];
#pragma unroll
    for (int k = 0; k < 4; k++) y[k] = pack_bf16(fmaf(bf_lo(x[4*i+k]), rs, mr), fmaf(bf_hi(x[4*i+k]), rs, mr));
    stg128((uint4*)dst + i * 32 + lane, y[0], y[1], y[2], y[3]);
  }
}

__global__ void __cluster_dims__(2, 1, 1) __launch_bounds__(512, 1) gemm_kernel(const __grid_constant__ GemmMaps M, const bf16* __restrict__ x) {
  using namespace gm;
  extern __shared__ __align__(1024) uint8_t smem[];
  const uint32_t sb = smem_u32(smem);
  const int tid = threadIdx.x, wid = __shfl_sync(0xffffffffu, tid >> 5, 0), wg = wid >> 2, warp = wid & 3;
  int budget = SPIN_BUDGET;
  const int rank = blockIdx.x & 1;
  const uint32_t peer = mapa(sb, rank ^ 1);
  if (tid < 24) mbar_init(sb + B_FULL + 8 * tid, tid >> 3 == 1 ? 2 : 1);
  fence_mbar_init();
  if (wid == 1 && rank == 0) sts32v(sb + JOB + 16, bcast(e_ticket(g_fl.ticket)));
  cluster_arrive(); cluster_wait();
  int pair;
  asm volatile("ld.shared::cluster.u32 %0, [%1];" : "=r"(pair) : "r"(mapa(sb + JOB + 16, 0)) : "memory");
  pair = __shfl_sync(0xffffffffu, pair, 0);
  const int cta = pair * 2 + rank, lane = lane_reg();
  if (wg >= 2) {
    reg_dec<72>();
    if (wid == 8 || wid == 10) {
      Pipe p; p.s = 0; p.ph = 1;
      for (int n = 0; ; n++) {
        if (wid == 8) e_expect_tx(sb + B_MSG + 8 * (n & 1), 4);
        mbar_wait(sb + B_MSG + 8 * (n & 1), (n >> 1) & 1, budget);
        const int msg = __shfl_sync(0xffffffffu, lds32v(sb + MSG + 4 * (n & 1)), 0);
        const int ty = (msg >> 11) & 3, l = (msg >> 10) & 1;
        const bool shb = ty == T_GU && l, spl = is_split(ty, l, (msg >> 6) & 15);
        const int cb = ((msg >> 6) & 15) + (shb ? rank : 0), j = (msg & 63) + (ty == T_END || shb ? 0 : rank);
        const int ke = ty == T_O ? 64 : ty == T_GU ? 16 : 56, k0 = spl ? rank : 0, dk = spl ? 2 : 1;
        const int c0 = ty == T_GU ? j * 64 : spl ? (j >> 1) * 128 : j * 128, c1 = ty == T_GU ? c0 : c0 + 64;
        mbar_wait(sb + B_EMPTY + 8 * p.s, p.ph, budget);
        trap_if_spent(budget);
        auto stages = [&](auto f) {
#pragma unroll 1
          for (int k = k0; k < ke; k += dk) {
            mbar_wait(sb + B_EMPTY + 8 * p.s, p.ph, budget);
            f(k, sb + p.s * STAGE_BYTES, sb + B_FULL + 8 * p.s);
            p.next();
          }
        };
        if (wid == 8) {
          const int job = ty << 11 | l << 10 | cb << 6 | j;
          sts32v(sb + JOB + 4 * (n & 1), job | p.s << 16 | (p.ph ^ 1) << 20);
          e_arrive(sb + B_JOB + 8 * (n & 1));
          if (ty == T_END) break;
          if (ty != T_GU) { e_expect_tx(sb + B_FULL + 8 * p.s, spl ? 16384 : STAGE_BYTES); p.next(); }
          const CUtensorMap* const m0 = ty == T_D ? &M.wd : shb && rank ? &M.wu : &M.wg, * const m1 = ty == T_D ? &M.wd : &M.wu;
          if (ty == T_O) stages([&](int k, uint32_t a, uint32_t fb) { e_expect_tx(fb, STAGE_BYTES); e_tma_5d(a + 16384, &M.wo, c0, k * 2, fb); e_tma_5d(a + 24576, &M.wo, c1, k * 2, fb); });
          else if (shb) stages([&](int k, uint32_t a, uint32_t fb) { e_expect_tx(fb, STAGE_BYTES); e_tma_2d_mc(a + 16384 + rank * 8192, m0, c0, k * 64, fb); });
          else stages([&](int k, uint32_t a, uint32_t fb) { e_expect_tx(fb, STAGE_BYTES); e_tma_2d(a + 16384, m0, c0, k * 64, fb); e_tma_2d(a + 24576, m1, c1, k * 64, fb); });
        } else {
          if (ty == T_END) break;
          const int row = l * SEQ + cb * 128, kt = ke + k0 - G_LOOK * dk;
          int rdy = msg >> 16;
          auto need = [&](int k) {
            if (k == kt) e_arrive(sb + B_TRIG);
            while (k >= rdy && k >= (rdy = a_ready(ty, l, cb))) { __nanosleep(G_SLEEP); trap_if_spent(--budget); }
          };
          if (ty != T_GU) {
            need(0);
            const uint32_t a = sb + p.s * STAGE_BYTES, fb = sb + B_FULL + 8 * p.s;
            const CUtensorMap* const m = ty == T_D ? (spl ? &M.x1 : &M.x1s) : l ? &M.x2 : &M.x;
            const int r = (ty == T_D ? row : cb * 128) + (spl ? rank * 64 : 0);
            e_tma_2d(a, m, c0, r, fb); e_tma_2d(a + 16384, m, c1, r, fb);
            p.next();
          }
          if (shb || spl) {
            const CUtensorMap* const ma = ty == T_O ? &M.o : ty == T_GU ? &M.xms : &M.hs;
            stages([&](int k, uint32_t a, uint32_t fb) { need(k); e_tma_2d(a, ma, k * 64, row, fb); });
          } else {
            const CUtensorMap* const ma = ty == T_GU ? &M.xm : &M.h;
            stages([&](int k, uint32_t a, uint32_t fb) { need(k); e_tma_2d_mc(a + rank * 8192, ma, k * 64, row + rank * 64, fb); });
          }
        }
      }
    } else if (wid == 9 && rank == 0) {
      int k1 = pair < 18 ? 0 : 68;
      bool late = false;
      for (int n = 0, ty = 0; ty != T_END; n++) {
        mbar_wait(sb + B_TRIG, (n & 1) ^ 1, budget);
        int l, cb, j, rdy = 64;
        while (true) {
          const int ph = k1 & 3;
          const bool gap = ph == 3;
          if (k1 < 68) {
            cb = (k1++ >> 2) - (pair < 8 ? ph : 0);
            if ((unsigned)cb >= 16 || (ph == 2 && pair >> 3 != 1) || (gap && (pair < 8 || late || !(G_FILL & (pair >> 3))))) continue;
            if (!gap) {
              l = 0;
              ty = pair < 8 ? (ph ? T_D : T_O) : T_GU;
              j = 2 * (pair < 8 ? pair : pair - 8 + 10 * ph);
              rdy = a_ready(ty, 0, cb);
              if (ph == 0) late = rdy != 0;
              break;
            }
          }
          int d0 = ld_relaxed(g_fl.dep + lane), d1 = ld_relaxed(g_fl.dep + 32 + lane);
          const int t0 = ld_relaxed(g_fl.taken + lane), t1 = ld_relaxed(g_fl.taken + 32 + lane);
          const bool l0 = t0 < (lane < 16 ? 8 : lane & 1 ? 0 : 56), l1 = lane < 16 && t1 < (lane < G_DS ? 4 : 8);
          const uint32_t rd = __ballot_sync(0xffffffffu, d0 >= 128);
          uint32_t ok0 = __ballot_sync(0xffffffffu, l0) & rd & (rd >> 1 | 0xffff), ok1 = __ballot_sync(0xffffffffu, l1 && h_ready(d1) > 0);
          if (gap) { ok1 = 0; if (pair < 16) ok0 &= G_FILL & 8 ? ((k1 >> 2 ^ pair) & 1 ? ~0u : 0u) : G_FILL & 4 ? 0xffff0003u : 0xffff0000u; }
          ty = T_END; l = 1; cb = j = 0;
          if (!gap && !__any_sync(0xffffffffu, l0 || l1)) break;
          if (ok1 & ((1u << G_DS) - 1)) ok1 &= (1u << G_DS) - 1;
          uint32_t m = ok0 ? ok0 : ok1;
          if (!m && !gap) __nanosleep(100);
          while (m) {
            const int nth = ok0 ? 0 : pair % __popc(m);
            const int b = __ffs(__ballot_sync(0xffffffffu, __popc(m << (31 - lane)) > nth)) - 1, gn = b + (ok0 ? 0 : 32);
            const int t = bcast(e_ticket(g_fl.taken + gn));
            if (t < (gn < 16 ? 8 : gn < 32 ? 56 : gn < 32 + G_DS ? 4 : 8)) { ty = gn >> 4; cb = gn & 15; j = ty == T_GU ? t : 2 * t; break; }
            m &= ~(1u << b);
          }
          if (ty != T_END) {
            rdy = a_ready(ty, 1, cb);
            if (ty == T_GU) a_ready(ty, 1, cb + 1);
            break;
          }
          trap_if_spent(--budget);
        }
        const int msg = rdy << 16 | ty << 11 | l << 10 | cb << 6 | j;
        e_st_async32(peer + MSG + 4 * (n & 1), msg, peer + B_MSG + 8 * (n & 1));
        e_st_async32(sb + MSG + 4 * (n & 1), msg, sb + B_MSG + 8 * (n & 1));
      }
    } else if (wg == 3) {
      bool open = lane < 16 && ld_relaxed(g_fl.rows + lane) < 128;
      while (__any_sync(0xffffffffu, open)) {
        int v = 0;
        if (open) asm volatile("ld.acquire.gpu.global.s32 %0, [%1];" : "=r"(v) : "l"(g_fl.part + lane) : "memory");
        const uint32_t ok = __ballot_sync(0xffffffffu, open && v >= 16);
        if (!ok) {
          if (--budget <= 0) break;
          __nanosleep(G_SLEEP2);
          continue;
        }
        const int cb = __ffs(__ballot_sync(0xffffffffu, __popc(ok << (31 - lane)) > (cta >> 5) % __popc(ok))) - 1;
        const int r = bcast(e_ticket(g_fl.rows + cb));
        if (r >= 128) { open = open && lane != cb; continue; }
        ln_row(g_x1[1] + (size_t)(cb * 128 + r) * DM, g_xm[1] + (size_t)(cb * 128 + r) * DM, lane);
        __syncwarp();
        e_flag_add(g_fl.dep + grp(T_GU, 1, cb));
      }
      if (cta == 0 && wid == 12) {
        asm volatile("griddepcontrol.wait;" ::: "memory");
        g_fl.xn[lane >> 4][lane & 15][0] = 0;
      }
    }
    cluster_arrive(); cluster_wait();
  } else {
    reg_inc<184>();
    if (cta < NEARLY) {
#pragma unroll 1
      for (int r = 2 * (cta * 8 + wid); r < SEQ; r += 16 * NEARLY) {
        ln_row(x + (size_t)r * DM, g_xn[0] + (size_t)r * DM, lane);
        ln_row(x + (size_t)(r + 1) * DM, g_xn[0] + (size_t)(r + 1) * DM, lane);
        __syncwarp();
        e_flag_add(g_fl.xn[0][r >> 7], 2);
      }
    }
    const bool lead = warp == 0;
    const uint32_t eb = (warp == 1 ? peer : sb) + B_EMPTY;
    const int rl = warp < 2 ? 0 : -1;
    const uint32_t so = sb + SO + wg * 16384;
    const int r0 = warp * 16 + (lane & 7) + ((lane >> 3) & 1) * 8;
    const uint32_t sw = r0 * 128 + (((lane >> 4) ^ (r0 & 7)) << 4);
    int xph = 0;
    for (int n = wg; ; n += 2) {
      float d0[64], d1[64];
      mbar_wait(sb + B_JOB + 8 * wg, (n >> 1) & 1, budget);
      fault_if_spent(budget);
      const int job = __shfl_sync(0xffffffffu, lds32v(sb + JOB + 4 * wg), 0);
      const int ty = (job >> 11) & 3, l = (job >> 10) & 1, cb = (job >> 6) & 15, j = job & 63;
      if (ty == T_END) {
        if (n > 0) nbar_sync_r(1 + wg, 256);
        if (lead && !(job & 1)) { sts32v(sb + JOB + 4 * (wg ^ 1), job | 1); e_arrive(sb + B_JOB + 8 * (wg ^ 1)); }
        if (!(job & 1)) nbar_arrive_r(1 + (wg ^ 1), 256);
        break;
      }
      Pipe q; q.s = (job >> 16) & 15; q.ph = job >> 20;
      const bool spl = is_split(ty, l, cb);
      if (ty != T_GU) mbar_wait(sb + B_FULL + 8 * q.s, q.ph, budget);
#pragma unroll
      for (int m = 0; m < 2; m++) {
        float* d = m ? d1 : d0;
        if (ty != T_GU && !(m && spl)) {
#pragma unroll
          for (int c = 0; c < 8; c++) {
            uint32_t r[4];
            ldsm4(sb + q.s * STAGE_BYTES + (c >> 2) * 16384 + m * 8192 + (sw ^ ((c & 3) << 5)), r[0], r[1], r[2], r[3]);
#pragma unroll
            for (int i = 0; i < 4; i++) { d[8*c+2*i] = bf_lo(r[i]); d[8*c+2*i+1] = bf_hi(r[i]); }
          }
        } else {
#pragma unroll
          for (int i = 0; i < 64; i++) d[i] = 0.f;
        }
      }
      if (ty != T_GU) {
        fence_proxy_async();
        nbar_sync_r(3 + wg, 128);
        arrive_cl_if_eq(eb + 8 * q.s, lane, rl);
        q.next();
      }
      pin<64>(d0); pin<64>(d1);
      if (n > 0) nbar_sync_r(1 + wg, 256);
      const int nk = ty == T_O ? 32 : ty == T_GU ? 16 : spl ? 28 : 56;
      const uint32_t ro = spl ? rank * 512 : 0;
      int prev = 0;
      for (int i = 0; i < nk; i++) {
        mbar_wait(sb + B_FULL + 8 * q.s, q.ph, budget);
        const uint32_t da = desc_base(sb) + q.s * (STAGE_BYTES / 16);
        wg_fence();
        sfor<0, 4>([&](auto K) {
          constexpr int k = K;
          typedef Op<16384 + k * 2048, 8192, 1024, 1, 1> OB;
          wg_ss128<1, Op<k * 32, 16, 1024, 1, 0>, OB>(d0, da + ro, da);
          wg_ss128<1, Op<8192 + k * 32, 16, 1024, 1, 0>, OB>(d1, da - ro, da);
        });
        wg_commit();
        wg_wait<1>();
        arrive_cl_if_eq(eb + 8 * prev, lane, i ? rl : -1);
        prev = q.s;
        q.next();
      }
      nbar_arrive_r(1 + (wg ^ 1), 256);
      wg_wait<0>();
      pin<64>(d0); pin<64>(d1);
      arrive_cl_if_eq(eb + 8 * prev, lane, rl);
      if (spl) {
        const uint32_t xa = SO + wg * 16384 + warp * 512 + lane * 16;
        if (lead) e_expect_tx(sb + B_XF + 8 * wg, 16384);
        mbar_wait(sb + B_SF + 8 * wg, ((n >> 1) & 1) ^ 1, budget);
#pragma unroll
        for (int i = 0; i < 8; i++) {
          const float* d = d1 + 8 * i;
          st_async128(peer + xa + i * 2048, pack_bf16(d[0], d[1]), pack_bf16(d[2], d[3]), pack_bf16(d[4], d[5]), pack_bf16(d[6], d[7]), peer + B_XF + 8 * wg);
        }
        mbar_wait(sb + B_XF + 8 * wg, xph, budget);
        xph ^= 1;
        uint32_t y[32];
#pragma unroll
        for (int i = 0; i < 8; i++) {
          const float* d = d0 + 8 * i;
          const uint4 v = lds128(sb + xa + i * 2048);
          y[4*i] = pack_bf16(d[0] + bf_lo(v.x), d[1] + bf_hi(v.x)); y[4*i+1] = pack_bf16(d[2] + bf_lo(v.y), d[3] + bf_hi(v.y));
          y[4*i+2] = pack_bf16(d[4] + bf_lo(v.z), d[5] + bf_hi(v.z)); y[4*i+3] = pack_bf16(d[6] + bf_lo(v.w), d[7] + bf_hi(v.w));
        }
        float2* const st = &g_stat[ty >> 1][cb & 1][0][rank * 64 + warp * 16 + (lane >> 2) * 2];
        if (!l) {
          float mn[2], sq[2];
#pragma unroll
          for (int z = 0; z < 2; z++) {
            float m = 0, s2 = 0;
#pragma unroll
            for (int i = 0; i < 16; i++) m += bf_lo(y[2*i+z]) + bf_hi(y[2*i+z]);
            m += __shfl_xor_sync(0xffffffffu, m, 1); m += __shfl_xor_sync(0xffffffffu, m, 2);
            m *= 1.f / 128;
#pragma unroll
            for (int i = 0; i < 16; i++) { const float a = bf_lo(y[2*i+z]) - m, b = bf_hi(y[2*i+z]) - m; s2 = fmaf(a, a, fmaf(b, b, s2)); }
            s2 += __shfl_xor_sync(0xffffffffu, s2, 1); s2 += __shfl_xor_sync(0xffffffffu, s2, 2);
            mn[z] = m; sq[z] = s2;
          }
          if ((lane & 3) == 0) stg_rlx128(st + (j >> 1) * 128, __float_as_uint(mn[0]), (__float_as_uint(sq[0]) & ~31u) | (cb + 1), __float_as_uint(mn[1]), __float_as_uint(sq[1]));
          __syncwarp();
        }
        auto put = [&](const CUtensorMap* mo, int row) {
          nbar_sync_r(3 + wg, 128);
#pragma unroll
          for (int c = 0; c < 8; c++) stsm4(so + (c >> 2) * 8192 + (sw ^ ((c & 3) << 5)), y[4*c], y[4*c+1], y[4*c+2], y[4*c+3]);
          fence_proxy_async();
          nbar_sync_r(3 + wg, 128);
          if (lead) { e_tma_store_2d(mo, so, (j >> 1) * 128, row); e_tma_store_2d(mo, so + 8192, (j >> 1) * 128 + 64, row); bulk_commit(); }
        };
        const int row = (ty == T_O ? l * SEQ : 0) + cb * 128 + rank * 64;
        put(ty == T_O ? &M.x1 : l ? &M.out : &M.x2, row);
        if (!l) {
          uint4 u[2];
          while (true) {
            u[0] = ldg_rlx128(st + (lane & 3) * 256); u[1] = ldg_rlx128(st + (lane & 3) * 256 + 128);
            if (!__any_sync(0xffffffffu, ((u[0].y ^ (cb + 1)) | (u[1].y ^ (cb + 1))) & 31) || --budget <= 0) break;
            __nanosleep(G_SLEEP3);
          }
#pragma unroll
          for (int z = 0; z < 2; z++) {
            const float ma = __uint_as_float(z ? u[0].z : u[0].x), mb = __uint_as_float(z ? u[1].z : u[1].x);
            float m = ma + mb;
            m += __shfl_xor_sync(0xffffffffu, m, 1); m += __shfl_xor_sync(0xffffffffu, m, 2);
            m *= 0.125f;
            float s2 = __uint_as_float(z ? u[0].w : u[0].y & ~31u) + __uint_as_float(z ? u[1].w : u[1].y & ~31u) + 128.f * ((ma - m) * (ma - m) + (mb - m) * (mb - m));
            s2 += __shfl_xor_sync(0xffffffffu, s2, 1); s2 += __shfl_xor_sync(0xffffffffu, s2, 2);
            const float rs = rsqrtf(s2 * (1.f / DM) + 1e-5f), mr = -m * rs;
#pragma unroll
            for (int i = 0; i < 16; i++) y[2*i+z] = pack_bf16(fmaf(bf_lo(y[2*i+z]), rs, mr), fmaf(bf_hi(y[2*i+z]), rs, mr));
          }
          if (lead) bulk_wait_read<0>();
          put(ty == T_O ? &M.xm : &M.xn, row);
        }
      } else {
        if (ty == T_GU) {
#pragma unroll
          for (int i = 0; i < 32; i++) { d0[i] = geglu(d0[i], d0[32 + i]); d1[i] = geglu(d1[i], d1[32 + i]); }
        }
#pragma unroll
        for (int hf = 0; hf < 2; hf++) {
          if (hf) {
            if (ty == T_GU) break;
            if (lead) bulk_wait_read<0>();
            nbar_sync_r(3 + wg, 128);
          }
#pragma unroll
          for (int m = 0; m < 2; m++)
#pragma unroll
            for (int c = 0; c < 4; c++) {
              const float* d = (m ? d1 : d0) + 32 * hf + 8 * c;
              stsm4(so + m * 8192 + (sw ^ (c << 5)), pack_bf16(d[0], d[1]), pack_bf16(d[2], d[3]), pack_bf16(d[4], d[5]), pack_bf16(d[6], d[7]));
            }
          fence_proxy_async();
          nbar_sync_r(3 + wg, 128);
          if (lead) {
            if (ty == T_GU) e_tma_store_2d(&M.hs, so, j * 64, l * SEQ + cb * 128); else e_tma_store_2d(&M.outs, so, j * 128 + hf * 64, cb * 128);
            bulk_commit();
          }
        }
      }
      if (lead) {
        bulk_wait<0>();
        e_arrive_cl(peer + B_SF + 8 * wg);
        if (ty == T_GU) e_flag_add(g_fl.dep + grp(T_D, l, cb), 1 << (j / 20 * 8));
        else if (ty == T_O || !l) e_flag_add(l ? g_fl.part + cb : ty == T_O ? g_fl.dep + grp(T_GU, 0, cb) : g_fl.xn[1][cb], l ? 1 : 8);
      }
    }
    cluster_arrive(); cluster_wait();
  }
}

typedef CUresult (*PFN_encodeTiled)(CUtensorMap*, CUtensorMapDataType, cuuint32_t, void*, const cuuint64_t*, const cuuint64_t*,
                                    const cuuint32_t*, const cuuint32_t*, CUtensorMapInterleave, CUtensorMapSwizzle,
                                    CUtensorMapL2promotion, CUtensorMapFloatOOBfill);
static PFN_encodeTiled g_encode = nullptr;
static int g_sms = 0;
static CUtensorMap encode(const void* ptr, int rank, const cuuint64_t* dims, const cuuint64_t* strides, const cuuint32_t* box) {
  CUtensorMap m;
  const cuuint32_t es[5] = {1, 1, 1, 1, 1};
  g_encode(&m, CU_TENSOR_MAP_DATA_TYPE_BFLOAT16, rank, (void*)ptr, dims, strides, box, es, CU_TENSOR_MAP_INTERLEAVE_NONE,
           CU_TENSOR_MAP_SWIZZLE_128B, CU_TENSOR_MAP_L2_PROMOTION_L2_256B, CU_TENSOR_MAP_FLOAT_OOB_FILL_NONE);
  return m;
}
static CUtensorMap make_map(const void* ptr, uint64_t rows, uint64_t cols, uint32_t box_rows) {
  const cuuint64_t dims[2] = {cols, rows}, strides[1] = {cols * 2};
  const cuuint32_t box[2] = {64, box_rows};
  return encode(ptr, 2, dims, strides, box);
}
static CUtensorMap make_map_x(const void* ptr) {
  const cuuint64_t dims[3] = {DM, NSTEP * 32, 2}, strides[2] = {DM * 2, (cuuint64_t)NSTEP * 32 * DM * 2};
  const cuuint32_t box[3] = {64, 32, 2};
  return encode(ptr, 3, dims, strides, box);
}
static CUtensorMap make_map_x1(const void* ptr) {
  const cuuint64_t dims[3] = {64, 2 * NSTEP * 32, DM / 64}, strides[2] = {DM * 2, 128};
  const cuuint32_t box[3] = {64, 32, 2};
  return encode(ptr, 3, dims, strides, box);
}
static CUtensorMap make_map_wo(const void* ptr) {
  const cuuint64_t dims[5] = {DM, 2, 4, 4, NH * DH / 32}, strides[4] = {DM * 2, 8 * DM * 2, 2 * DM * 2, 32 * DM * 2};
  const cuuint32_t box[5] = {64, 2, 4, 4, 2};
  return encode(ptr, 5, dims, strides, box);
}

extern "C" void kernel_launch(void* const* d_in, const int* in_sizes, int n_in, void* d_out, int out_size) {
  const bf16 *x = (const bf16*)d_in[0], *mem0 = (const bf16*)d_in[1], *Wo = (const bf16*)d_in[5];
  if (!g_encode) {
    void* p = nullptr; cudaDriverEntryPointQueryResult q;
    cudaGetDriverEntryPoint("cuTensorMapEncodeTiled", &p, cudaEnableDefault, &q);
    g_encode = (PFN_encodeTiled)p;
    int dev = 0;
    cudaGetDevice(&dev);
    cudaDeviceGetAttribute(&g_sms, cudaDevAttrMultiProcessorCount, dev);
    cudaFuncSetAttribute(rec_kernel, cudaFuncAttributeMaxDynamicSharedMemorySize, rec::SMEM);
    cudaFuncSetAttribute(gemm_kernel, cudaFuncAttributeMaxDynamicSharedMemorySize, gm::SMEM);
  }
  void *xn, *o, *x1, *xm, *x2, *hh;
  cudaGetSymbolAddress(&xn, g_xn); cudaGetSymbolAddress(&o, g_o); cudaGetSymbolAddress(&x1, g_x1);
  cudaGetSymbolAddress(&xm, g_xm); cudaGetSymbolAddress(&x2, g_x2); cudaGetSymbolAddress(&hh, g_h);
  RecMaps R;
  for (int i = 0; i < 3; i++) R.w[i] = make_map(d_in[2 + i], DM, NH * DH, 16);
  R.wo = make_map(Wo, NH * DH, DM, 64); R.x[0] = make_map_x(xn); R.x[1] = make_map_x1(xn);
  rec_kernel<<<96, 512, rec::SMEM>>>(R, Wo, mem0, 0);
  GemmMaps G;
  G.o = make_map(o, 2 * SEQ, NH * DH, 128); G.wo = make_map_wo(Wo);
  G.x1 = make_map(x1, 2 * SEQ, DM, 64); G.x1s = make_map(x1, 2 * SEQ, DM, 128);
  G.xn = make_map((bf16*)xn + (NSTEP + LAG) * 32 * DM, SEQ, DM, 64);
  G.xm = make_map(xm, 2 * SEQ, DM, 64); G.xms = make_map(xm, 2 * SEQ, DM, 128);
  G.wg = make_map(d_in[8], DM, DF, 64); G.wu = make_map(d_in[9], DM, DF, 64); G.wd = make_map(d_in[10], DF, DM, 64);
  G.h = make_map(hh, 2 * SEQ, DF, 64); G.hs = make_map(hh, 2 * SEQ, DF, 128);
  G.x = make_map(x, SEQ, DM, 64); G.x2 = make_map(x2, SEQ, DM, 64); G.out = make_map(d_out, SEQ, DM, 64); G.outs = make_map(d_out, SEQ, DM, 128);
  cudaLaunchConfig_t cfg = {};
  cfg.gridDim = dim3(g_sms & ~1); cfg.blockDim = dim3(512); cfg.dynamicSmemBytes = gm::SMEM; cfg.stream = cudaStreamPerThread;
  cudaLaunchAttribute at;
  at.id = cudaLaunchAttributeProgrammaticStreamSerialization; at.val.programmaticStreamSerializationAllowed = 1;
  cfg.attrs = &at; cfg.numAttrs = 1;
  cudaLaunchKernelEx(&cfg, gemm_kernel, G, x);
}
```

```cpp
#include <cuda_runtime.h>
#include <cuda_bf16.h>
#include <cuda.h>
#include <stdint.h>

#define DEVI __device__ __forceinline__
typedef __nv_bfloat16 bf16;

#define LAG 16
constexpr int SEQ = 2048, DM = 1024, NH = 32, DH = 128, DF = 3584, NSEG = 64, NSTEP = NSEG + LAG;
static_assert(NSTEP % 2 == 0, "tags and slots of the exchange buffers return to their initial state");

__device__ __align__(1024) bf16 g_xn[2][NSTEP * 32 * DM];
__device__ __align__(1024) bf16 g_o[2][SEQ * NH * DH];
__device__ __align__(1024) bf16 g_x1[2][SEQ * DM];
__device__ __align__(1024) bf16 g_xm[2][SEQ * DM];
__device__ __align__(1024) bf16 g_x2[SEQ * DM];
__device__ __align__(1024) bf16 g_h[2][SEQ * DF];
__device__ __align__(1024) uint4 g_part[256 * 32 * 8];
__device__ __align__(1024) uint32_t g_ann[2][32][64];
__device__ __align__(1024) uint4 g_mem[2][2048];
__device__ __align__(128) float2 g_stat[2][2][8][128];
__host__ __device__ constexpr int grp(int type, int layer, int blk) { return layer ? 16 * type + blk : 64 + (16 * type + blk) * 32; }
struct Flags {
  int xn[2][16][32];
  int dep[64 + 48 * 32];
  int taken[64];
  int rows[32];
  int part[32];
  int ticket[32];
};
__device__ __align__(128) Flags g_fl;

DEVI uint32_t smem_u32(const void* p) { return (uint32_t)__cvta_generic_to_shared(p); }
DEVI void mbar_init(uint32_t bar, uint32_t cnt) { asm volatile("mbarrier.init.shared::cta.b64 [%0], %1;" :: "r"(bar), "r"(cnt) : "memory"); }
DEVI void mbar_expect_tx(uint32_t bar, uint32_t bytes) { asm volatile("mbarrier.arrive.expect_tx.shared::cta.b64 _, [%0], %1;" :: "r"(bar), "r"(bytes) : "memory"); }
DEVI void mbar_arrive(uint32_t bar) { asm volatile("mbarrier.arrive.shared::cta.b64 _, [%0];" :: "r"(bar) : "memory"); }
DEVI bool mbar_try(uint32_t bar, uint32_t parity) {
  uint32_t p;
  asm volatile("{.reg .pred p; mbarrier.try_wait.parity.shared::cta.b64 p, [%1], %2; selp.u32 %0, 1, 0, p;}" : "=r"(p) : "r"(bar), "r"(parity) : "memory");
  return p;
}
DEVI bool mbar_test(uint32_t bar, uint32_t parity) {
  uint32_t p;
  asm volatile("{.reg .pred p; mbarrier.test_wait.parity.shared::cta.b64 p, [%1], %2; selp.u32 %0, 1, 0, p;}" : "=r"(p) : "r"(bar), "r"(parity) : "memory");
  return p;
}
constexpr int SPIN_BUDGET = 1 << 20;
DEVI void mbar_wait(uint32_t bar, uint32_t parity, int& budget) {
  while (!mbar_try(bar, parity)) { if (--budget < 0) break; }
}
DEVI void trap_if_spent(int budget) { asm volatile("{.reg .pred p; setp.le.s32 p, %0, 0; @p trap;}" :: "r"(budget) : "memory"); }
DEVI void fault_if_spent(int budget) { asm volatile("{.reg .pred p; setp.le.s32 p, %0, 0; @p st.global.u32 [%1], 0;}" :: "r"(budget), "l"(0ull) : "memory"); }
DEVI uint32_t mapa(uint32_t addr, uint32_t rank) { uint32_t r; asm("mapa.shared::cluster.u32 %0, %1, %2;" : "=r"(r) : "r"(addr), "r"(rank)); return r; }
DEVI void cluster_arrive() { asm volatile("barrier.cluster.arrive.release.aligned;" ::: "memory"); }
DEVI void cluster_wait() { asm volatile("barrier.cluster.wait.acquire.aligned;" ::: "memory"); }
DEVI void fence_mbar_init() { asm volatile("fence.mbarrier_init.release.cluster;" ::: "memory"); }
DEVI void fence_proxy_async() { asm volatile("fence.proxy.async.shared::cta;" ::: "memory"); }
DEVI void tma_load_2d(uint32_t dst, const CUtensorMap* m, int c0, int c1, uint32_t bar) {
  asm volatile("cp.async.bulk.tensor.2d.shared::cluster.global.mbarrier::complete_tx::bytes [%0], [%1, {%3, %4}], [%2];"
    :: "r"(dst), "l"(m), "r"(bar), "r"(c0), "r"(c1) : "memory");
}
DEVI void tma_load_5d(uint32_t dst, const CUtensorMap* m, int c0, int c4, uint32_t bar) {
  asm volatile("cp.async.bulk.tensor.5d.shared::cluster.global.mbarrier::complete_tx::bytes [%0], [%1, {%3, %5, %5, %5, %4}], [%2];"
    :: "r"(dst), "l"(m), "r"(bar), "r"(c0), "r"(c4), "r"(0) : "memory");
}
DEVI void tma_prefetch_2d(const CUtensorMap* m, int c0, int c1) {
  asm volatile("cp.async.bulk.prefetch.tensor.2d.L2.global [%0, {%1, %2}];" :: "l"(m), "r"(c0), "r"(c1) : "memory");
}
DEVI void tma_prefetch_5d(const CUtensorMap* m, int c0, int c4) {
  asm volatile("cp.async.bulk.prefetch.tensor.5d.L2.global [%0, {%1, %3, %3, %3, %2}];" :: "l"(m), "r"(c0), "r"(c4), "r"(0) : "memory");
}
#define ELECT "{.reg .pred p; elect.sync _|p, 0xffffffff;\n @p "
DEVI void e_expect_tx(uint32_t bar, uint32_t bytes) { asm volatile(ELECT "mbarrier.arrive.expect_tx.shared::cta.b64 _, [%0], %1;}" :: "r"(bar), "r"(bytes) : "memory"); }
DEVI void e_arrive(uint32_t bar) { asm volatile(ELECT "mbarrier.arrive.shared::cta.b64 _, [%0];}" :: "r"(bar) : "memory"); }
DEVI void e_arrive_cl(uint32_t bar) { asm volatile(ELECT "mbarrier.arrive.shared::cluster.b64 _, [%0];}" :: "r"(bar) : "memory"); }
DEVI void e_tma_2d(uint32_t dst, const CUtensorMap* m, int c0, int c1, uint32_t bar) {
  asm volatile(ELECT "cp.async.bulk.tensor.2d.shared::cluster.global.mbarrier::complete_tx::bytes [%0], [%1, {%3, %4}], [%2];}"
    :: "r"(dst), "l"(m), "r"(bar), "r"(c0), "r"(c1) : "memory");
}
DEVI void e_tma_2d_mc(uint32_t dst, const CUtensorMap* m, int c0, int c1, uint32_t bar) {
  asm volatile(ELECT "cp.async.bulk.tensor.2d.shared::cluster.global.mbarrier::complete_tx::bytes.multicast::cluster [%0], [%1, {%3, %4}], [%2], %5;}"
    :: "r"(dst), "l"(m), "r"(bar), "r"(c0), "r"(c1), "h"((unsigned short)3) : "memory");
}
DEVI void e_st_async32(uint32_t a, uint32_t x, uint32_t bar) {
  asm volatile(ELECT "st.async.weak.shared::cluster.mbarrier::complete_tx::bytes.b32 [%0], %1, [%2];}" :: "r"(a), "r"(x), "r"(bar) : "memory");
}
DEVI void e_tma_store_2d(const CUtensorMap* m, uint32_t src, int c0, int c1) {
  asm volatile(ELECT "cp.async.bulk.tensor.2d.global.shared::cta.bulk_group [%0, {%2, %3}], [%1];}" :: "l"(m), "r"(src), "r"(c0), "r"(c1) : "memory");
}
DEVI void e_flag_add(int* p, int v = 1) {
  asm volatile("{.reg .pred p; elect.sync _|p, 0xffffffff;\n fence.proxy.async.global; @p red.release.gpu.global.add.s32 [%0], %1;}" :: "l"(p), "r"(v) : "memory");
}
DEVI int e_ticket(int* p) { int v = 0; asm volatile(ELECT "atom.relaxed.gpu.global.add.s32 %0, [%1], 1;}" : "+r"(v) : "l"(p) : "memory"); __syncwarp(); return v; }
DEVI int bcast(int v) { return __reduce_max_sync(0xffffffffu, v); }
DEVI int ld_relaxed(const int* p) { int v; asm volatile("ld.relaxed.gpu.global.s32 %0, [%1];" : "=r"(v) : "l"(p) : "memory"); return v; }
DEVI int ld_acquire(const int* p) { int v; asm volatile("ld.acquire.gpu.global.s32 %0, [%1];" : "=r"(v) : "l"(p) : "memory"); return __shfl_sync(0xffffffffu, v, 0); }
DEVI void e_tma_3d(uint32_t dst, const CUtensorMap* m, int c0, int c1, int c2, uint32_t bar) {
  asm volatile(ELECT "cp.async.bulk.tensor.3d.shared::cluster.global.mbarrier::complete_tx::bytes [%0], [%1, {%3, %4, %5}], [%2];}"
    :: "r"(dst), "l"(m), "r"(bar), "r"(c0), "r"(c1), "r"(c2) : "memory");
}
DEVI void e_tma_5d(uint32_t dst, const CUtensorMap* m, int c0, int c4, uint32_t bar) {
  asm volatile(ELECT "cp.async.bulk.tensor.5d.shared::cluster.global.mbarrier::complete_tx::bytes [%0], [%1, {%3, %5, %5, %5, %4}], [%2];}"
    :: "r"(dst), "l"(m), "r"(bar), "r"(c0), "r"(c4), "r"(0) : "memory");
}
DEVI void e_bulk_g2s(uint32_t dst, const void* src, uint32_t bytes, uint32_t bar) {
  asm volatile(ELECT "cp.async.bulk.shared::cluster.global.mbarrier::complete_tx::bytes [%0], [%1], %2, [%3];}" :: "r"(dst), "l"(src), "r"(bytes), "r"(bar) : "memory");
}
DEVI void e_prefetch(const void* src, uint32_t bytes) {
  asm volatile(ELECT "cp.async.bulk.prefetch.L2.global [%0], %1;}" :: "l"(src), "r"(bytes) : "memory");
}
DEVI void bulk_commit() { asm volatile("cp.async.bulk.commit_group;" ::: "memory"); }
template<int N> DEVI void bulk_wait_read() { asm volatile("cp.async.bulk.wait_group.read %0;" :: "n"(N) : "memory"); }
template<int N> DEVI void bulk_wait() { asm volatile("cp.async.bulk.wait_group %0;" :: "n"(N) : "memory"); }
template<int ID, int N> DEVI void nbar_sync() { asm volatile("bar.sync %0, %1;" :: "n"(ID), "n"(N) : "memory"); }
template<int ID, int N> DEVI void nbar_arrive() { asm volatile("bar.arrive %0, %1;" :: "n"(ID), "n"(N) : "memory"); }
DEVI void nbar_sync_r(int id, int n) { asm volatile("bar.sync %0, %1;" :: "r"(id), "r"(n) : "memory"); }
DEVI void nbar_arrive_r(int id, int n) { asm volatile("bar.arrive %0, %1;" :: "r"(id), "r"(n) : "memory"); }
template<int R> DEVI void reg_inc() { asm volatile("setmaxnreg.inc.sync.aligned.u32 %0;" :: "n"(R)); }
template<int R> DEVI void reg_dec() { asm volatile("setmaxnreg.dec.sync.aligned.u32 %0;" :: "n"(R)); }
DEVI void wg_fence() { asm volatile("wgmma.fence.sync.aligned;" ::: "memory"); }
DEVI void wg_commit() { asm volatile("wgmma.commit_group.sync.aligned;" ::: "memory"); }
template<int N> DEVI void wg_wait() { asm volatile("wgmma.wait_group.sync.aligned %0;" :: "n"(N) : "memory"); }
DEVI uint32_t pack_bf16(float lo, float hi) { uint32_t r; asm("cvt.rn.bf16x2.f32 %0, %1, %2;" : "=r"(r) : "f"(hi), "f"(lo)); return r; }
DEVI float bf_lo(uint32_t v) { return __uint_as_float(v << 16); }
DEVI float bf_hi(uint32_t v) { return __uint_as_float(v & 0xffff0000u); }
DEVI uint32_t movmat(uint32_t a) { uint32_t r; asm volatile("movmatrix.sync.aligned.m8n8.trans.b16 %0, %1;" : "=r"(r) : "r"(a)); return r; }
DEVI void ldsm4(uint32_t addr, uint32_t& r0, uint32_t& r1, uint32_t& r2, uint32_t& r3) {
  asm volatile("ldmatrix.sync.aligned.m8n8.x4.shared.b16 {%0,%1,%2,%3}, [%4];" : "=r"(r0), "=r"(r1), "=r"(r2), "=r"(r3) : "r"(addr) : "memory");
}
DEVI void ldsm4t(uint32_t addr, uint32_t& r0, uint32_t& r1, uint32_t& r2, uint32_t& r3) {
  asm volatile("ldmatrix.sync.aligned.m8n8.x4.trans.shared.b16 {%0,%1,%2,%3}, [%4];" : "=r"(r0), "=r"(r1), "=r"(r2), "=r"(r3) : "r"(addr) : "memory");
}
DEVI void stsm4(uint32_t addr, uint32_t r0, uint32_t r1, uint32_t r2, uint32_t r3) {
  asm volatile("stmatrix.sync.aligned.m8n8.x4.shared.b16 [%0], {%1,%2,%3,%4};" :: "r"(addr), "r"(r0), "r"(r1), "r"(r2), "r"(r3) : "memory");
}
DEVI uint4 lds128(uint32_t a) { uint4 v; asm volatile("ld.shared.v4.u32 {%0,%1,%2,%3}, [%4];" : "=r"(v.x), "=r"(v.y), "=r"(v.z), "=r"(v.w) : "r"(a) : "memory"); return v; }
DEVI uint32_t lds32v(uint32_t a) { uint32_t v; asm volatile("ld.volatile.shared.u32 %0, [%1];" : "=r"(v) : "r"(a) : "memory"); return v; }
DEVI void sts32v(uint32_t a, uint32_t v) { asm volatile("st.volatile.shared.u32 [%0], %1;" :: "r"(a), "r"(v) : "memory"); }
DEVI void st_async128(uint32_t a, uint32_t x, uint32_t y, uint32_t z, uint32_t w, uint32_t bar) {
  asm volatile("st.async.weak.shared::cluster.mbarrier::complete_tx::bytes.v4.b32 [%0], {%1,%2,%3,%4}, [%5];" :: "r"(a), "r"(x), "r"(y), "r"(z), "r"(w), "r"(bar) : "memory");
}
DEVI void st_async32(uint32_t a, uint32_t x, uint32_t bar) {
  asm volatile("st.async.weak.shared::cluster.mbarrier::complete_tx::bytes.b32 [%0], %1, [%2];" :: "r"(a), "r"(x), "r"(bar) : "memory");
}
DEVI void st_cl128(bool own, uint32_t a, uint32_t x, uint32_t y, uint32_t z, uint32_t w, uint32_t bar) {
  asm volatile("{.reg .pred p; setp.ne.u32 p, %6, 0; @p st.shared.v4.b32 [%0], {%1,%2,%3,%4};\n"
               "@!p st.async.weak.shared::cluster.mbarrier::complete_tx::bytes.v4.b32 [%0], {%1,%2,%3,%4}, [%5];}"
               :: "r"(a), "r"(x), "r"(y), "r"(z), "r"(w), "r"(bar), "r"((uint32_t)own) : "memory");
}
DEVI void st_cl32(bool own, uint32_t a, uint32_t x, uint32_t bar) {
  asm volatile("{.reg .pred p; setp.ne.u32 p, %3, 0; @p st.shared.b32 [%0], %1;\n"
               "@!p st.async.weak.shared::cluster.mbarrier::complete_tx::bytes.b32 [%0], %1, [%2];}" :: "r"(a), "r"(x), "r"(bar), "r"((uint32_t)own) : "memory");
}
DEVI uint4 ldg_rlx128(const void* p) {
  uint4 v;
  asm volatile("ld.relaxed.gpu.global.v4.b32 {%0,%1,%2,%3}, [%4];" : "=r"(v.x), "=r"(v.y), "=r"(v.z), "=r"(v.w) : "l"(p) : "memory");
  return v;
}
DEVI void stg_rlx128(void* p, uint32_t x, uint32_t y, uint32_t z, uint32_t w) {
  asm volatile("st.relaxed.gpu.global.v4.b32 [%0], {%1,%2,%3,%4};" :: "l"(p), "r"(x), "r"(y), "r"(z), "r"(w) : "memory");
}
DEVI void stg128(void* p, uint32_t x, uint32_t y, uint32_t z, uint32_t w) {
  asm volatile("st.global.v4.b32 [%0], {%1,%2,%3,%4};" :: "l"(p), "r"(x), "r"(y), "r"(z), "r"(w) : "memory");
}
DEVI void stg_rlx64(void* p, uint32_t x, uint32_t y) { asm volatile("st.relaxed.gpu.global.v2.b32 [%0], {%1,%2};" :: "l"(p), "r"(x), "r"(y) : "memory"); }
DEVI void stg_rlx32(void* p, uint32_t x) { asm volatile("st.relaxed.gpu.global.b32 [%0], %1;" :: "l"(p), "r"(x) : "memory"); }
DEVI uint32_t clock32() { uint32_t c; asm volatile("mov.u32 %0, %%clock;" : "=r"(c) :: "memory"); return c; }
DEVI uint32_t gtime() { uint32_t c; asm volatile("mov.u32 %0, %%globaltimer_lo;" : "=r"(c) :: "memory"); return c; }
DEVI void wait_time(uint32_t t, int& budget) { while ((int)(gtime() - t) < 0 && --budget > 0) {} }
DEVI uint2 ldg_rlx64(const void* p) { uint2 v; asm volatile("ld.relaxed.gpu.global.v2.b32 {%0,%1}, [%2];" : "=r"(v.x), "=r"(v.y) : "l"(p) : "memory"); return v; }
DEVI void sts16(uint32_t a, uint32_t x) { asm volatile("st.shared.b16 [%0], %1;" :: "r"(a), "h"((unsigned short)x) : "memory"); }
DEVI void sts128(uint32_t a, uint32_t x) { asm volatile("st.shared.v4.b32 [%0], {%1,%1,%1,%1};" :: "r"(a), "r"(x) : "memory"); }
DEVI void arrive_if_eq(uint32_t bar, int a, int b) { asm volatile("{.reg .pred p; setp.eq.s32 p, %1, %2; @p mbarrier.arrive.shared::cta.b64 _, [%0];}" :: "r"(bar), "r"(a), "r"(b) : "memory"); }
DEVI void arrive_cl_if_eq(uint32_t bar, int a, int b) { asm volatile("{.reg .pred p; setp.eq.s32 p, %1, %2; @p mbarrier.arrive.shared::cluster.b64 _, [%0];}" :: "r"(bar), "r"(a), "r"(b) : "memory"); }
template<int ID, int N> DEVI bool nbar_or(bool x) {
  uint32_t r;
  asm volatile("{.reg .pred p, q; setp.ne.u32 p, %1, 0; bar.red.or.pred q, %2, %3, p; selp.u32 %0, 1, 0, q;}" : "=r"(r) : "r"((uint32_t)x), "n"(ID), "n"(N) : "memory");
  return __any_sync(0xffffffffu, r);
}
DEVI void spin_until(uint32_t t0, int d) { while ((int)(clock32() - t0) < d) {} }
DEVI void flag_wait(const int* p, int n, int& budget) {
  while (ld_acquire(p) < n && --budget > 0) __nanosleep(128);
  asm volatile("fence.proxy.async.global;" ::: "memory");
}

#define F4(C, o)  C(d[o+0]), C(d[o+1]), C(d[o+2]), C(d[o+3])
#define F8(C, o)  F4(C, o), F4(C, o+4)
#define F32(C, o) F8(C, o), F8(C, o+8), F8(C, o+16), F8(C, o+24)
#define R4  "{%0,%1,%2,%3}"
#define R8  "{%0,%1,%2,%3,%4,%5,%6,%7}"
#define R16 "{%0,%1,%2,%3,%4,%5,%6,%7,%8,%9,%10,%11,%12,%13,%14,%15}"
#define R20 "{%0,%1,%2,%3,%4,%5,%6,%7,%8,%9,%10,%11,%12,%13,%14,%15,%16,%17,%18,%19}"
#define R32 "{%0,%1,%2,%3,%4,%5,%6,%7,%8,%9,%10,%11,%12,%13,%14,%15,%16,%17,%18,%19,%20,%21,%22,%23,%24,%25,%26,%27,%28,%29,%30,%31}"
#define R64 "{%0,%1,%2,%3,%4,%5,%6,%7,%8,%9,%10,%11,%12,%13,%14,%15,%16,%17,%18,%19,%20,%21,%22,%23,%24,%25,%26,%27,%28,%29,%30,%31," \
  "%32,%33,%34,%35,%36,%37,%38,%39,%40,%41,%42,%43,%44,%45,%46,%47,%48,%49,%50,%51,%52,%53,%54,%55,%56,%57,%58,%59,%60,%61,%62,%63}"
template<uint32_t OFF, uint32_t LBO, uint32_t SBO, uint32_t SW, int T> struct Op {
  static constexpr uint32_t lo = (OFF >> 4) | ((LBO >> 4) << 16), hi = (SBO >> 4) | (SW << 30);
  static constexpr int t = T;
};
DEVI uint32_t desc_base(uint32_t addr) { return (addr & 0x3FFFF) >> 4; }
#define RS_ASM(SHAPE, REGS, A0, A1, A2, A3, B, LO, HI, T, SD) \
  "{.reg .b64 tb; .reg .b32 lb; add.u32 lb, " B ", " LO "; mov.b64 tb, {lb, " HI "};\n" \
  "wgmma.mma_async.sync.aligned." SHAPE ".f32.bf16.bf16 " REGS ", {" A0 "," A1 "," A2 "," A3 "}, tb, " SD ", 1, 1, " T ";}"
#define WG_RS(NAME, SHAPE, REGS, LIST, ...) \
  template<int ACC, class OB> DEVI void NAME(float* d, const uint32_t* a, uint32_t b) { \
    if (ACC) asm volatile(RS_ASM(SHAPE, REGS, __VA_ARGS__) \
      : LIST("+f") : "r"(a[0]), "r"(a[1]), "r"(a[2]), "r"(a[3]), "r"(b), "n"(OB::lo), "n"(OB::hi), "n"(OB::t), "n"(ACC & 1)); \
    else asm volatile(RS_ASM(SHAPE, REGS, __VA_ARGS__) \
      : LIST("=f") : "r"(a[0]), "r"(a[1]), "r"(a[2]), "r"(a[3]), "r"(b), "n"(OB::lo), "n"(OB::hi), "n"(OB::t), "n"(0)); \
  }
#define SS_ASM(SHAPE, REGS, A, B, LA, HA, TA, LB, HB, TB, SD) \
  "{.reg .b64 ta, tb; .reg .b32 la, lb; add.u32 la, " A ", " LA "; mov.b64 ta, {la, " HA "}; add.u32 lb, " B ", " LB "; mov.b64 tb, {lb, " HB "};\n" \
  "wgmma.mma_async.sync.aligned." SHAPE ".f32.bf16.bf16 " REGS ", ta, tb, " SD ", 1, 1, " TA ", " TB ";}"
#define WG_SS(NAME, SHAPE, REGS, LIST, ...) \
  template<int ACC, class OA, class OB> DEVI void NAME(float* d, uint32_t a, uint32_t b) { \
    if (ACC) asm volatile(SS_ASM(SHAPE, REGS, __VA_ARGS__) \
      : LIST("+f") : "r"(a), "r"(b), "n"(OA::lo), "n"(OA::hi), "n"(OA::t), "n"(OB::lo), "n"(OB::hi), "n"(OB::t), "n"(ACC & 1)); \
    else asm volatile(SS_ASM(SHAPE, REGS, __VA_ARGS__) \
      : LIST("=f") : "r"(a), "r"(b), "n"(OA::lo), "n"(OA::hi), "n"(OA::t), "n"(OB::lo), "n"(OB::hi), "n"(OB::t), "n"(0)); \
  }
#define L4(C)  F4(C, 0)
#define L8(C)  F8(C, 0)
#define L16(C) F8(C, 0), F8(C, 8)
#define L20(C) F8(C, 0), F8(C, 8), F4(C, 16)
#define L32(C) F32(C, 0)
WG_RS(wg_rs8, "m64n8k16", R4, L4, "%4", "%5", "%6", "%7", "%8", "%9", "%10", "%11", "%12")
WG_RS(wg_rs16, "m64n16k16", R8, L8, "%8", "%9", "%10", "%11", "%12", "%13", "%14", "%15", "%16")
WG_RS(wg_rs32, "m64n32k16", R16, L16, "%16", "%17", "%18", "%19", "%20", "%21", "%22", "%23", "%24")
WG_SS(wg_ss32, "m64n32k16", R16, L16, "%16", "%17", "%18", "%19", "%20", "%21", "%22", "%23", "%24")
WG_RS(wg_rs64, "m64n64k16", R32, L32, "%32", "%33", "%34", "%35", "%36", "%37", "%38", "%39", "%40")
WG_SS(wg_ss8, "m64n8k16", R4, L4, "%4", "%5", "%6", "%7", "%8", "%9", "%10", "%11", "%12")
WG_SS(wg_ss16, "m64n16k16", R8, L8, "%8", "%9", "%10", "%11", "%12", "%13", "%14", "%15", "%16")
WG_SS(wg_ss40, "m64n40k16", R20, L20, "%20", "%21", "%22", "%23", "%24", "%25", "%26", "%27", "%28")
WG_SS(wg_ss64, "m64n64k16", R32, L32, "%32", "%33", "%34", "%35", "%36", "%37", "%38", "%39", "%40")
#define L64(C) F32(C, 0), F32(C, 32)
WG_SS(wg_ss128, "m64n128k16", R64, L64, "%64", "%65", "%66", "%67", "%68", "%69", "%70", "%71", "%72")
template<int I> struct IC { __host__ __device__ constexpr operator int() const { return I; } };
template<int I, int N, class F> DEVI void sfor(F&& f) {
  if constexpr (I < N) { f(IC<I>{}); sfor<I + 1, N>(f); }
}

#define R_CL 6
namespace rec {
constexpr int NHI = 36, NLO = 5, NRS = NHI + NLO, NSS = 64 - NRS;
constexpr uint32_t WS = 0;
constexpr uint32_t WO = 2 * NSS * 2048;
constexpr uint32_t RING = WO + 65536;
constexpr uint32_t QB = RING + 40960, RG = 2080, POSQ = 0x64210, POSK = 0xB9753, POSV = 0xEDCA8;
#define JA 2
constexpr uint32_t WA = QB;
constexpr uint32_t OM = QB + 9 * RG, OMS = 2 * RG;
constexpr uint32_t OM2 = QB + 16384, OM2S = 2048;
constexpr uint32_t WH = QB + 20480;
constexpr uint32_t B_PART = QB + 15 * RG - 32;
constexpr uint32_t PM0 = QB + 16384, PM1 = QB + 15 * RG, PM2 = PM1 + 256;
constexpr uint32_t BARS = PM2 + 128;
constexpr uint32_t B_FULL = BARS, B_EMPTY = BARS + 40, B_MLAND = BARS + 80, B_QK = BARS + 112, B_V = BARS + 120, B_OM = BARS + 128,
                   B_WA = BARS + 136, B_SDONE = BARS + 144, B_BFREE = BARS + 152, B_W1 = PM1, B_W2 = PM1 + 8, B_WO = PM1 + 16;
constexpr uint32_t SMEM = BARS + 160;
static_assert(SMEM <= 232448 && QB % 1024 == 0, "smem map");
constexpr int R1 = (PM1 - WO) / 4096;
constexpr int NB_WO = 1, NB_ST = 2, NB_P = 3, NB_TR = 4, NB_X = 5, NB_G = 6, NB_G1 = 7, NB_G2 = 8, NB_G4 = 9, NB_S = 10;
__host__ __device__ constexpr bool is_lo(int j) { return j % 12 == 8; }
__host__ __device__ constexpr int lo_before(int j) { return (j + 3) / 12; }
__host__ __device__ constexpr int ss_before(int j) { return (j - lo_before(j)) * NSS / (64 - NLO); }
__host__ __device__ constexpr bool is_ss(int j) { return ss_before(j + 1) != ss_before(j); }
__host__ __device__ constexpr int reg_idx(int j) { return is_lo(j) ? NHI + lo_before(j) : j - ss_before(j) - lo_before(j); }
#define LOQ(i) ((0x12010 >> (4 * (i))) & 3)
template<int j> using OpW = Op<WS + ss_before(j) * 2048, 16, 1024, 1, 1>;
#define P_G1 1
#define P_G2 3
#define P_G2L 0
#define P_OS 1
#define P_NA 6
#define P_G4 10
#define P_G5 12
#define P_FW 0
#define P_SEND 0xff3f2f10u
#define P_WB 2
#define P_WOL 0
#define P_G4L 0
#define P_S1 1
#define P_S2 2
#define P_S0 3
#define P_MB 0
#define P_S4 5
#define P_S5 6
constexpr uint32_t SLOT1 = 0x32410324, USE1 = 0x22111110;
DEVI bool single(int s) { return s < LAG - 1 || s >= NSEG - 1; }
#define TUN(i, v) (v)
}
#define PROFW(wq, i)
DEVI uint32_t mapr(int h, uint32_t addr, int rank) { return mapa(addr, rank + (R_CL == 6 ? (h & 1) * 3 : 0)); }
template<int N> DEVI void pin(float* d) {
#pragma unroll
  for (int i = 0; i < N; i++) asm volatile("" : "+f"(d[i]) :: "memory");
}
DEVI void keep(const void* a) { asm volatile("{.reg .pred p; setp.eq.u64 p, %0, 0; vote.sync.any.pred p, p, 0xffffffff; @p exit;}" :: "l"(a) : "memory"); }
DEVI int lane_reg() { return __shfl_sync(0xffffffffu, threadIdx.x & 31, threadIdx.x & 31); }
#define LANE_NOW [[maybe_unused]] const int lane = lane0 + ((uint32_t)budget >> 30), g = lane >> 2, c = lane & 3

DEVI void rec_proj(const uint32_t sb, const int h, const int rank, const int w, const CUtensorMap* mW, const CUtensorMap* mWo, const uint32_t zero) {
  using namespace rec;
  const int lane0 = lane_reg(), wg = w >> 2, ww = w & 3;
  int budget = SPIN_BUDGET;
  uint32_t wr[NRS * 4];
  {
    LANE_NOW;
    const uint32_t wsw = ((lane & 7) + (lane >> 4) * 8) * 128 + (((ww * 2 + ((lane >> 3) & 1)) ^ (lane & 7)) << 4);
    mbar_wait(sb + B_W1, 0, budget);
#pragma unroll
    for (int r = 0; r < R1; r++) ldsm4t(sb + WO + (wg * R1 + r) * 2048 + wsw, wr[4*r], wr[4*r+1], wr[4*r+2], wr[4*r+3]);
    fence_proxy_async();
    nbar_sync<NB_ST, 256>();
    if (w == 0) {
      if (lane == 0) { mbar_expect_tx(sb + B_W2, (NRS - R1) * 4096); mbar_expect_tx(sb + B_WO, rank == 2 ? 65536 + 16384 + 8192 : 65536); }
      __syncwarp();
      for (int i = lane; i < 128; i += 32) {
        const int j = i & 63, t = i >> 6, r = reg_idx(j);
        if (!is_ss(j) && r >= R1) tma_load_2d(sb + RING + (t * (NRS - R1) + r - R1) * 2048, mW, h * DH + t * 64, j * 16, sb + B_W2);
      }
      const int t0 = (rank + 1) % 3;
      if (lane < 8) tma_load_2d(sb + WO + lane * 8192, mWo, (3 * ((lane >> 1) + (lane >> 1 >= JA)) + t0) * 64, h * DH + (lane & 1) * 64, sb + B_WO);
      else if (rank == 2 && lane < 11) tma_load_2d(lane < 10 ? sb + WA + (lane - 8) * 8192 : sb + WH, mWo, lane < 10 ? 3 * JA * 64 : 15 * 64, h * DH + (lane > 8) * 64, sb + B_WO);
    }
    mbar_wait(sb + B_W2, 0, budget);
#pragma unroll
    for (int r = R1; r < NRS; r++) ldsm4t(sb + RING + (wg * (NRS - R1) + r - R1) * 2048 + wsw, wr[4*r], wr[4*r+1], wr[4*r+2], wr[4*r+3]);
    fence_proxy_async();
    cluster_arrive(); cluster_wait();
  }
  const uint32_t d0 = desc_base(sb), da = d0 + wg * (NSS * 128);
  const uint32_t pos = rank == 0 ? POSQ : rank == 1 ? POSK : POSV, bar = rank == 2 ? B_V : B_QK;
  uint32_t stg[3][4] = {}, pk[16] = {};
  auto stage = [&](uint32_t* t, int r) {
#pragma unroll
    for (int i = 0; i < 4; i++) asm volatile("xor.b32 %0, %1, %2;" : "+r"(t[i]) : "r"(wr[4 * r + i]), "r"(zero));
  };
#pragma unroll 1
  for (int s = -1; s < NSTEP; s++) {
    const uint32_t fl = single(s) ? (s + 1) & 1 : 0;
    if (s >= 0) {
      float d[8];
      stage(stg[0], NHI);
      mbar_wait(sb + B_FULL, 0, budget);
      PROFW(0, 16);
      sfor<0, 8>([&](auto E) {
        constexpr int e = E, q = e >> 1;
        wg_fence();
        sfor<8 * e, 8 * e + 8>([&](auto J) {
          constexpr int j = J;
          typedef Op<RING + j * 512, 256, 128, 0, 1> OB;
          if constexpr (is_ss(j)) wg_ss16<j != 0, OpW<j>, OB>(d, da, d0);
          else wg_rs16<j != 0, OB>(d, is_lo(j) ? stg[LOQ(lo_before(j))] : wr + 4 * reg_idx(j), d0);
        });
        wg_commit();
        if constexpr (e == 0) { if (s > 0) mbar_wait(sb + B_BFREE, (s & 1) ^ 1, budget); }
        if constexpr (e > 0 && !(e & 1)) {
          wg_wait<1>();
          arrive_if_eq(sb + B_EMPTY + 8 * (q - 1), lane0, ww * 32);
        }
        if constexpr (e < 6 && !(e & 1)) sfor<lo_before(16 * q + 16), lo_before(16 * q + 32)>([&](auto I) { constexpr int i = I; stage(stg[LOQ(i)], NHI + i); });
        if constexpr (e < 6 && (e & 1) == P_FW) mbar_wait(sb + B_FULL + 8 * (q + 1), q ? fl : 0, budget);
        if constexpr (((P_SEND >> (4 * e)) & 15) < 4) {
          constexpr int n = (P_SEND >> (4 * e)) & 15;
          LANE_NOW;
          const uint32_t r = mapr(h, sb, n >> 1);
          uint32_t t[4];
#pragma unroll
          for (int i = 0; i < 4; i++) { if (n == 0) t[i] = pk[i]; else asm volatile("xor.b32 %0, %1, %2;" : "=r"(t[i]) : "r"(pk[4*n+i]), "r"(zero)); }
          st_cl128(rank == n >> 1, r + QB + ((pos >> (4 + 4 * c)) & 15) * RG + w * 256 + (n & 1) * 128 + g * 16, t[0], t[1], t[2], t[3], r + bar);
        }
      });
      LANE_NOW;
      const uint32_t dst = QB + (pos & 15) * RG + w * 256 + lane * 4;
      wg_wait<0>();
      pin<8>(d);
      {
        const uint32_t x0 = pack_bf16(d[0], d[1]), x1 = pack_bf16(d[2], d[3]), y0 = pack_bf16(d[4], d[5]), y1 = pack_bf16(d[6], d[7]);
        const uint32_t r = mapr(h, sb, rank == 0);
        if (rank < 2) { sts32v(sb + dst, rank ? y0 : x0); sts32v(sb + dst + 128, rank ? y1 : x1); fence_proxy_async(); }
        st_async32(r + dst, rank ? x0 : y0, r + bar); st_async32(r + dst + 128, rank ? x1 : y1, r + bar);
        if (rank < 2) e_arrive(sb + B_QK);
        else { const uint32_t r1 = mapr(h, sb, 1); st_async32(r1 + dst, y0, r1 + bar); st_async32(r1 + dst + 128, y1, r1 + bar); }
      }
      PROFW(0, 17);
      if (s == NSTEP - 1) break;
      arrive_if_eq(sb + B_EMPTY + 24, lane0, ww * 32);
    } else e_arrive(sb + B_EMPTY + 8 * ww);
    const bool gate = rank < 2 && s >= 0;
    if (single(s)) {
      float d[16];
      sfor<0, 8>([&](auto C) {
        constexpr int cc = C, sl = (SLOT1 >> (4 * cc)) & 15;
        if constexpr (cc == 0) mbar_wait(sb + B_FULL + 8 * sl, 0, budget);
        if constexpr (cc == P_S1) { if (gate) nbar_sync<NB_G1, 384>(); }
        if constexpr (cc == P_S2) { if (gate) nbar_sync<NB_G2, 384>(); }
        if constexpr (cc == P_S0) nbar_sync<NB_WO, 384>();
        if constexpr (cc == P_S4 || cc == P_S5) { if (gate && cc == (rank ? P_S5 : P_S4)) nbar_sync<NB_G4, 384>(); }
        if constexpr (lo_before(cc * 8 + 8) != lo_before(cc * 8)) stage(stg[0], NHI + lo_before(cc * 8));
        wg_fence();
        sfor<0, 8>([&](auto I) {
          constexpr int i = I, j = cc * 8 + i;
          typedef Op<RING + sl * 8192 + (i >> 2) * 4096 + (i & 3) * 32, 16, 1024, 1, 0> OB;
          if constexpr (is_ss(j)) wg_ss32<j != 0, OpW<j>, OB>(d, da, d0);
          else wg_rs32<j != 0, OB>(d, is_lo(j) ? stg[0] : wr + 4 * reg_idx(j), d0);
        });
        wg_commit();
        if constexpr (cc < 7) {
          constexpr int sn = (SLOT1 >> (4 * cc + 4)) & 15;
          mbar_wait(sb + B_FULL + 8 * sn, ((USE1 >> (4 * cc + 4)) & 1) ^ (sn >> 1 == 1 ? fl : 0), budget);
        }
        wg_wait<0>();
        arrive_if_eq(sb + B_EMPTY + 8 * sl, lane0, ww * 32);
      });
      pin<16>(d);
      PROFW(0, 20);
#pragma unroll
      for (int i = 0; i < 8; i++) pk[i] = pk[8 + i] = pack_bf16(d[4 * (i & 3) + ((i >> 1) & 2)], d[4 * (i & 3) + ((i >> 1) & 2) + 1]);
      continue;
    }
    float d[32];
    sfor<0, 16>([&](auto C) {
      constexpr int cc = C, sl = (cc + 4) % 5;
      if constexpr (cc == 0) mbar_wait(sb + B_FULL + 8 * sl, 0, budget);
      if constexpr (cc == P_G1) { if (gate) nbar_sync<NB_G1, 384>(); }
      if constexpr (cc == P_G2) { if (gate) nbar_sync<NB_G2, 384>(); }
      if constexpr (cc == P_NA) {
        PROFW(0, 18);
        nbar_sync<NB_WO, 384>();
      }
      if constexpr (cc == P_G4 || cc == P_G5) { if (gate && cc == (rank ? P_G5 : P_G4)) nbar_sync<NB_G4, 384>(); }
      wg_fence();
      sfor<0, 4>([&](auto I) {
        constexpr int i = I, j = cc * 4 + i;
        typedef Op<RING + sl * 8192 + i * 32, 16, 1024, 1, 0> OB;
        if constexpr (is_ss(j)) wg_ss64<j != 0, OpW<j>, OB>(d, da, d0);
        else wg_rs64<j != 0, OB>(d, is_lo(j) ? stg[0] : wr + 4 * reg_idx(j), d0);
      });
      wg_commit();
      if constexpr (cc == P_NA) PROFW(0, 19);
      if constexpr (cc < 15) {
        if constexpr (is_lo(cc * 4 + 4)) stage(stg[0], reg_idx(cc * 4 + 4));
        mbar_wait(sb + B_FULL + 8 * ((sl + 1) % 5), ((cc + 5) / 5) & 1, budget);
      }
      wg_wait<0>();
      arrive_if_eq(sb + B_EMPTY + 8 * sl, lane0, ww * 32);
    });
    pin<32>(d);
    PROFW(0, 20);
#pragma unroll
    for (int i = 0; i < 16; i++) pk[i] = pack_bf16(d[16 * (i >> 3) + 4 * (i & 3) + ((i >> 1) & 2)], d[16 * (i >> 3) + 4 * (i & 3) + ((i >> 1) & 2) + 1]);
  }
}

DEVI float softmax_row(float* v, uint32_t* p) {
  constexpr float SC = 0.08838834764831845f * 1.4426950408889634f;
  float m = fmaxf(fmaxf(fmaxf(fmaxf(v[0], v[1]), fmaxf(v[2], v[3])), fmaxf(fmaxf(v[4], v[5]), fmaxf(v[6], v[7]))), fmaxf(v[8], v[9]));
  m = fmaxf(m, __shfl_xor_sync(0xffffffffu, m, 1));
  m = fmaxf(m, __shfl_xor_sync(0xffffffffu, m, 2));
  const float ms = -m * SC, mh = fmaf(m, -SC, -1.f);
#pragma unroll
  for (int i = 0; i < 10; i++) asm("ex2.approx.ftz.f32 %0, %1;" : "=f"(v[i]) : "f"(fmaf(v[i], SC, i < 8 ? ms : mh)));
#pragma unroll
  for (int n = 0; n < 5; n++) p[n] = pack_bf16(v[2*n], v[2*n+1]);
  return fmaf(v[8] + v[9], 2.f, ((v[0] + v[1]) + (v[2] + v[3])) + ((v[4] + v[5]) + (v[6] + v[7])));
}

template<bool ATT>
DEVI void rec_attn(const uint32_t sb, int h, int rank, int w, const bf16* __restrict__ Wo, const bf16* __restrict__ mem0) {
  using namespace rec;
  const int lane0 = lane_reg();
  int budget = SPIN_BUDGET;
  constexpr int NT = ATT ? 5 : 6;
  uint32_t wl[16];
  if (!ATT) {
    LANE_NOW;
#pragma unroll
    for (int i = 0; i < 16; i++) {
      const int dh = 8 * (i >> 1) + 2 * c;
      const unsigned short* p = (const unsigned short*)Wo + (size_t)(h * DH + dh) * DM + 15 * 64 + 16 * w + 8 * (i & 1) + g;
      wl[i] = p[0] | (uint32_t)p[DM] << 16;
    }
  }
  mbar_wait(sb + B_WO, 0, budget);
  cluster_arrive(); cluster_wait();
  const uint32_t d0 = desc_base(sb);
  uint32_t pph = 0;
#pragma unroll 1
  for (int s = -1; s < NSTEP; s++) {
    asm volatile("" : "+r"(h), "+r"(rank), "+r"(w));
    const uint32_t sp = s & 1;
    const int t0 = ATT ? rank + 1 : 0;
    const bool more = s + 1 < NSTEP;
    float hold[10] = {0, 0, 0, 0, 0, 0, 0, 0, 0, 0};
    if (ATT && s >= 0) {
      float sc[20];
      LANE_NOW;
      mbar_wait(sb + B_QK, sp, budget);
      PROFW(0, 1);
      fence_proxy_async();
      wg_fence();
      sfor<0, 8>([&](auto K) { constexpr int k = K; wg_ss40<k != 0, Op<QB + k * 256, 128, RG, 0, 1>, Op<QB + 3 * RG + k * 256, 128, 2 * RG, 0, 1>>(sc, d0, d0); });
      wg_commit();
      if (P_G1 < 16 && more) nbar_arrive<NB_G1, 384>();
      mbar_wait(sb + B_V, sp, budget);
      wg_wait<0>();
      pin<20>(sc);
      if (w == 3 && more) nbar_arrive<NB_S, 64>();
      PROFW(1, 2);
      if (w == 0) {
        uint32_t p[5];
        float v[10];
#pragma unroll
        for (int i = 0; i < 10; i++) v[i] = sc[4 * (i >> 1) + (i & 1)];
        softmax_row(v, p);
        const uint32_t a = sb + lane * 4;
        sts32v(a + PM0, p[0]); sts32v(a + PM0 + 128, p[1]); sts32v(a + PM1, p[2]); sts32v(a + PM1 + 128, p[3]); sts32v(a + PM2, p[4]);
      }
      if (more) {
        float rs[4], ot[2][4];
        uint32_t one[4];
#pragma unroll
        for (int i = 0; i < 4; i++) one[i] = 0x3F803F80u + ((uint32_t)budget >> (31 - i));
        typedef Op<PM0, 128, 128, 0, 0> P0; typedef Op<PM1, 128, 128, 0, 0> P1; typedef Op<PM2, 0, 128, 0, 0> P2;
        fence_proxy_async();
        nbar_sync<NB_P, 128>();
        PROFW(0, 3);
        wg_fence();
        wg_rs8<0, P0>(rs, one, d0); wg_rs8<1, P1>(rs, one, d0); wg_rs8<1, P2>(rs, one, d0);
        wg_commit();
        sfor<0, 2>([&](auto T) {
          constexpr int t = T;
          wg_ss8<0, Op<QB + 8 * RG + t * 1024, 2 * RG, 128, 0, 0>, P0>(ot[t], d0, d0);
          wg_ss8<1, Op<QB + 12 * RG + t * 1024, RG, 128, 0, 0>, P1>(ot[t], d0, d0);
          wg_ss8<1, Op<QB + 14 * RG + t * 1024, 0, 128, 0, 0>, P2>(ot[t], d0, d0);
        });
        wg_commit();
        if (P_G2 < 16 && !P_G2L) nbar_arrive<NB_G2, 384>();
        const uint32_t oa = w * 256 + lane * 4, r1 = mapr(h, sb, rank ^ 1), r2 = mapr(h, sb, 2);
        mbar_wait(sb + B_SDONE, sp, budget);
        wg_wait<1>();
        pin<4>(rs);
        float i0, i1;
        asm volatile("rcp.approx.ftz.f32 %0, %1;" : "=f"(i0) : "f"(rs[0]));
        asm volatile("rcp.approx.ftz.f32 %0, %1;" : "=f"(i1) : "f"(rs[1]));
        wg_wait<0>();
        pin<4>(ot[0]); pin<4>(ot[1]);
        uint32_t x[4];
#pragma unroll
        for (int j = 0; j < 4; j++) {
          x[j] = pack_bf16(ot[j >> 1][2 * (j & 1)] * i0, ot[j >> 1][2 * (j & 1) + 1] * i1);
          sts32v(sb + OM + rank * OMS + oa + (j >> 1) * 1024 + (j & 1) * 128, x[j]);
        }
        fence_proxy_async();
#pragma unroll
        for (int j = 0; j < 8; j++) {
          const int i = P_OS ? j >> 1 : j & 3;
          if (P_OS ? j & 1 : j >> 2) st_async32(r1 + OM + rank * OMS + oa + (i >> 1) * 1024 + (i & 1) * 128, x[i], r1 + B_OM);
          else st_async32(r2 + OM2 + rank * OM2S + oa + (i >> 1) * 1024 + (i & 1) * 128, x[i], r2 + B_OM);
        }
        e_arrive(sb + B_OM);
        if (P_G2 < 16 && P_G2L) nbar_arrive<NB_G2, 384>();
        PROFW(0, 4);
      }
#pragma unroll
      for (int i = 0; i < 10; i++) hold[i] = w ? sc[4 * (i >> 1) + (i & 1)] : sc[4 * (i >> 1) + 2 + (i & 1)];
    }
    if (more && s >= 0) {
      LANE_NOW;
      char* const pw = (char*)g_part + (uint32_t)((t0 * 16 + w * 4 + (lane >> 3)) * 4096 + h * 128 + ((lane ^ h) & 7) * 16);
      mbar_wait(sb + B_OM, sp, budget);
      if (w == 0) nbar_arrive<NB_G, 128>();
      PROFW(1, 5);
      if (!ATT) fence_proxy_async();
      float acc[3][8];
      auto store = [&](auto J) {
        constexpr int j = J;
        float* d = acc[j % 3];
        pin<8>(d);
        uint32_t x[4];
#pragma unroll
        for (int i = 0; i < 4; i++) { const uint32_t m = (h >> 3) == i; x[i] = (pack_bf16(d[2*i], d[2*i+1]) & ~m) | (m & ~sp); }
        stg_rlx128(pw + j * (48 * 4096), x[0], x[1], x[2], x[3]);
        if constexpr (ATT && j == JA) nbar_arrive<NB_TR, 160>();
        if constexpr (j == 2) PROFW(3, 26);
      };
      sfor<0, NT>([&](auto J) {
        constexpr int j = J;
        if constexpr (ATT && j == JA) { mbar_wait(sb + B_WA, sp, budget); PROFW(2, 0); }
        wg_fence();
        sfor<0, 8>([&](auto K) {
          constexpr int k = K;
          typedef Op<(ATT ? OM : OM2) + k * 256, 128, ATT ? OMS : OM2S, 0, 1> OB;
          if constexpr (j == 5 && k < 4) wg_rs16<k ? 1 : 2, OB>(acc[j % 3], wl + 4 * k, d0);
          else wg_ss16<k ? 1 : j < 3 ? 0 : 2, Op<(j == JA ? WA : j < 5 ? WO + (j - (j > JA)) * 16384 : WH - 8192) + k * 2048, 16, 1024, 1, 1>, OB>(acc[j % 3], d0, d0);
        });
        wg_commit();
        if constexpr (j == 0) { if (w == 3) e_expect_tx(sb + B_OM, ATT ? 2048 : 4096); }
        if constexpr (j == NT - 1 && !P_WOL) nbar_arrive<NB_WO, 384>();
        if constexpr (j > 0 && j != P_WB + 1) { wg_wait<1>(); store(IC<j - 1>{}); }
        if constexpr (j == P_WB || j == NT - 1) { wg_wait<0>(); store(IC<j>{}); }
        if constexpr (j == P_WB) {
          const uint32_t t = clock32();
          if (ATT) {
            if (w == 3 && lane < 14) sts128(sb + PM1 + lane * 16, (lane >> 1) == 3 ? 0x3F803F80u : 0);
            if (w == 3 || P_MB) fence_proxy_async();
            nbar_sync<NB_P, 128>();
          } else if (P_MB) fence_proxy_async();
          spin_until(t, TUN(8, 100));
        }
      });
      if (P_WOL) { spin_until(clock32(), TUN(9, 0)); nbar_arrive<NB_WO, 384>(); }
    } else if (more) nbar_arrive<NB_WO, 384>();
    PROFW(0, 6);
    asm volatile("" : "+r"(h), "+r"(rank), "+r"(w));
#pragma unroll 1
    for (int pass = 0; ATT && pass < 2; pass++)
    if (pass != rank) {
      LANE_NOW;
      const int lim = 8 * (g >> 1) + (g & 1) + 2 * w - 8 * c;
      uint32_t p[5];
#pragma unroll
      for (int i = 0; i < 8; i++) hold[2+i] = i <= lim ? hold[2+i] : -INFINITY;
      const float psum = softmax_row(hold, p);
#pragma unroll
      for (int i = 0; i < 5; i++) hold[i] = __uint_as_float(p[i]);
      hold[5] = psum;
    } else if (more) {
      LANE_NOW;
      const int blk = rank * 32 + h;
      char* const mw = (char*)g_mem + (uint32_t)(sp * 32768 + blk * 512 + w * 128 + lane * 4);
      uint32_t v0 = 0;
      if (s == -1 || (s == LAG - 1 && (w & 1))) {
        const unsigned short* q = (const unsigned short*)mem0 + c * 2 * DM + blk * 16 + (w >> 1) * 8 + g;
        v0 = q[0] | (uint32_t)q[DM] << 16;
        if (v0 == 0) v0 = 0x8000u;
      }
      keep(mw);
      if (s >= 0) {
        const uint32_t ca = sb + WA + lane * 128 + (((2 * w) ^ lane) & 7) * 16 + (lane >> 3) * 4;
        const uint32_t sa = sb + OM + (((g >> 1) & 1) * 2 + (g >> 2)) * 128 + (2 * c + (w >> 1)) * 16 + (w & 1) * 8 + (g & 1) * 2;
        for (bool first = true; ; first = false) {
          float r[4];
          mbar_wait(sb + B_PART, pph, budget);
          PROFW(0, 11);
          pph ^= 1;
          wg_fence();
          sfor<0, 8>([&](auto K) { constexpr int k = K; wg_ss8<k != 0, Op<WA + k * 2048, 16, 1024, 1, 1>, Op<PM1 + (6 - (k & 6)) * 16, 0, 128, 0, 0>>(r, d0, d0); });
          wg_commit();
          if (P_G4 < 16 && !P_G4L && first) nbar_arrive<NB_G4, 384>();
          const uint32_t x0 = lds32v(ca), x1 = lds32v(ca + 4096), x2 = lds32v(ca + 8192), x3 = lds32v(ca + 12288);
          bool bad = __any_sync(0xffffffffu, (sp ? x0 | x1 | x2 | x3 : ~(x0 & x1 & x2 & x3)) & 1) && budget > 0;
          wg_wait<0>();
          pin<4>(r);
          uint32_t y = pack_bf16(r[0], r[2]);
          y |= (y & 0xffffu) ? 0 : 0x8000u;
          y |= (y >> 16) ? 0 : 0x80000000u;
          if (bad) y = 0;
          sts16(sa, y); sts16(sa + 4, y >> 16);
          nbar_sync<NB_P, 128>();
          y = lds32v(sb + OM + w * 128 + lane * 4);
          const bool ok = !__any_sync(0xffffffffu, y == 0);
          if (ok) stg_rlx32(mw, v0 ? v0 : y);
          if (P_G4 < 16 && P_G4L && first) nbar_arrive<NB_G4, 384>();
          if (ok) break;
          nbar_sync<NB_P, 128>();
          budget--;
          if (w == 0) { e_expect_tx(sb + B_PART, 16384); e_bulk_g2s(sb + WA, (const char*)g_part + blk * 16384, 16384, sb + B_PART); }
          __syncwarp();
        }
      } else stg_rlx32(mw, v0);
      stg_rlx32(mw + (sp ? -32768 : 32768), 0);
      PROFW(1, 8);
    }
    if (ATT && s >= 0) {
      const int seg = s - (rank ? LAG : 0);
      const bool act = (unsigned)seg < NSEG;
      LANE_NOW;
      uint32_t a[12];
#pragma unroll
      for (int i = 0; i < 12; i++) a[i] = __float_as_uint(hold[i < 10 ? i >> 1 : 4]) + ((uint32_t)budget >> (31 - (i & 3)));
      float o[32], inv, psum = hold[5];
      char* const ob = (char*)g_o[rank] + ((size_t)(seg * 32 + 8 * (g >> 1) + (g & 1) + 2 * w) * (NH * DH) + h * DH + c * 8) * 2;
      sfor<0, 2>([&](auto HF) {
        constexpr int hf = HF;
        wg_fence();
        wg_rs64<hf * 2, Op<QB + 8 * RG + hf * 1024, 2 * RG, 128, 0, 0>>(o, a, d0);
        wg_rs64<1, Op<QB + 12 * RG + hf * 1024, RG, 128, 0, 0>>(o, a + 4, d0);
        wg_rs64<1, Op<QB + 14 * RG + hf * 1024, 0, 128, 0, 0>>(o, a + 8, d0);
        wg_commit();
        if constexpr (hf == 0) {
          psum += __shfl_xor_sync(0xffffffffu, psum, 1);
          psum += __shfl_xor_sync(0xffffffffu, psum, 2);
          asm("rcp.approx.ftz.f32 %0, %1;" : "=f"(inv) : "f"(psum));
        }
        wg_wait<0>();
        pin<32>(o);
        if constexpr (hf == 1) { if (w < 3 && more) e_arrive_cl(mapr(h, sb + B_BFREE, w)); }
        if (act) {
#pragma unroll
          for (int i = 0; i < 2; i++)
            stg128(ob + (hf * 2 + i) * 64, pack_bf16(o[16*i] * inv, o[16*i+1] * inv), pack_bf16(o[16*i+4] * inv, o[16*i+5] * inv),
                   pack_bf16(o[16*i+8] * inv, o[16*i+9] * inv), pack_bf16(o[16*i+12] * inv, o[16*i+13] * inv));
        }
      });
      PROFW(0, 7);
      if (act && (seg & 3) == 3) {
        nbar_sync<NB_P, 128>();
        if (w == 0) e_flag_add(g_fl.dep + grp(0, rank, seg >> 2), 4);
      }
    } else if (!ATT && w == 3) {
      if (s + 4 < NSEG) e_prefetch(g_xn[0] + (size_t)((s + 4) * 32 + h) * DM, 2048);
    }
  }
  cluster_arrive(); cluster_wait();
  char* const pw = (char*)g_part + (size_t)((ATT ? rank + 1 : 0) * 16 + w * 4 + (lane0 >> 3)) * 4096 + h * 128 + (lane0 & 7) * 16;
#pragma unroll
  for (int j = 0; j < NT; j++) stg_rlx128(pw + j * (48 * 4096), 0, 0, 0, 0);
}

DEVI void rec_load(const uint32_t sb, const int h, const int rank, const int w, const CUtensorMap* mX, const CUtensorMap* mWo) {
  using namespace rec;
  static_assert(((NSTEP - 1) & 31) != 1 && ((NSTEP - 2) & 31) != 2, "stale time stamps of the previous launch never match");
  const int lane0 = lane_reg(), mq = (w + 3) & 3;
  int budget = SPIN_BUDGET;
  if (w == 0) { e_flag_add(g_fl.xn[0][0]); flag_wait(g_fl.xn[0][0], 96, budget); }
  bool late = false;
  cluster_arrive(); cluster_wait();
  if (w == 0) { if (lane0 < 4) mbar_arrive(sb + B_FULL + 8 * lane0); __syncwarp(); }
  uint32_t lph = 0;
#pragma unroll 1
  for (int s = -1; s < NSTEP - 1; s++) {
    if (w == 0) {
      if (late) flag_wait(g_fl.xn[1][(s + 1 - LAG) >> 2], 128, budget);
      if (single(s)) {
#pragma unroll 1
        for (int i = 0; i < 8; i++) {
          const int k = i < 5 ? (0x21430 >> (4 * i)) & 15 : i;
          const int sl = (SLOT1 >> (4 * k)) & 15;
          mbar_wait(sb + B_EMPTY + 8 * sl, (((USE1 >> (4 * k)) ^ (sl >> 1 == 1 ? s + 1 : 0)) & 1) ^ 1, budget);
          e_expect_tx(sb + B_FULL + 8 * sl, 8192);
          e_tma_3d(sb + RING + sl * 8192, mX + 1, 0, (s + 1 + (s < LAG ? 0 : NSTEP)) * 32, k * 2, sb + B_FULL + 8 * sl);
        }
      } else {
        int sl = 4, ph = 1;
#pragma unroll 1
        for (int i = 0; i < 16; i++) {
          mbar_wait(sb + B_EMPTY + 8 * sl, ph, budget);
          e_expect_tx(sb + B_FULL + 8 * sl, 8192);
          e_tma_3d(sb + RING + sl * 8192, mX, i * 64, (s + 1) * 32, 0, sb + B_FULL + 8 * sl);
          if (++sl == 5) { sl = 0; ph ^= 1; }
        }
      }
      nbar_arrive<NB_X, 128>();
      const int sn = s + 2 - LAG;
      late = (sn & 3) == 0 && (unsigned)sn < NSEG && ld_acquire(g_fl.xn[1][sn >> 2]) < 128;
      asm volatile("fence.proxy.async.global;" ::: "memory");
    }
    uint32_t t = gtime();
    if (s >= 0) {
      uint2 a;
      if (w == 2 && rank < 2) {
        nbar_sync<NB_S, 64>();
        e_expect_tx(sb + B_WA, 16384);
        e_tma_2d(sb + WA, mWo, (3 * JA + 1 + rank) * 64, h * DH, sb + B_WA);
        e_tma_2d(sb + WA + 8192, mWo, (3 * JA + 1 + rank) * 64, h * DH + 64, sb + B_WA);
        e_arrive_cl(mapr(h, sb + B_SDONE, rank ^ 1));
        stg_rlx32(&g_ann[s & 1][lane0][h * 2 + rank], (gtime() & ~31u) | ((s + 1) & 31));
        e_expect_tx(sb + B_QK, 10240);
        e_expect_tx(sb + B_V, 10240);
      }
      if (w) nbar_sync<NB_G, 128>();
      do { a = ldg_rlx64(&g_ann[s & 1][h][lane0 * 2]); } while (__any_sync(0xffffffffu, ((a.x ^ (s + 1)) | (a.y ^ (s + 1))) & 31) && --budget > 0);
      t += __reduce_max_sync(0xffffffffu, max((int)(a.x - t), (int)(a.y - t)));
      t = (t & ~31u) - (single(s) ? TUN(6, 150) : 0);
      PROFW(1, 12);
      if (w == 1 && rank < 2) {
        nbar_sync<NB_TR, 160>();
        wait_time(t + (rank ? TUN(1, 1800) : TUN(0, 1400)), budget);
        e_expect_tx(sb + B_PART, 16384);
        e_bulk_g2s(sb + WA, (const char*)g_part + (rank * 32 + h) * 16384, 16384, sb + B_PART);
        PROFW(1, 21);
      }
      t -= single(s) ? TUN(7, 50) : 0;
      t += mq == 0 ? TUN(2, 2400) : mq == 1 ? TUN(3, 2500) : mq == 2 ? TUN(4, 2900) : TUN(5, 3000);
    }
    if (w) nbar_sync<NB_X, 128>();
    mbar_wait(sb + B_EMPTY + 8 * mq, mq >= 2 && single(s) ? (s + 1) & 1 : 1, budget);
    PROFW(1, 9);
    wait_time(t, budget);
    PROFW(1, 22); PROFW(3, 23);
    while (true) {
      e_expect_tx(sb + B_MLAND + 8 * mq, 8192);
      e_bulk_g2s(sb + RING + mq * 8192, (const char*)g_mem + (s & 1) * 32768 + mq * 8192, 8192, sb + B_MLAND + 8 * mq);
      const uint32_t a = sb + RING + mq * 8192 + lane0 * 32 + (lane0 >> 2) * 4;
      mbar_wait(sb + B_MLAND + 8 * mq, lph, budget);
      lph ^= 1;
      PROFW(1, 24);
      uint32_t mn = 0xffffffffu;
#pragma unroll
      for (int i = 0; i < 8; i++) mn = min(mn, lds32v(a + i * 1024));
      if (!__any_sync(0xffffffffu, mn == 0) || --budget <= 0) break;
    }
    e_arrive(sb + B_FULL + 8 * mq);
    PROFW(1, 10); PROFW(2, 13); PROFW(3, 14); PROFW(0, 15);
  }
}

DEVI void ln_row(const uint4* u, bf16* dst, int lane) {
  const uint32_t* x = (const uint32_t*)u;
  float mean = 0, q = 0;
#pragma unroll
  for (int i = 0; i < 16; i++) mean += bf_lo(x[i]) + bf_hi(x[i]);
  mean *= 1.f / 32;
#pragma unroll
  for (int i = 0; i < 16; i++) { const float a = bf_lo(x[i]) - mean, b = bf_hi(x[i]) - mean; q = fmaf(a, a, fmaf(b, b, q)); }
#pragma unroll
  for (int o = 1; o < 32; o *= 2) {
    const float m2 = __shfl_xor_sync(0xffffffffu, mean, o), q2 = __shfl_xor_sync(0xffffffffu, q, o), dl = m2 - mean;
    q = fmaf(dl * dl, 16.f * o, q + q2);
    mean = 0.5f * (mean + m2);
  }
  const float rs = rsqrtf(q * (1.f / DM) + 1e-5f), mr = -mean * rs;
#pragma unroll
  for (int i = 0; i < 4; i++) {
    uint32_t y[4];
#pragma unroll
    for (int k = 0; k < 4; k++) y[k] = pack_bf16(fmaf(bf_lo(x[4*i+k]), rs, mr), fmaf(bf_hi(x[4*i+k]), rs, mr));
    stg128((uint4*)dst + i * 32 + lane, y[0], y[1], y[2], y[3]);
  }
}

struct RecMaps { CUtensorMap w[3], wo, x[2]; };
__global__ void __cluster_dims__(R_CL, 1, 1) __launch_bounds__(512, 1)
rec_kernel(const __grid_constant__ RecMaps M, const bf16* __restrict__ Wo, const bf16* __restrict__ mem0, const bf16* __restrict__ x, uint32_t zero) {
  using namespace rec;
  extern __shared__ __align__(1024) uint8_t smem[];
  const uint32_t sb = smem_u32(smem);
  const int tid = threadIdx.x, warp = __shfl_sync(0xffffffffu, tid >> 5, 0), wg = warp >> 2, lane = tid & 31;
  const int h = blockIdx.x / 3, rank = blockIdx.x % 3;
  if (warp == 0) {
    if (lane < 20) mbar_init(sb + BARS + 8 * lane, (lane >= 5 && lane < 10) || lane == 19 ? 2 : lane == 14 ? 9 : lane == 16 && rank < 2 ? 5 : 1);
    else if (lane < 23) mbar_init(sb + B_W1 + 8 * (lane - 20), 1);
    else if (lane == 23) mbar_init(sb + B_PART, 1);
    fence_mbar_init();
    __syncwarp();
    if (lane == 0) { mbar_expect_tx(sb + B_W1, (NSS + R1) * 4096); mbar_expect_tx(sb + B_QK, 10240); mbar_expect_tx(sb + B_V, 10240); mbar_expect_tx(sb + B_OM, rank < 2 ? 2048 : 4096); }
    __syncwarp();
    for (int i = lane; i < 128; i += 32) {
      const int j = i >> 1, t = i & 1, r = reg_idx(j);
      if (is_ss(j)) tma_load_2d(sb + WS + (t * NSS + ss_before(j)) * 2048, &M.w[rank], h * DH + t * 64, j * 16, sb + B_W1);
      else if (r < R1) tma_load_2d(sb + WO + (t * R1 + r) * 2048, &M.w[rank], h * DH + t * 64, j * 16, sb + B_W1);
      else tma_prefetch_2d(&M.w[rank], h * DH + t * 64, j * 16);
    }
    const int t = 3 * (lane >> 1) + (rank + 1) % 3;
    if (t < 16) tma_prefetch_2d(&M.wo, t * 64, h * DH + (lane & 1) * 64);
  } else if (warp == 1) {
    constexpr int N = (sizeof(Flags) - sizeof(g_fl.xn)) / 16;
    if (lane < 8 && blockIdx.x * 8 + lane < N) ((uint4*)g_fl.dep)[blockIdx.x * 8 + lane] = make_uint4(0, 0, 0, 0);
    static_assert(N <= 96 * 8, "flag reset");
    __threadfence();
    __syncwarp();
    asm volatile("griddepcontrol.launch_dependents;" ::: "memory");
  } else if (warp >= 5 && blockIdx.x * 11 + warp - 5 < SEQ / 2) {
    const size_t o = (size_t)(blockIdx.x * 11 + warp - 5) * (2 * DM);
    uint4 u[8];
#pragma unroll
    for (int i = 0; i < 8; i++) u[i] = __ldg((const uint4*)(x + o) + i * 32 + lane);
    ln_row(u, g_xn[0] + o, lane);
    ln_row(u + 4, g_xn[0] + o + DM, lane);
  }
  __syncthreads();
  if (wg == 3) {
    reg_dec<24>();
    rec_load(sb, h, rank, warp & 3, M.x, &M.wo);
    cluster_arrive(); cluster_wait();
  } else if (wg == 2) {
    reg_dec<72>();
    if (rank < 2) rec_attn<true>(sb, h, rank, warp & 3, Wo, mem0);
    else rec_attn<false>(sb, h, rank, warp & 3, Wo, mem0);
  } else {
    reg_inc<208>();
    rec_proj(sb, h, rank, warp, &M.w[rank], &M.wo, zero);
    cluster_arrive(); cluster_wait();
  }
}

namespace gm {
constexpr int STAGES = 6, STAGE_BYTES = 32768;
constexpr uint32_t SO = STAGES * STAGE_BYTES, B_FULL = SO + 32768, B_TRIG = B_FULL + 56, B_EMPTY = B_FULL + 64, B_JOB = B_FULL + 128,
                   B_MSG = B_FULL + 144, B_XF = B_FULL + 160, B_SF = B_FULL + 176, JOB = B_FULL + 192, MSG = JOB + 8, SMEM = B_FULL + 256;
constexpr int T_O = 0, T_GU = 1, T_D = 2, T_END = 3;
#define G_LOOK 8
#define G_FILL 7
#define G_SLEEP 200
#define G_SLEEP2 500
#define G_SLEEP3 200
#define G_DS 12
DEVI bool is_split(int ty, int l, int cb) { return ty == T_O || (ty == T_D && (!l || cb >= G_DS)); }
struct Pipe { int s, ph; DEVI void next() { if (++s == STAGES) { s = 0; ph ^= 1; } } };
}
struct GemmMaps { CUtensorMap o, wo, x, x1, x1s, xm, xms, xn, wg, wu, h, hs, wd, x2, out, outs; };

DEVI float geglu(float g, float u) {
  const float z = g * (0.7978845608028654f + 0.035677408136300125f * g * g);
  float t; asm("tanh.approx.f32 %0, %1;" : "=f"(t) : "f"(z));
  const float hg = 0.5f * g;
  return fmaf(hg, t, hg) * u;
}
DEVI int h_ready(int v) { const int t = v ^ 0x101414; return t ? ((__ffs(t) - 1) >> 3) * 20 : 56; }
DEVI int a_ready(int ty, int l, int cb) {
  const int v = ld_acquire(g_fl.dep + grp(ty, l, cb));
  asm volatile("fence.proxy.async.global;" ::: "memory");
  return ty == gm::T_D ? h_ready(v) : v >= 128 ? 64 : 0;
}

__global__ void __cluster_dims__(2, 1, 1) __launch_bounds__(512, 1) gemm_kernel(const __grid_constant__ GemmMaps M) {
  using namespace gm;
  extern __shared__ __align__(1024) uint8_t smem[];
  const uint32_t sb = smem_u32(smem);
  const int tid = threadIdx.x, wid = __shfl_sync(0xffffffffu, tid >> 5, 0), wg = wid >> 2, warp = wid & 3;
  int budget = SPIN_BUDGET;
  const int rank = blockIdx.x & 1;
  const uint32_t peer = mapa(sb, rank ^ 1);
  if (tid < 24) mbar_init(sb + B_FULL + 8 * tid, tid >> 3 == 1 ? 2 : 1);
  fence_mbar_init();
  if (wid == 1 && rank == 0) sts32v(sb + JOB + 16, bcast(e_ticket(g_fl.ticket)));
  cluster_arrive(); cluster_wait();
  int pair;
  asm volatile("ld.shared::cluster.u32 %0, [%1];" : "=r"(pair) : "r"(mapa(sb + JOB + 16, 0)) : "memory");
  pair = __shfl_sync(0xffffffffu, pair, 0);
  const int cta = pair * 2 + rank, lane = lane_reg();
  if (wg >= 2) {
    reg_dec<72>();
    if (wid == 8 || wid == 10) {
      Pipe p; p.s = 0; p.ph = 1;
      for (int n = 0; ; n++) {
        if (wid == 8) e_expect_tx(sb + B_MSG + 8 * (n & 1), 4);
        mbar_wait(sb + B_MSG + 8 * (n & 1), (n >> 1) & 1, budget);
        const int msg = __shfl_sync(0xffffffffu, lds32v(sb + MSG + 4 * (n & 1)), 0);
        const int ty = (msg >> 11) & 3, l = (msg >> 10) & 1;
        const bool shb = ty == T_GU && l, spl = is_split(ty, l, (msg >> 6) & 15);
        const int cb = ((msg >> 6) & 15) + (shb ? rank : 0), j = (msg & 63) + (ty == T_END || shb ? 0 : rank);
        const int ke = ty == T_O ? 64 : ty == T_GU ? 16 : 56, k0 = spl ? rank : 0, dk = spl ? 2 : 1;
        const int c0 = ty == T_GU ? j * 64 : spl ? (j >> 1) * 128 : j * 128, c1 = ty == T_GU ? c0 : c0 + 64;
        mbar_wait(sb + B_EMPTY + 8 * p.s, p.ph, budget);
        trap_if_spent(budget);
        auto stages = [&](auto f) {
#pragma unroll 1
          for (int k = k0; k < ke; k += dk) {
            mbar_wait(sb + B_EMPTY + 8 * p.s, p.ph, budget);
            f(k, sb + p.s * STAGE_BYTES, sb + B_FULL + 8 * p.s);
            p.next();
          }
        };
        if (wid == 8) {
          const int job = ty << 11 | l << 10 | cb << 6 | j;
          sts32v(sb + JOB + 4 * (n & 1), job | p.s << 16 | (p.ph ^ 1) << 20);
          e_arrive(sb + B_JOB + 8 * (n & 1));
          if (ty == T_END) break;
          if (ty != T_GU) { e_expect_tx(sb + B_FULL + 8 * p.s, spl ? 16384 : STAGE_BYTES); p.next(); }
          const CUtensorMap* const m0 = ty == T_D ? &M.wd : shb && rank ? &M.wu : &M.wg, * const m1 = ty == T_D ? &M.wd : &M.wu;
          if (ty == T_O) stages([&](int k, uint32_t a, uint32_t fb) { e_expect_tx(fb, STAGE_BYTES); e_tma_5d(a + 16384, &M.wo, c0, k * 2, fb); e_tma_5d(a + 24576, &M.wo, c1, k * 2, fb); });
          else if (shb) stages([&](int k, uint32_t a, uint32_t fb) { e_expect_tx(fb, STAGE_BYTES); e_tma_2d_mc(a + 16384 + rank * 8192, m0, c0, k * 64, fb); });
          else stages([&](int k, uint32_t a, uint32_t fb) { e_expect_tx(fb, STAGE_BYTES); e_tma_2d(a + 16384, m0, c0, k * 64, fb); e_tma_2d(a + 24576, m1, c1, k * 64, fb); });
        } else {
          if (ty == T_END) break;
          const int row = l * SEQ + cb * 128, kt = ke + k0 - G_LOOK * dk;
          int rdy = msg >> 16;
          auto need = [&](int k) {
            if (k == kt) e_arrive(sb + B_TRIG);
            while (k >= rdy && k >= (rdy = a_ready(ty, l, cb))) { __nanosleep(G_SLEEP); trap_if_spent(--budget); }
          };
          if (ty != T_GU) {
            need(0);
            const uint32_t a = sb + p.s * STAGE_BYTES, fb = sb + B_FULL + 8 * p.s;
            const CUtensorMap* const m = ty == T_D ? (spl ? &M.x1 : &M.x1s) : l ? &M.x2 : &M.x;
            const int r = (ty == T_D ? row : cb * 128) + (spl ? rank * 64 : 0);
            e_tma_2d(a, m, c0, r, fb); e_tma_2d(a + 16384, m, c1, r, fb);
            p.next();
          }
          if (shb || spl) {
            const CUtensorMap* const ma = ty == T_O ? &M.o : ty == T_GU ? &M.xms : &M.hs;
            stages([&](int k, uint32_t a, uint32_t fb) { need(k); e_tma_2d(a, ma, k * 64, row, fb); });
          } else {
            const CUtensorMap* const ma = ty == T_GU ? &M.xm : &M.h;
            stages([&](int k, uint32_t a, uint32_t fb) { need(k); e_tma_2d_mc(a + rank * 8192, ma, k * 64, row + rank * 64, fb); });
          }
        }
      }
    } else if (wid == 9 && rank == 0) {
      int k1 = pair < 18 ? 0 : 68;
      bool late = false;
      for (int n = 0, ty = 0; ty != T_END; n++) {
        mbar_wait(sb + B_TRIG, (n & 1) ^ 1, budget);
        int l, cb, j, rdy = 64;
        while (true) {
          const int ph = k1 & 3;
          const bool gap = ph == 3;
          if (k1 < 68) {
            cb = (k1++ >> 2) - (pair < 8 ? ph : 0);
            if ((unsigned)cb >= 16 || (ph == 2 && pair >> 3 != 1) || (gap && (pair < 8 || late || !(G_FILL & (pair >> 3))))) continue;
            if (!gap) {
              l = 0;
              ty = pair < 8 ? (ph ? T_D : T_O) : T_GU;
              j = 2 * (pair < 8 ? pair : pair - 8 + 10 * ph);
              rdy = a_ready(ty, 0, cb);
              if (ph == 0) late = rdy != 0;
              break;
            }
          }
          int d0 = ld_relaxed(g_fl.dep + lane), d1 = ld_relaxed(g_fl.dep + 32 + lane);
          const int t0 = ld_relaxed(g_fl.taken + lane), t1 = ld_relaxed(g_fl.taken + 32 + lane);
          const bool l0 = t0 < (lane < 16 ? 8 : lane & 1 ? 0 : 56), l1 = lane < 16 && t1 < (lane < G_DS ? 4 : 8);
          const uint32_t rd = __ballot_sync(0xffffffffu, d0 >= 128);
          uint32_t ok0 = __ballot_sync(0xffffffffu, l0) & rd & (rd >> 1 | 0xffff), ok1 = __ballot_sync(0xffffffffu, l1 && h_ready(d1) > 0);
          if (gap) { ok1 = 0; if (pair < 16) ok0 &= G_FILL & 8 ? ((k1 >> 2 ^ pair) & 1 ? ~0u : 0u) : G_FILL & 4 ? 0xffff0003u : 0xffff0000u; }
          ty = T_END; l = 1; cb = j = 0;
          if (!gap && !__any_sync(0xffffffffu, l0 || l1)) break;
          if (ok1 & ((1u << G_DS) - 1)) ok1 &= (1u << G_DS) - 1;
          uint32_t m = ok0 ? ok0 : ok1;
          if (!m && !gap) __nanosleep(100);
          while (m) {
            const int nth = ok0 ? 0 : pair % __popc(m);
            const int b = __ffs(__ballot_sync(0xffffffffu, __popc(m << (31 - lane)) > nth)) - 1, gn = b + (ok0 ? 0 : 32);
            const int t = bcast(e_ticket(g_fl.taken + gn));
            if (t < (gn < 16 ? 8 : gn < 32 ? 56 : gn < 32 + G_DS ? 4 : 8)) { ty = gn >> 4; cb = gn & 15; j = ty == T_GU ? t : 2 * t; break; }
            m &= ~(1u << b);
          }
          if (ty != T_END) {
            rdy = a_ready(ty, 1, cb);
            if (ty == T_GU) a_ready(ty, 1, cb + 1);
            break;
          }
          trap_if_spent(--budget);
        }
        const int msg = rdy << 16 | ty << 11 | l << 10 | cb << 6 | j;
        e_st_async32(peer + MSG + 4 * (n & 1), msg, peer + B_MSG + 8 * (n & 1));
        e_st_async32(sb + MSG + 4 * (n & 1), msg, sb + B_MSG + 8 * (n & 1));
      }
    } else if (wg == 3) {
      bool open = lane < 16 && ld_relaxed(g_fl.rows + lane) < 128;
      while (__any_sync(0xffffffffu, open)) {
        int v = 0;
        if (open) asm volatile("ld.acquire.gpu.global.s32 %0, [%1];" : "=r"(v) : "l"(g_fl.part + lane) : "memory");
        const uint32_t ok = __ballot_sync(0xffffffffu, open && v >= 16);
        if (!ok) {
          if (--budget <= 0) break;
          __nanosleep(G_SLEEP2);
          continue;
        }
        const int cb = __ffs(__ballot_sync(0xffffffffu, __popc(ok << (31 - lane)) > (cta >> 5) % __popc(ok))) - 1;
        const int r = bcast(e_ticket(g_fl.rows + cb));
        if (r >= 128) { open = open && lane != cb; continue; }
        uint4 u[4];
#pragma unroll
        for (int i = 0; i < 4; i++) u[i] = ldg_rlx128((const uint4*)(g_x1[1] + (size_t)(cb * 128 + r) * DM) + i * 32 + lane);
        ln_row(u, g_xm[1] + (size_t)(cb * 128 + r) * DM, lane);
        __syncwarp();
        e_flag_add(g_fl.dep + grp(T_GU, 1, cb));
      }
      if (cta == 0 && wid == 12) {
        asm volatile("griddepcontrol.wait;" ::: "memory");
        g_fl.xn[lane >> 4][lane & 15][0] = 0;
      }
    }
    cluster_arrive(); cluster_wait();
  } else {
    reg_inc<184>();
    const bool lead = warp == 0;
    const uint32_t eb = (warp == 1 ? peer : sb) + B_EMPTY;
    const int rl = warp < 2 ? 0 : -1;
    const uint32_t so = sb + SO + wg * 16384;
    const int r0 = warp * 16 + (lane & 7) + ((lane >> 3) & 1) * 8;
    const uint32_t sw = r0 * 128 + (((lane >> 4) ^ (r0 & 7)) << 4);
    int xph = 0;
    for (int n = wg; ; n += 2) {
      float d0[64], d1[64];
      mbar_wait(sb + B_JOB + 8 * wg, (n >> 1) & 1, budget);
      fault_if_spent(budget);
      const int job = __shfl_sync(0xffffffffu, lds32v(sb + JOB + 4 * wg), 0);
      const int ty = (job >> 11) & 3, l = (job >> 10) & 1, cb = (job >> 6) & 15, j = job & 63;
      if (ty == T_END) {
        if (n > 0) nbar_sync_r(1 + wg, 256);
        if (lead && !(job & 1)) { sts32v(sb + JOB + 4 * (wg ^ 1), job | 1); e_arrive(sb + B_JOB + 8 * (wg ^ 1)); }
        if (!(job & 1)) nbar_arrive_r(1 + (wg ^ 1), 256);
        break;
      }
      Pipe q; q.s = (job >> 16) & 15; q.ph = job >> 20;
      const bool spl = is_split(ty, l, cb);
      if (ty != T_GU) mbar_wait(sb + B_FULL + 8 * q.s, q.ph, budget);
#pragma unroll
      for (int m = 0; m < 2; m++) {
        float* d = m ? d1 : d0;
        if (ty != T_GU && !(m && spl)) {
#pragma unroll
          for (int c = 0; c < 8; c++) {
            uint32_t r[4];
            ldsm4(sb + q.s * STAGE_BYTES + (c >> 2) * 16384 + m * 8192 + (sw ^ ((c & 3) << 5)), r[0], r[1], r[2], r[3]);
#pragma unroll
            for (int i = 0; i < 4; i++) { d[8*c+2*i] = bf_lo(r[i]); d[8*c+2*i+1] = bf_hi(r[i]); }
          }
        } else {
#pragma unroll
          for (int i = 0; i < 64; i++) d[i] = 0.f;
        }
      }
      if (ty != T_GU) {
        fence_proxy_async();
        nbar_sync_r(3 + wg, 128);
        arrive_cl_if_eq(eb + 8 * q.s, lane, rl);
        q.next();
      }
      pin<64>(d0); pin<64>(d1);
      if (n > 0) nbar_sync_r(1 + wg, 256);
      const int nk = ty == T_O ? 32 : ty == T_GU ? 16 : spl ? 28 : 56;
      const uint32_t ro = spl ? rank * 512 : 0;
      int prev = 0;
      for (int i = 0; i < nk; i++) {
        mbar_wait(sb + B_FULL + 8 * q.s, q.ph, budget);
        const uint32_t da = desc_base(sb) + q.s * (STAGE_BYTES / 16);
        wg_fence();
        sfor<0, 4>([&](auto K) {
          constexpr int k = K;
          typedef Op<16384 + k * 2048, 8192, 1024, 1, 1> OB;
          wg_ss128<1, Op<k * 32, 16, 1024, 1, 0>, OB>(d0, da + ro, da);
          wg_ss128<1, Op<8192 + k * 32, 16, 1024, 1, 0>, OB>(d1, da - ro, da);
        });
        wg_commit();
        wg_wait<1>();
        arrive_cl_if_eq(eb + 8 * prev, lane, i ? rl : -1);
        prev = q.s;
        q.next();
      }
      nbar_arrive_r(1 + (wg ^ 1), 256);
      wg_wait<0>();
      pin<64>(d0); pin<64>(d1);
      arrive_cl_if_eq(eb + 8 * prev, lane, rl);
      if (spl) {
        const uint32_t xa = SO + wg * 16384 + warp * 512 + lane * 16;
        if (lead) e_expect_tx(sb + B_XF + 8 * wg, 16384);
        mbar_wait(sb + B_SF + 8 * wg, ((n >> 1) & 1) ^ 1, budget);
#pragma unroll
        for (int i = 0; i < 8; i++) {
          const float* d = d1 + 8 * i;
          st_async128(peer + xa + i * 2048, pack_bf16(d[0], d[1]), pack_bf16(d[2], d[3]), pack_bf16(d[4], d[5]), pack_bf16(d[6], d[7]), peer + B_XF + 8 * wg);
        }
        mbar_wait(sb + B_XF + 8 * wg, xph, budget);
        xph ^= 1;
        uint32_t y[32];
#pragma unroll
        for (int i = 0; i < 8; i++) {
          const float* d = d0 + 8 * i;
          const uint4 v = lds128(sb + xa + i * 2048);
          y[4*i] = pack_bf16(d[0] + bf_lo(v.x), d[1] + bf_hi(v.x)); y[4*i+1] = pack_bf16(d[2] + bf_lo(v.y), d[3] + bf_hi(v.y));
          y[4*i+2] = pack_bf16(d[4] + bf_lo(v.z), d[5] + bf_hi(v.z)); y[4*i+3] = pack_bf16(d[6] + bf_lo(v.w), d[7] + bf_hi(v.w));
        }
        float2* const st = &g_stat[ty >> 1][cb & 1][0][rank * 64 + warp * 16 + (lane >> 2) * 2];
        if (!l) {
          float mn[2], sq[2];
#pragma unroll
          for (int z = 0; z < 2; z++) {
            float m = 0, s2 = 0;
#pragma unroll
            for (int i = 0; i < 16; i++) m += bf_lo(y[2*i+z]) + bf_hi(y[2*i+z]);
            m += __shfl_xor_sync(0xffffffffu, m, 1); m += __shfl_xor_sync(0xffffffffu, m, 2);
            m *= 1.f / 128;
#pragma unroll
            for (int i = 0; i < 16; i++) { const float a = bf_lo(y[2*i+z]) - m, b = bf_hi(y[2*i+z]) - m; s2 = fmaf(a, a, fmaf(b, b, s2)); }
            s2 += __shfl_xor_sync(0xffffffffu, s2, 1); s2 += __shfl_xor_sync(0xffffffffu, s2, 2);
            mn[z] = m; sq[z] = s2;
          }
          if ((lane & 3) == 0) stg_rlx128(st + (j >> 1) * 128, __float_as_uint(mn[0]), (__float_as_uint(sq[0]) & ~31u) | (cb + 1), __float_as_uint(mn[1]), __float_as_uint(sq[1]));
          __syncwarp();
        }
        auto put = [&](const CUtensorMap* mo, int row) {
          nbar_sync_r(3 + wg, 128);
#pragma unroll
          for (int c = 0; c < 8; c++) stsm4(so + (c >> 2) * 8192 + (sw ^ ((c & 3) << 5)), y[4*c], y[4*c+1], y[4*c+2], y[4*c+3]);
          fence_proxy_async();
          nbar_sync_r(3 + wg, 128);
          if (lead) { e_tma_store_2d(mo, so, (j >> 1) * 128, row); e_tma_store_2d(mo, so + 8192, (j >> 1) * 128 + 64, row); bulk_commit(); }
        };
        const int row = (ty == T_O ? l * SEQ : 0) + cb * 128 + rank * 64;
        put(ty == T_O ? &M.x1 : l ? &M.out : &M.x2, row);
        if (!l) {
          uint4 u[2];
          while (true) {
            u[0] = ldg_rlx128(st + (lane & 3) * 256); u[1] = ldg_rlx128(st + (lane & 3) * 256 + 128);
            if (!__any_sync(0xffffffffu, ((u[0].y ^ (cb + 1)) | (u[1].y ^ (cb + 1))) & 31) || --budget <= 0) break;
            __nanosleep(G_SLEEP3);
          }
#pragma unroll
          for (int z = 0; z < 2; z++) {
            const float ma = __uint_as_float(z ? u[0].z : u[0].x), mb = __uint_as_float(z ? u[1].z : u[1].x);
            float m = ma + mb;
            m += __shfl_xor_sync(0xffffffffu, m, 1); m += __shfl_xor_sync(0xffffffffu, m, 2);
            m *= 0.125f;
            float s2 = __uint_as_float(z ? u[0].w : u[0].y & ~31u) + __uint_as_float(z ? u[1].w : u[1].y & ~31u) + 128.f * ((ma - m) * (ma - m) + (mb - m) * (mb - m));
            s2 += __shfl_xor_sync(0xffffffffu, s2, 1); s2 += __shfl_xor_sync(0xffffffffu, s2, 2);
            const float rs = rsqrtf(s2 * (1.f / DM) + 1e-5f), mr = -m * rs;
#pragma unroll
            for (int i = 0; i < 16; i++) y[2*i+z] = pack_bf16(fmaf(bf_lo(y[2*i+z]), rs, mr), fmaf(bf_hi(y[2*i+z]), rs, mr));
          }
          if (lead) bulk_wait_read<0>();
          put(ty == T_O ? &M.xm : &M.xn, row);
        }
      } else {
        if (ty == T_GU) {
#pragma unroll
          for (int i = 0; i < 32; i++) { d0[i] = geglu(d0[i], d0[32 + i]); d1[i] = geglu(d1[i], d1[32 + i]); }
        }
#pragma unroll
        for (int hf = 0; hf < 2; hf++) {
          if (hf) {
            if (ty == T_GU) break;
            if (lead) bulk_wait_read<0>();
            nbar_sync_r(3 + wg, 128);
          }
#pragma unroll
          for (int m = 0; m < 2; m++)
#pragma unroll
            for (int c = 0; c < 4; c++) {
              const float* d = (m ? d1 : d0) + 32 * hf + 8 * c;
              stsm4(so + m * 8192 + (sw ^ (c << 5)), pack_bf16(d[0], d[1]), pack_bf16(d[2], d[3]), pack_bf16(d[4], d[5]), pack_bf16(d[6], d[7]));
            }
          fence_proxy_async();
          nbar_sync_r(3 + wg, 128);
          if (lead) {
            if (ty == T_GU) e_tma_store_2d(&M.hs, so, j * 64, l * SEQ + cb * 128); else e_tma_store_2d(&M.outs, so, j * 128 + hf * 64, cb * 128);
            bulk_commit();
          }
        }
      }
      if (lead) {
        bulk_wait<0>();
        e_arrive_cl(peer + B_SF + 8 * wg);
        if (ty == T_GU) e_flag_add(g_fl.dep + grp(T_D, l, cb), 1 << (j / 20 * 8));
        else if (ty == T_O || !l) e_flag_add(l ? g_fl.part + cb : ty == T_O ? g_fl.dep + grp(T_GU, 0, cb) : g_fl.xn[1][cb], l ? 1 : 8);
      }
    }
    cluster_arrive(); cluster_wait();
  }
}

typedef CUresult (*PFN_encodeTiled)(CUtensorMap*, CUtensorMapDataType, cuuint32_t, void*, const cuuint64_t*, const cuuint64_t*,
                                    const cuuint32_t*, const cuuint32_t*, CUtensorMapInterleave, CUtensorMapSwizzle,
                                    CUtensorMapL2promotion, CUtensorMapFloatOOBfill);
static PFN_encodeTiled g_encode = nullptr;
static int g_sms = 0;
static CUtensorMap encode(const void* ptr, int rank, const cuuint64_t* dims, const cuuint64_t* strides, const cuuint32_t* box) {
  CUtensorMap m;
  const cuuint32_t es[5] = {1, 1, 1, 1, 1};
  g_encode(&m, CU_TENSOR_MAP_DATA_TYPE_BFLOAT16, rank, (void*)ptr, dims, strides, box, es, CU_TENSOR_MAP_INTERLEAVE_NONE,
           CU_TENSOR_MAP_SWIZZLE_128B, CU_TENSOR_MAP_L2_PROMOTION_L2_256B, CU_TENSOR_MAP_FLOAT_OOB_FILL_NONE);
  return m;
}
static CUtensorMap make_map(const void* ptr, uint64_t rows, uint64_t cols, uint32_t box_rows) {
  const cuuint64_t dims[2] = {cols, rows}, strides[1] = {cols * 2};
  const cuuint32_t box[2] = {64, box_rows};
  return encode(ptr, 2, dims, strides, box);
}
static CUtensorMap make_map_x(const void* ptr) {
  const cuuint64_t dims[3] = {DM, NSTEP * 32, 2}, strides[2] = {DM * 2, (cuuint64_t)NSTEP * 32 * DM * 2};
  const cuuint32_t box[3] = {64, 32, 2};
  return encode(ptr, 3, dims, strides, box);
}
static CUtensorMap make_map_x1(const void* ptr) {
  const cuuint64_t dims[3] = {64, 2 * NSTEP * 32, DM / 64}, strides[2] = {DM * 2, 128};
  const cuuint32_t box[3] = {64, 32, 2};
  return encode(ptr, 3, dims, strides, box);
}
static CUtensorMap make_map_wo(const void* ptr) {
  const cuuint64_t dims[5] = {DM, 2, 4, 4, NH * DH / 32}, strides[4] = {DM * 2, 8 * DM * 2, 2 * DM * 2, 32 * DM * 2};
  const cuuint32_t box[5] = {64, 2, 4, 4, 2};
  return encode(ptr, 5, dims, strides, box);
}

extern "C" void kernel_launch(void* const* d_in, const int* in_sizes, int n_in, void* d_out, int out_size) {
  const bf16 *x = (const bf16*)d_in[0], *mem0 = (const bf16*)d_in[1], *Wo = (const bf16*)d_in[5];
  if (!g_encode) {
    void* p = nullptr; cudaDriverEntryPointQueryResult q;
    cudaGetDriverEntryPoint("cuTensorMapEncodeTiled", &p, cudaEnableDefault, &q);
    g_encode = (PFN_encodeTiled)p;
    int dev = 0;
    cudaGetDevice(&dev);
    cudaDeviceGetAttribute(&g_sms, cudaDevAttrMultiProcessorCount, dev);
    cudaFuncSetAttribute(rec_kernel, cudaFuncAttributeMaxDynamicSharedMemorySize, rec::SMEM);
    cudaFuncSetAttribute(gemm_kernel, cudaFuncAttributeMaxDynamicSharedMemorySize, gm::SMEM);
  }
  void *xn, *o, *x1, *xm, *x2, *hh;
  cudaGetSymbolAddress(&xn, g_xn); cudaGetSymbolAddress(&o, g_o); cudaGetSymbolAddress(&x1, g_x1);
  cudaGetSymbolAddress(&xm, g_xm); cudaGetSymbolAddress(&x2, g_x2); cudaGetSymbolAddress(&hh, g_h);
  RecMaps R;
  for (int i = 0; i < 3; i++) R.w[i] = make_map(d_in[2 + i], DM, NH * DH, 16);
  R.wo = make_map(Wo, NH * DH, DM, 64); R.x[0] = make_map_x(xn); R.x[1] = make_map_x1(xn);
  rec_kernel<<<96, 512, rec::SMEM>>>(R, Wo, mem0, x, 0);
  GemmMaps G;
  G.o = make_map(o, 2 * SEQ, NH * DH, 128); G.wo = make_map_wo(Wo);
  G.x1 = make_map(x1, 2 * SEQ, DM, 64); G.x1s = make_map(x1, 2 * SEQ, DM, 128);
  G.xn = make_map((bf16*)xn + (NSTEP + LAG) * 32 * DM, SEQ, DM, 64);
  G.xm = make_map(xm, 2 * SEQ, DM, 64); G.xms = make_map(xm, 2 * SEQ, DM, 128);
  G.wg = make_map(d_in[8], DM, DF, 64); G.wu = make_map(d_in[9], DM, DF, 64); G.wd = make_map(d_in[10], DF, DM, 64);
  G.h = make_map(hh, 2 * SEQ, DF, 64); G.hs = make_map(hh, 2 * SEQ, DF, 128);
  G.x = make_map(x, SEQ, DM, 64); G.x2 = make_map(x2, SEQ, DM, 64); G.out = make_map(d_out, SEQ, DM, 64); G.outs = make_map(d_out, SEQ, DM, 128);
  cudaLaunchConfig_t cfg = {};
  cfg.gridDim = dim3(g_sms & ~1); cfg.blockDim = dim3(512); cfg.dynamicSmemBytes = gm::SMEM; cfg.stream = cudaStreamPerThread;
  cudaLaunchAttribute at;
  at.id = cudaLaunchAttributeProgrammaticStreamSerialization; at.val.programmaticStreamSerializationAllowed = 1;
  cfg.attrs = &at; cfg.numAttrs = 1;
  cudaLaunchKernelEx(&cfg, gemm_kernel, G);
}
```

```cpp
#include <cuda_runtime.h>
#include <cuda_bf16.h>
#include <cuda.h>
#include <stdint.h>

#define DEVI __device__ __forceinline__
typedef __nv_bfloat16 bf16;

#define LAG 16
constexpr int SEQ = 2048, DM = 1024, NH = 32, DH = 128, DF = 3584, NSEG = 64, NSTEP = NSEG + LAG;
static_assert(NSTEP % 2 == 0, "tags and slots of the exchange buffers return to their initial state");

__device__ __align__(1024) bf16 g_xn[2][NSTEP * 32 * DM];
__device__ __align__(1024) bf16 g_o[2][SEQ * NH * DH];
__device__ __align__(1024) bf16 g_x1[2][SEQ * DM];
__device__ __align__(1024) bf16 g_xm[2][SEQ * DM];
__device__ __align__(1024) bf16 g_x2[SEQ * DM];
__device__ __align__(1024) bf16 g_h[2][SEQ * DF];
__device__ __align__(1024) uint4 g_part[256 * 32 * 8];
__device__ __align__(1024) uint32_t g_ann[2][32][64];
__device__ __align__(1024) uint4 g_mem[2][2048];
__device__ __align__(128) float2 g_stat[3][2][8][128];
__host__ __device__ constexpr int grp(int type, int layer, int blk) { return layer ? 16 * type + blk : 64 + (16 * type + blk) * 32; }
struct Flags {
  int xn[2][16][32];
  int dep[64 + 48 * 32];
  int taken[64];
  int rows[32];
  int part[32];
  int ticket[32];
};
__device__ __align__(128) Flags g_fl;

DEVI uint32_t smem_u32(const void* p) { return (uint32_t)__cvta_generic_to_shared(p); }
DEVI void mbar_init(uint32_t bar, uint32_t cnt) { asm volatile("mbarrier.init.shared::cta.b64 [%0], %1;" :: "r"(bar), "r"(cnt) : "memory"); }
DEVI void mbar_expect_tx(uint32_t bar, uint32_t bytes) { asm volatile("mbarrier.arrive.expect_tx.shared::cta.b64 _, [%0], %1;" :: "r"(bar), "r"(bytes) : "memory"); }
DEVI void mbar_arrive(uint32_t bar) { asm volatile("mbarrier.arrive.shared::cta.b64 _, [%0];" :: "r"(bar) : "memory"); }
DEVI bool mbar_try(uint32_t bar, uint32_t parity) {
  uint32_t p;
  asm volatile("{.reg .pred p; mbarrier.try_wait.parity.shared::cta.b64 p, [%1], %2; selp.u32 %0, 1, 0, p;}" : "=r"(p) : "r"(bar), "r"(parity) : "memory");
  return p;
}
DEVI bool mbar_test(uint32_t bar, uint32_t parity) {
  uint32_t p;
  asm volatile("{.reg .pred p; mbarrier.test_wait.parity.shared::cta.b64 p, [%1], %2; selp.u32 %0, 1, 0, p;}" : "=r"(p) : "r"(bar), "r"(parity) : "memory");
  return p;
}
constexpr int SPIN_BUDGET = 1 << 20;
DEVI void mbar_wait(uint32_t bar, uint32_t parity, int& budget) {
  while (!mbar_try(bar, parity)) { if (--budget < 0) break; }
}
DEVI void trap_if_spent(int budget) { asm volatile("{.reg .pred p; setp.le.s32 p, %0, 0; @p trap;}" :: "r"(budget) : "memory"); }
DEVI void fault_if_spent(int budget) { asm volatile("{.reg .pred p; setp.le.s32 p, %0, 0; @p st.global.u32 [%1], 0;}" :: "r"(budget), "l"(0ull) : "memory"); }
DEVI uint32_t mapa(uint32_t addr, uint32_t rank) { uint32_t r; asm("mapa.shared::cluster.u32 %0, %1, %2;" : "=r"(r) : "r"(addr), "r"(rank)); return r; }
DEVI void cluster_arrive() { asm volatile("barrier.cluster.arrive.release.aligned;" ::: "memory"); }
DEVI void cluster_wait() { asm volatile("barrier.cluster.wait.acquire.aligned;" ::: "memory"); }
DEVI void fence_mbar_init() { asm volatile("fence.mbarrier_init.release.cluster;" ::: "memory"); }
DEVI void fence_proxy_async() { asm volatile("fence.proxy.async.shared::cta;" ::: "memory"); }
DEVI void tma_load_2d(uint32_t dst, const CUtensorMap* m, int c0, int c1, uint32_t bar) {
  asm volatile("cp.async.bulk.tensor.2d.shared::cluster.global.mbarrier::complete_tx::bytes [%0], [%1, {%3, %4}], [%2];"
    :: "r"(dst), "l"(m), "r"(bar), "r"(c0), "r"(c1) : "memory");
}
DEVI void tma_load_5d(uint32_t dst, const CUtensorMap* m, int c0, int c4, uint32_t bar) {
  asm volatile("cp.async.bulk.tensor.5d.shared::cluster.global.mbarrier::complete_tx::bytes [%0], [%1, {%3, %5, %5, %5, %4}], [%2];"
    :: "r"(dst), "l"(m), "r"(bar), "r"(c0), "r"(c4), "r"(0) : "memory");
}
DEVI void tma_prefetch_2d(const CUtensorMap* m, int c0, int c1) {
  asm volatile("cp.async.bulk.prefetch.tensor.2d.L2.global [%0, {%1, %2}];" :: "l"(m), "r"(c0), "r"(c1) : "memory");
}
DEVI void tma_prefetch_5d(const CUtensorMap* m, int c0, int c4) {
  asm volatile("cp.async.bulk.prefetch.tensor.5d.L2.global [%0, {%1, %3, %3, %3, %2}];" :: "l"(m), "r"(c0), "r"(c4), "r"(0) : "memory");
}
#define ELECT "{.reg .pred p; elect.sync _|p, 0xffffffff;\n @p "
DEVI void e_expect_tx(uint32_t bar, uint32_t bytes) { asm volatile(ELECT "mbarrier.arrive.expect_tx.shared::cta.b64 _, [%0], %1;}" :: "r"(bar), "r"(bytes) : "memory"); }
DEVI void e_arrive(uint32_t bar) { asm volatile(ELECT "mbarrier.arrive.shared::cta.b64 _, [%0];}" :: "r"(bar) : "memory"); }
DEVI void e_arrive_cl(uint32_t bar) { asm volatile(ELECT "mbarrier.arrive.shared::cluster.b64 _, [%0];}" :: "r"(bar) : "memory"); }
DEVI void e_tma_2d(uint32_t dst, const CUtensorMap* m, int c0, int c1, uint32_t bar) {
  asm volatile(ELECT "cp.async.bulk.tensor.2d.shared::cluster.global.mbarrier::complete_tx::bytes [%0], [%1, {%3, %4}], [%2];}"
    :: "r"(dst), "l"(m), "r"(bar), "r"(c0), "r"(c1) : "memory");
}
DEVI void e_tma_2d_mc(uint32_t dst, const CUtensorMap* m, int c0, int c1, uint32_t bar) {
  asm volatile(ELECT "cp.async.bulk.tensor.2d.shared::cluster.global.mbarrier::complete_tx::bytes.multicast::cluster [%0], [%1, {%3, %4}], [%2], %5;}"
    :: "r"(dst), "l"(m), "r"(bar), "r"(c0), "r"(c1), "h"((unsigned short)3) : "memory");
}
DEVI void e_st_async32(uint32_t a, uint32_t x, uint32_t bar) {
  asm volatile(ELECT "st.async.weak.shared::cluster.mbarrier::complete_tx::bytes.b32 [%0], %1, [%2];}" :: "r"(a), "r"(x), "r"(bar) : "memory");
}
DEVI void e_tma_store_2d(const CUtensorMap* m, uint32_t src, int c0, int c1) {
  asm volatile(ELECT "cp.async.bulk.tensor.2d.global.shared::cta.bulk_group [%0, {%2, %3}], [%1];}" :: "l"(m), "r"(src), "r"(c0), "r"(c1) : "memory");
}
DEVI void e_flag_add(int* p, int v = 1) {
  asm volatile("{.reg .pred p; elect.sync _|p, 0xffffffff;\n fence.proxy.async.global; @p red.release.gpu.global.add.s32 [%0], %1;}" :: "l"(p), "r"(v) : "memory");
}
DEVI int e_ticket(int* p) { int v = 0; asm volatile(ELECT "atom.relaxed.gpu.global.add.s32 %0, [%1], 1;}" : "+r"(v) : "l"(p) : "memory"); __syncwarp(); return v; }
DEVI int bcast(int v) { return __reduce_max_sync(0xffffffffu, v); }
DEVI int ld_relaxed(const int* p) { int v; asm volatile("ld.relaxed.gpu.global.s32 %0, [%1];" : "=r"(v) : "l"(p) : "memory"); return v; }
DEVI int ld_acquire(const int* p) { int v; asm volatile("ld.acquire.gpu.global.s32 %0, [%1];" : "=r"(v) : "l"(p) : "memory"); return __shfl_sync(0xffffffffu, v, 0); }
DEVI void e_tma_3d(uint32_t dst, const CUtensorMap* m, int c0, int c1, int c2, uint32_t bar) {
  asm volatile(ELECT "cp.async.bulk.tensor.3d.shared::cluster.global.mbarrier::complete_tx::bytes [%0], [%1, {%3, %4, %5}], [%2];}"
    :: "r"(dst), "l"(m), "r"(bar), "r"(c0), "r"(c1), "r"(c2) : "memory");
}
DEVI void e_tma_5d(uint32_t dst, const CUtensorMap* m, int c0, int c4, uint32_t bar) {
  asm volatile(ELECT "cp.async.bulk.tensor.5d.shared::cluster.global.mbarrier::complete_tx::bytes [%0], [%1, {%3, %5, %5, %5, %4}], [%2];}"
    :: "r"(dst), "l"(m), "r"(bar), "r"(c0), "r"(c4), "r"(0) : "memory");
}
DEVI void e_bulk_g2s(uint32_t dst, const void* src, uint32_t bytes, uint32_t bar) {
  asm volatile(ELECT "cp.async.bulk.shared::cluster.global.mbarrier::complete_tx::bytes [%0], [%1], %2, [%3];}" :: "r"(dst), "l"(src), "r"(bytes), "r"(bar) : "memory");
}
DEVI void e_prefetch(const void* src, uint32_t bytes) {
  asm volatile(ELECT "cp.async.bulk.prefetch.L2.global [%0], %1;}" :: "l"(src), "r"(bytes) : "memory");
}
DEVI void bulk_commit() { asm volatile("cp.async.bulk.commit_group;" ::: "memory"); }
template<int N> DEVI void bulk_wait_read() { asm volatile("cp.async.bulk.wait_group.read %0;" :: "n"(N) : "memory"); }
template<int N> DEVI void bulk_wait() { asm volatile("cp.async.bulk.wait_group %0;" :: "n"(N) : "memory"); }
template<int ID, int N> DEVI void nbar_sync() { asm volatile("bar.sync %0, %1;" :: "n"(ID), "n"(N) : "memory"); }
template<int ID, int N> DEVI void nbar_arrive() { asm volatile("bar.arrive %0, %1;" :: "n"(ID), "n"(N) : "memory"); }
DEVI void nbar_sync_r(int id, int n) { asm volatile("bar.sync %0, %1;" :: "r"(id), "r"(n) : "memory"); }
DEVI void nbar_arrive_r(int id, int n) { asm volatile("bar.arrive %0, %1;" :: "r"(id), "r"(n) : "memory"); }
template<int R> DEVI void reg_inc() { asm volatile("setmaxnreg.inc.sync.aligned.u32 %0;" :: "n"(R)); }
template<int R> DEVI void reg_dec() { asm volatile("setmaxnreg.dec.sync.aligned.u32 %0;" :: "n"(R)); }
DEVI void wg_fence() { asm volatile("wgmma.fence.sync.aligned;" ::: "memory"); }
DEVI void wg_commit() { asm volatile("wgmma.commit_group.sync.aligned;" ::: "memory"); }
template<int N> DEVI void wg_wait() { asm volatile("wgmma.wait_group.sync.aligned %0;" :: "n"(N) : "memory"); }
DEVI uint32_t pack_bf16(float lo, float hi) { uint32_t r; asm("cvt.rn.bf16x2.f32 %0, %1, %2;" : "=r"(r) : "f"(hi), "f"(lo)); return r; }
DEVI float bf_lo(uint32_t v) { return __uint_as_float(v << 16); }
DEVI float bf_hi(uint32_t v) { return __uint_as_float(v & 0xffff0000u); }
DEVI uint32_t movmat(uint32_t a) { uint32_t r; asm volatile("movmatrix.sync.aligned.m8n8.trans.b16 %0, %1;" : "=r"(r) : "r"(a)); return r; }
DEVI void ldsm4(uint32_t addr, uint32_t& r0, uint32_t& r1, uint32_t& r2, uint32_t& r3) {
  asm volatile("ldmatrix.sync.aligned.m8n8.x4.shared.b16 {%0,%1,%2,%3}, [%4];" : "=r"(r0), "=r"(r1), "=r"(r2), "=r"(r3) : "r"(addr) : "memory");
}
DEVI void ldsm4t(uint32_t addr, uint32_t& r0, uint32_t& r1, uint32_t& r2, uint32_t& r3) {
  asm volatile("ldmatrix.sync.aligned.m8n8.x4.trans.shared.b16 {%0,%1,%2,%3}, [%4];" : "=r"(r0), "=r"(r1), "=r"(r2), "=r"(r3) : "r"(addr) : "memory");
}
DEVI void stsm4(uint32_t addr, uint32_t r0, uint32_t r1, uint32_t r2, uint32_t r3) {
  asm volatile("stmatrix.sync.aligned.m8n8.x4.shared.b16 [%0], {%1,%2,%3,%4};" :: "r"(addr), "r"(r0), "r"(r1), "r"(r2), "r"(r3) : "memory");
}
DEVI uint4 lds128(uint32_t a) { uint4 v; asm volatile("ld.shared.v4.u32 {%0,%1,%2,%3}, [%4];" : "=r"(v.x), "=r"(v.y), "=r"(v.z), "=r"(v.w) : "r"(a) : "memory"); return v; }
DEVI uint32_t lds32v(uint32_t a) { uint32_t v; asm volatile("ld.volatile.shared.u32 %0, [%1];" : "=r"(v) : "r"(a) : "memory"); return v; }
DEVI void sts32v(uint32_t a, uint32_t v) { asm volatile("st.volatile.shared.u32 [%0], %1;" :: "r"(a), "r"(v) : "memory"); }
DEVI void st_async128(uint32_t a, uint32_t x, uint32_t y, uint32_t z, uint32_t w, uint32_t bar) {
  asm volatile("st.async.weak.shared::cluster.mbarrier::complete_tx::bytes.v4.b32 [%0], {%1,%2,%3,%4}, [%5];" :: "r"(a), "r"(x), "r"(y), "r"(z), "r"(w), "r"(bar) : "memory");
}
DEVI void st_async32(uint32_t a, uint32_t x, uint32_t bar) {
  asm volatile("st.async.weak.shared::cluster.mbarrier::complete_tx::bytes.b32 [%0], %1, [%2];" :: "r"(a), "r"(x), "r"(bar) : "memory");
}
DEVI void st_cl128(bool own, uint32_t a, uint32_t x, uint32_t y, uint32_t z, uint32_t w, uint32_t bar) {
  asm volatile("{.reg .pred p; setp.ne.u32 p, %6, 0; @p st.shared.v4.b32 [%0], {%1,%2,%3,%4};\n"
               "@!p st.async.weak.shared::cluster.mbarrier::complete_tx::bytes.v4.b32 [%0], {%1,%2,%3,%4}, [%5];}"
               :: "r"(a), "r"(x), "r"(y), "r"(z), "r"(w), "r"(bar), "r"((uint32_t)own) : "memory");
}
DEVI void st_cl32(bool own, uint32_t a, uint32_t x, uint32_t bar) {
  asm volatile("{.reg .pred p; setp.ne.u32 p, %3, 0; @p st.shared.b32 [%0], %1;\n"
               "@!p st.async.weak.shared::cluster.mbarrier::complete_tx::bytes.b32 [%0], %1, [%2];}" :: "r"(a), "r"(x), "r"(bar), "r"((uint32_t)own) : "memory");
}
DEVI uint4 ldg_rlx128(const void* p) {
  uint4 v;
  asm volatile("ld.relaxed.gpu.global.v4.b32 {%0,%1,%2,%3}, [%4];" : "=r"(v.x), "=r"(v.y), "=r"(v.z), "=r"(v.w) : "l"(p) : "memory");
  return v;
}
DEVI void stg_rlx128(void* p, uint32_t x, uint32_t y, uint32_t z, uint32_t w) {
  asm volatile("st.relaxed.gpu.global.v4.b32 [%0], {%1,%2,%3,%4};" :: "l"(p), "r"(x), "r"(y), "r"(z), "r"(w) : "memory");
}
DEVI void stg128(void* p, uint32_t x, uint32_t y, uint32_t z, uint32_t w) {
  asm volatile("st.global.v4.b32 [%0], {%1,%2,%3,%4};" :: "l"(p), "r"(x), "r"(y), "r"(z), "r"(w) : "memory");
}
DEVI void stg_rlx64(void* p, uint32_t x, uint32_t y) { asm volatile("st.relaxed.gpu.global.v2.b32 [%0], {%1,%2};" :: "l"(p), "r"(x), "r"(y) : "memory"); }
DEVI void stg_rlx32(void* p, uint32_t x) { asm volatile("st.relaxed.gpu.global.b32 [%0], %1;" :: "l"(p), "r"(x) : "memory"); }
DEVI uint32_t clock32() { uint32_t c; asm volatile("mov.u32 %0, %%clock;" : "=r"(c) :: "memory"); return c; }
DEVI uint32_t gtime() { uint32_t c; asm volatile("mov.u32 %0, %%globaltimer_lo;" : "=r"(c) :: "memory"); return c; }
DEVI void wait_time(uint32_t t, int& budget) { while ((int)(gtime() - t) < 0 && --budget > 0) {} }
DEVI uint2 ldg_rlx64(const void* p) { uint2 v; asm volatile("ld.relaxed.gpu.global.v2.b32 {%0,%1}, [%2];" : "=r"(v.x), "=r"(v.y) : "l"(p) : "memory"); return v; }
DEVI void sts16(uint32_t a, uint32_t x) { asm volatile("st.shared.b16 [%0], %1;" :: "r"(a), "h"((unsigned short)x) : "memory"); }
DEVI void sts128(uint32_t a, uint32_t x) { asm volatile("st.shared.v4.b32 [%0], {%1,%1,%1,%1};" :: "r"(a), "r"(x) : "memory"); }
DEVI void arrive_if_eq(uint32_t bar, int a, int b) { asm volatile("{.reg .pred p; setp.eq.s32 p, %1, %2; @p mbarrier.arrive.shared::cta.b64 _, [%0];}" :: "r"(bar), "r"(a), "r"(b) : "memory"); }
DEVI void arrive_cl_if_eq(uint32_t bar, int a, int b) { asm volatile("{.reg .pred p; setp.eq.s32 p, %1, %2; @p mbarrier.arrive.shared::cluster.b64 _, [%0];}" :: "r"(bar), "r"(a), "r"(b) : "memory"); }
template<int ID, int N> DEVI bool nbar_or(bool x) {
  uint32_t r;
  asm volatile("{.reg .pred p, q; setp.ne.u32 p, %1, 0; bar.red.or.pred q, %2, %3, p; selp.u32 %0, 1, 0, q;}" : "=r"(r) : "r"((uint32_t)x), "n"(ID), "n"(N) : "memory");
  return __any_sync(0xffffffffu, r);
}
DEVI void spin_until(uint32_t t0, int d) { while ((int)(clock32() - t0) < d) {} }
DEVI void flag_wait(const int* p, int n, int& budget) {
  while (ld_acquire(p) < n && --budget > 0) __nanosleep(128);
  asm volatile("fence.proxy.async.global;" ::: "memory");
}

#define F4(C, o)  C(d[o+0]), C(d[o+1]), C(d[o+2]), C(d[o+3])
#define F8(C, o)  F4(C, o), F4(C, o+4)
#define F32(C, o) F8(C, o), F8(C, o+8), F8(C, o+16), F8(C, o+24)
#define R4  "{%0,%1,%2,%3}"
#define R8  "{%0,%1,%2,%3,%4,%5,%6,%7}"
#define R16 "{%0,%1,%2,%3,%4,%5,%6,%7,%8,%9,%10,%11,%12,%13,%14,%15}"
#define R20 "{%0,%1,%2,%3,%4,%5,%6,%7,%8,%9,%10,%11,%12,%13,%14,%15,%16,%17,%18,%19}"
#define R32 "{%0,%1,%2,%3,%4,%5,%6,%7,%8,%9,%10,%11,%12,%13,%14,%15,%16,%17,%18,%19,%20,%21,%22,%23,%24,%25,%26,%27,%28,%29,%30,%31}"
#define R64 "{%0,%1,%2,%3,%4,%5,%6,%7,%8,%9,%10,%11,%12,%13,%14,%15,%16,%17,%18,%19,%20,%21,%22,%23,%24,%25,%26,%27,%28,%29,%30,%31," \
  "%32,%33,%34,%35,%36,%37,%38,%39,%40,%41,%42,%43,%44,%45,%46,%47,%48,%49,%50,%51,%52,%53,%54,%55,%56,%57,%58,%59,%60,%61,%62,%63}"
template<uint32_t OFF, uint32_t LBO, uint32_t SBO, uint32_t SW, int T> struct Op {
  static constexpr uint32_t lo = (OFF >> 4) | ((LBO >> 4) << 16), hi = (SBO >> 4) | (SW << 30);
  static constexpr int t = T;
};
DEVI uint32_t desc_base(uint32_t addr) { return (addr & 0x3FFFF) >> 4; }
#define RS_ASM(SHAPE, REGS, A0, A1, A2, A3, B, LO, HI, T, SD) \
  "{.reg .b64 tb; .reg .b32 lb; add.u32 lb, " B ", " LO "; mov.b64 tb, {lb, " HI "};\n" \
  "wgmma.mma_async.sync.aligned." SHAPE ".f32.bf16.bf16 " REGS ", {" A0 "," A1 "," A2 "," A3 "}, tb, " SD ", 1, 1, " T ";}"
#define WG_RS(NAME, SHAPE, REGS, LIST, ...) \
  template<int ACC, class OB> DEVI void NAME(float* d, const uint32_t* a, uint32_t b) { \
    if (ACC) asm volatile(RS_ASM(SHAPE, REGS, __VA_ARGS__) \
      : LIST("+f") : "r"(a[0]), "r"(a[1]), "r"(a[2]), "r"(a[3]), "r"(b), "n"(OB::lo), "n"(OB::hi), "n"(OB::t), "n"(ACC & 1)); \
    else asm volatile(RS_ASM(SHAPE, REGS, __VA_ARGS__) \
      : LIST("=f") : "r"(a[0]), "r"(a[1]), "r"(a[2]), "r"(a[3]), "r"(b), "n"(OB::lo), "n"(OB::hi), "n"(OB::t), "n"(0)); \
  }
#define SS_ASM(SHAPE, REGS, A, B, LA, HA, TA, LB, HB, TB, SD) \
  "{.reg .b64 ta, tb; .reg .b32 la, lb; add.u32 la, " A ", " LA "; mov.b64 ta, {la, " HA "}; add.u32 lb, " B ", " LB "; mov.b64 tb, {lb, " HB "};\n" \
  "wgmma.mma_async.sync.aligned." SHAPE ".f32.bf16.bf16 " REGS ", ta, tb, " SD ", 1, 1, " TA ", " TB ";}"
#define WG_SS(NAME, SHAPE, REGS, LIST, ...) \
  template<int ACC, class OA, class OB> DEVI void NAME(float* d, uint32_t a, uint32_t b) { \
    if (ACC) asm volatile(SS_ASM(SHAPE, REGS, __VA_ARGS__) \
      : LIST("+f") : "r"(a), "r"(b), "n"(OA::lo), "n"(OA::hi), "n"(OA::t), "n"(OB::lo), "n"(OB::hi), "n"(OB::t), "n"(ACC & 1)); \
    else asm volatile(SS_ASM(SHAPE, REGS, __VA_ARGS__) \
      : LIST("=f") : "r"(a), "r"(b), "n"(OA::lo), "n"(OA::hi), "n"(OA::t), "n"(OB::lo), "n"(OB::hi), "n"(OB::t), "n"(0)); \
  }
#define L4(C)  F4(C, 0)
#define L8(C)  F8(C, 0)
#define L16(C) F8(C, 0), F8(C, 8)
#define L20(C) F8(C, 0), F8(C, 8), F4(C, 16)
#define L32(C) F32(C, 0)
WG_RS(wg_rs8, "m64n8k16", R4, L4, "%4", "%5", "%6", "%7", "%8", "%9", "%10", "%11", "%12")
WG_RS(wg_rs16, "m64n16k16", R8, L8, "%8", "%9", "%10", "%11", "%12", "%13", "%14", "%15", "%16")
WG_RS(wg_rs32, "m64n32k16", R16, L16, "%16", "%17", "%18", "%19", "%20", "%21", "%22", "%23", "%24")
WG_SS(wg_ss32, "m64n32k16", R16, L16, "%16", "%17", "%18", "%19", "%20", "%21", "%22", "%23", "%24")
WG_RS(wg_rs64, "m64n64k16", R32, L32, "%32", "%33", "%34", "%35", "%36", "%37", "%38", "%39", "%40")
WG_SS(wg_ss8, "m64n8k16", R4, L4, "%4", "%5", "%6", "%7", "%8", "%9", "%10", "%11", "%12")
WG_SS(wg_ss16, "m64n16k16", R8, L8, "%8", "%9", "%10", "%11", "%12", "%13", "%14", "%15", "%16")
WG_SS(wg_ss40, "m64n40k16", R20, L20, "%20", "%21", "%22", "%23", "%24", "%25", "%26", "%27", "%28")
WG_SS(wg_ss64, "m64n64k16", R32, L32, "%32", "%33", "%34", "%35", "%36", "%37", "%38", "%39", "%40")
#define L64(C) F32(C, 0), F32(C, 32)
WG_SS(wg_ss128, "m64n128k16", R64, L64, "%64", "%65", "%66", "%67", "%68", "%69", "%70", "%71", "%72")
template<int I> struct IC { __host__ __device__ constexpr operator int() const { return I; } };
template<int I, int N, class F> DEVI void sfor(F&& f) {
  if constexpr (I < N) { f(IC<I>{}); sfor<I + 1, N>(f); }
}

#define R_CL 6
namespace rec {
constexpr int NHI = 36, NLO = 5, NRS = NHI + NLO, NSS = 64 - NRS;
constexpr uint32_t WS = 0;
constexpr uint32_t WO = 2 * NSS * 2048;
constexpr uint32_t RING = WO + 65536;
constexpr uint32_t QB = RING + 40960, RG = 2080, POSQ = 0x64210, POSK = 0xB9753, POSV = 0xEDCA8;
#define JA 2
constexpr uint32_t WA = QB;
constexpr uint32_t OM = QB + 9 * RG, OMS = 2 * RG;
constexpr uint32_t OM2 = QB + 16384, OM2S = 2048;
constexpr uint32_t WH = QB + 20480;
constexpr uint32_t B_PART = QB + 15 * RG - 32;
constexpr uint32_t PM0 = QB + 16384, PM1 = QB + 15 * RG, PM2 = PM1 + 256;
constexpr uint32_t BARS = PM2 + 128;
constexpr uint32_t B_FULL = BARS, B_EMPTY = BARS + 40, B_MLAND = BARS + 80, B_QK = BARS + 112, B_V = BARS + 120, B_OM = BARS + 128,
                   B_WA = BARS + 136, B_SDONE = BARS + 144, B_BFREE = BARS + 152, B_W1 = PM1, B_W2 = PM1 + 8, B_WO = PM1 + 16;
constexpr uint32_t SMEM = BARS + 160;
static_assert(SMEM <= 232448 && QB % 1024 == 0, "smem map");
constexpr int R1 = (PM1 - WO) / 4096;
constexpr int NB_WO = 1, NB_ST = 2, NB_P = 3, NB_TR = 4, NB_X = 5, NB_G = 6, NB_G1 = 7, NB_G2 = 8, NB_G4 = 9, NB_S = 10;
__host__ __device__ constexpr bool is_lo(int j) { return j % 12 == 8; }
__host__ __device__ constexpr int lo_before(int j) { return (j + 3) / 12; }
__host__ __device__ constexpr int ss_before(int j) { return (j - lo_before(j)) * NSS / (64 - NLO); }
__host__ __device__ constexpr bool is_ss(int j) { return ss_before(j + 1) != ss_before(j); }
__host__ __device__ constexpr int reg_idx(int j) { return is_lo(j) ? NHI + lo_before(j) : j - ss_before(j) - lo_before(j); }
#define LOQ(i) ((0x12010 >> (4 * (i))) & 3)
template<int j> using OpW = Op<WS + ss_before(j) * 2048, 16, 1024, 1, 1>;
#define P_G1 1
#define P_G2 3
#define P_G2L 0
#define P_OS 1
#define P_NA 6
#define P_G4 10
#define P_G5 12
#define P_FW 0
#define P_SEND 0xff3f2f10u
#define P_WB 2
#define P_WOL 0
#define P_G4L 0
#define P_S1 1
#define P_S2 2
#define P_S0 3
#define P_MB 0
#define P_S4 5
#define P_S5 6
constexpr uint32_t SLOT1 = 0x32410324, USE1 = 0x22111110;
DEVI bool single(int s) { return s < LAG - 1 || s >= NSEG - 1; }
#define TUN(i, v) (v)
}
#define PROFW(wq, i)
DEVI uint32_t mapr(int h, uint32_t addr, int rank) { return mapa(addr, rank + (R_CL == 6 ? (h & 1) * 3 : 0)); }
template<int N> DEVI void pin(float* d) {
#pragma unroll
  for (int i = 0; i < N; i++) asm volatile("" : "+f"(d[i]) :: "memory");
}
DEVI void keep(const void* a) { asm volatile("{.reg .pred p; setp.eq.u64 p, %0, 0; vote.sync.any.pred p, p, 0xffffffff; @p exit;}" :: "l"(a) : "memory"); }
DEVI int lane_reg() { return __shfl_sync(0xffffffffu, threadIdx.x & 31, threadIdx.x & 31); }
#define LANE_NOW [[maybe_unused]] const int lane = lane0 + ((uint32_t)budget >> 30), g = lane >> 2, c = lane & 3

DEVI void rec_proj(const uint32_t sb, const int h, const int rank, const int w, const CUtensorMap* mW, const CUtensorMap* mWo, const uint32_t zero) {
  using namespace rec;
  const int lane0 = lane_reg(), wg = w >> 2, ww = w & 3;
  int budget = SPIN_BUDGET;
  uint32_t wr[NRS * 4];
  {
    LANE_NOW;
    const uint32_t wsw = ((lane & 7) + (lane >> 4) * 8) * 128 + (((ww * 2 + ((lane >> 3) & 1)) ^ (lane & 7)) << 4);
    mbar_wait(sb + B_W1, 0, budget);
#pragma unroll
    for (int r = 0; r < R1; r++) ldsm4t(sb + WO + (wg * R1 + r) * 2048 + wsw, wr[4*r], wr[4*r+1], wr[4*r+2], wr[4*r+3]);
    fence_proxy_async();
    nbar_sync<NB_ST, 256>();
    if (w == 0) {
      if (lane == 0) { mbar_expect_tx(sb + B_W2, (NRS - R1) * 4096); mbar_expect_tx(sb + B_WO, rank == 2 ? 65536 + 16384 + 8192 : 65536); }
      __syncwarp();
      for (int i = lane; i < 128; i += 32) {
        const int j = i & 63, t = i >> 6, r = reg_idx(j);
        if (!is_ss(j) && r >= R1) tma_load_2d(sb + RING + (t * (NRS - R1) + r - R1) * 2048, mW, h * DH + t * 64, j * 16, sb + B_W2);
      }
      const int t0 = (rank + 1) % 3;
      if (lane < 8) tma_load_2d(sb + WO + lane * 8192, mWo, (3 * ((lane >> 1) + (lane >> 1 >= JA)) + t0) * 64, h * DH + (lane & 1) * 64, sb + B_WO);
      else if (rank < 2 && lane < 10) tma_prefetch_2d(mWo, (3 * JA + t0) * 64, h * DH + (lane & 1) * 64);
      else if (rank == 2 && lane < 11) tma_load_2d(lane < 10 ? sb + WA + (lane - 8) * 8192 : sb + WH, mWo, lane < 10 ? 3 * JA * 64 : 15 * 64, h * DH + (lane > 8) * 64, sb + B_WO);
    }
    mbar_wait(sb + B_W2, 0, budget);
#pragma unroll
    for (int r = R1; r < NRS; r++) ldsm4t(sb + RING + (wg * (NRS - R1) + r - R1) * 2048 + wsw, wr[4*r], wr[4*r+1], wr[4*r+2], wr[4*r+3]);
    fence_proxy_async();
    cluster_arrive(); cluster_wait();
  }
  const uint32_t d0 = desc_base(sb), da = d0 + wg * (NSS * 128);
  const uint32_t pos = rank == 0 ? POSQ : rank == 1 ? POSK : POSV, bar = rank == 2 ? B_V : B_QK;
  uint32_t stg[3][4] = {}, pk[16] = {};
  auto stage = [&](uint32_t* t, int r) {
#pragma unroll
    for (int i = 0; i < 4; i++) asm volatile("xor.b32 %0, %1, %2;" : "+r"(t[i]) : "r"(wr[4 * r + i]), "r"(zero));
  };
#pragma unroll 1
  for (int s = -1; s < NSTEP; s++) {
    const uint32_t fl = single(s) ? (s + 1) & 1 : 0;
    if (s >= 0) {
      float d[8];
      stage(stg[0], NHI);
      mbar_wait(sb + B_FULL, 0, budget);
      PROFW(0, 16);
      sfor<0, 8>([&](auto E) {
        constexpr int e = E, q = e >> 1;
        wg_fence();
        sfor<8 * e, 8 * e + 8>([&](auto J) {
          constexpr int j = J;
          typedef Op<RING + j * 512, 256, 128, 0, 1> OB;
          if constexpr (is_ss(j)) wg_ss16<j != 0, OpW<j>, OB>(d, da, d0);
          else wg_rs16<j != 0, OB>(d, is_lo(j) ? stg[LOQ(lo_before(j))] : wr + 4 * reg_idx(j), d0);
        });
        wg_commit();
        if constexpr (e == 0) { if (s > 0) mbar_wait(sb + B_BFREE, (s & 1) ^ 1, budget); }
        if constexpr (e > 0 && !(e & 1)) {
          wg_wait<1>();
          arrive_if_eq(sb + B_EMPTY + 8 * (q - 1), lane0, ww * 32);
        }
        if constexpr (e < 6 && !(e & 1)) sfor<lo_before(16 * q + 16), lo_before(16 * q + 32)>([&](auto I) { constexpr int i = I; stage(stg[LOQ(i)], NHI + i); });
        if constexpr (e < 6 && (e & 1) == P_FW) mbar_wait(sb + B_FULL + 8 * (q + 1), q ? fl : 0, budget);
        if constexpr (((P_SEND >> (4 * e)) & 15) < 4) {
          constexpr int n = (P_SEND >> (4 * e)) & 15;
          LANE_NOW;
          const uint32_t r = mapr(h, sb, n >> 1);
          uint32_t t[4];
#pragma unroll
          for (int i = 0; i < 4; i++) { if (n == 0) t[i] = pk[i]; else asm volatile("xor.b32 %0, %1, %2;" : "=r"(t[i]) : "r"(pk[4*n+i]), "r"(zero)); }
          st_cl128(rank == n >> 1, r + QB + ((pos >> (4 + 4 * c)) & 15) * RG + w * 256 + (n & 1) * 128 + g * 16, t[0], t[1], t[2], t[3], r + bar);
        }
      });
      LANE_NOW;
      const uint32_t dst = QB + (pos & 15) * RG + w * 256 + lane * 4;
      wg_wait<0>();
      pin<8>(d);
      {
        const uint32_t x0 = pack_bf16(d[0], d[1]), x1 = pack_bf16(d[2], d[3]), y0 = pack_bf16(d[4], d[5]), y1 = pack_bf16(d[6], d[7]);
        const uint32_t r = mapr(h, sb, rank == 0);
        if (rank < 2) { sts32v(sb + dst, rank ? y0 : x0); sts32v(sb + dst + 128, rank ? y1 : x1); fence_proxy_async(); }
        st_async32(r + dst, rank ? x0 : y0, r + bar); st_async32(r + dst + 128, rank ? x1 : y1, r + bar);
        if (rank < 2) e_arrive(sb + B_QK);
        else { const uint32_t r1 = mapr(h, sb, 1); st_async32(r1 + dst, y0, r1 + bar); st_async32(r1 + dst + 128, y1, r1 + bar); }
      }
      PROFW(0, 17);
      if (s == NSTEP - 1) break;
      arrive_if_eq(sb + B_EMPTY + 24, lane0, ww * 32);
    } else e_arrive(sb + B_EMPTY + 8 * ww);
    const bool gate = rank < 2 && s >= 0;
    if (single(s)) {
      float d[16];
      sfor<0, 8>([&](auto C) {
        constexpr int cc = C, sl = (SLOT1 >> (4 * cc)) & 15;
        if constexpr (cc == 0) mbar_wait(sb + B_FULL + 8 * sl, 0, budget);
        if constexpr (cc == P_S1) { if (gate) nbar_sync<NB_G1, 384>(); }
        if constexpr (cc == P_S2) { if (gate) nbar_sync<NB_G2, 384>(); }
        if constexpr (cc == P_S0) nbar_sync<NB_WO, 384>();
        if constexpr (cc == P_S4 || cc == P_S5) { if (gate && cc == (rank ? P_S5 : P_S4)) nbar_sync<NB_G4, 384>(); }
        if constexpr (lo_before(cc * 8 + 8) != lo_before(cc * 8)) stage(stg[0], NHI + lo_before(cc * 8));
        wg_fence();
        sfor<0, 8>([&](auto I) {
          constexpr int i = I, j = cc * 8 + i;
          typedef Op<RING + sl * 8192 + (i >> 2) * 4096 + (i & 3) * 32, 16, 1024, 1, 0> OB;
          if constexpr (is_ss(j)) wg_ss32<j != 0, OpW<j>, OB>(d, da, d0);
          else wg_rs32<j != 0, OB>(d, is_lo(j) ? stg[0] : wr + 4 * reg_idx(j), d0);
        });
        wg_commit();
        if constexpr (cc < 7) {
          constexpr int sn = (SLOT1 >> (4 * cc + 4)) & 15;
          mbar_wait(sb + B_FULL + 8 * sn, ((USE1 >> (4 * cc + 4)) & 1) ^ (sn >> 1 == 1 ? fl : 0), budget);
        }
        wg_wait<0>();
        arrive_if_eq(sb + B_EMPTY + 8 * sl, lane0, ww * 32);
      });
      pin<16>(d);
      PROFW(0, 20);
#pragma unroll
      for (int i = 0; i < 8; i++) pk[i] = pk[8 + i] = pack_bf16(d[4 * (i & 3) + ((i >> 1) & 2)], d[4 * (i & 3) + ((i >> 1) & 2) + 1]);
      continue;
    }
    float d[32];
    sfor<0, 16>([&](auto C) {
      constexpr int cc = C, sl = (cc + 4) % 5;
      if constexpr (cc == 0) mbar_wait(sb + B_FULL + 8 * sl, 0, budget);
      if constexpr (cc == P_G1) { if (gate) nbar_sync<NB_G1, 384>(); }
      if constexpr (cc == P_G2) { if (gate) nbar_sync<NB_G2, 384>(); }
      if constexpr (cc == P_NA) {
        PROFW(0, 18);
        nbar_sync<NB_WO, 384>();
      }
      if constexpr (cc == P_G4 || cc == P_G5) { if (gate && cc == (rank ? P_G5 : P_G4)) nbar_sync<NB_G4, 384>(); }
      wg_fence();
      sfor<0, 4>([&](auto I) {
        constexpr int i = I, j = cc * 4 + i;
        typedef Op<RING + sl * 8192 + i * 32, 16, 1024, 1, 0> OB;
        if constexpr (is_ss(j)) wg_ss64<j != 0, OpW<j>, OB>(d, da, d0);
        else wg_rs64<j != 0, OB>(d, is_lo(j) ? stg[0] : wr + 4 * reg_idx(j), d0);
      });
      wg_commit();
      if constexpr (cc == P_NA) PROFW(0, 19);
      if constexpr (cc < 15) {
        if constexpr (is_lo(cc * 4 + 4)) stage(stg[0], reg_idx(cc * 4 + 4));
        mbar_wait(sb + B_FULL + 8 * ((sl + 1) % 5), ((cc + 5) / 5) & 1, budget);
      }
      wg_wait<0>();
      arrive_if_eq(sb + B_EMPTY + 8 * sl, lane0, ww * 32);
    });
    pin<32>(d);
    PROFW(0, 20);
#pragma unroll
    for (int i = 0; i < 16; i++) pk[i] = pack_bf16(d[16 * (i >> 3) + 4 * (i & 3) + ((i >> 1) & 2)], d[16 * (i >> 3) + 4 * (i & 3) + ((i >> 1) & 2) + 1]);
  }
}

DEVI float softmax_row(float* v, uint32_t* p) {
  constexpr float SC = 0.08838834764831845f * 1.4426950408889634f;
  float m = fmaxf(fmaxf(fmaxf(fmaxf(v[0], v[1]), fmaxf(v[2], v[3])), fmaxf(fmaxf(v[4], v[5]), fmaxf(v[6], v[7]))), fmaxf(v[8], v[9]));
  m = fmaxf(m, __shfl_xor_sync(0xffffffffu, m, 1));
  m = fmaxf(m, __shfl_xor_sync(0xffffffffu, m, 2));
  const float ms = -m * SC, mh = fmaf(m, -SC, -1.f);
#pragma unroll
  for (int i = 0; i < 10; i++) asm("ex2.approx.ftz.f32 %0, %1;" : "=f"(v[i]) : "f"(fmaf(v[i], SC, i < 8 ? ms : mh)));
#pragma unroll
  for (int n = 0; n < 5; n++) p[n] = pack_bf16(v[2*n], v[2*n+1]);
  return fmaf(v[8] + v[9], 2.f, ((v[0] + v[1]) + (v[2] + v[3])) + ((v[4] + v[5]) + (v[6] + v[7])));
}

template<bool ATT>
DEVI void rec_attn(const uint32_t sb, int h, int rank, int w, const bf16* __restrict__ Wo, const bf16* __restrict__ mem0) {
  using namespace rec;
  const int lane0 = lane_reg();
  int budget = SPIN_BUDGET;
  constexpr int NT = ATT ? 5 : 6;
  uint32_t wl[16];
  if (!ATT) {
    LANE_NOW;
#pragma unroll
    for (int i = 0; i < 16; i++) {
      const int dh = 8 * (i >> 1) + 2 * c;
      const unsigned short* p = (const unsigned short*)Wo + (size_t)(h * DH + dh) * DM + 15 * 64 + 16 * w + 8 * (i & 1) + g;
      wl[i] = p[0] | (uint32_t)p[DM] << 16;
    }
  }
  cluster_arrive(); cluster_wait();
  const uint32_t d0 = desc_base(sb);
  uint32_t pph = 0;
#pragma unroll 1
  for (int s = -1; s < NSTEP; s++) {
    asm volatile("" : "+r"(h), "+r"(rank), "+r"(w));
    const uint32_t sp = s & 1;
    const int t0 = ATT ? rank + 1 : 0;
    const bool more = s + 1 < NSTEP;
    if (s == 0) mbar_wait(sb + B_WO, 0, budget);
    float hold[10] = {0, 0, 0, 0, 0, 0, 0, 0, 0, 0};
    if (ATT && s >= 0) {
      float sc[20];
      LANE_NOW;
      mbar_wait(sb + B_QK, sp, budget);
      PROFW(0, 1);
      fence_proxy_async();
      wg_fence();
      sfor<0, 8>([&](auto K) { constexpr int k = K; wg_ss40<k != 0, Op<QB + k * 256, 128, RG, 0, 1>, Op<QB + 3 * RG + k * 256, 128, 2 * RG, 0, 1>>(sc, d0, d0); });
      wg_commit();
      if (P_G1 < 16 && more) nbar_arrive<NB_G1, 384>();
      mbar_wait(sb + B_V, sp, budget);
      wg_wait<0>();
      pin<20>(sc);
      if (w == 3 && more) nbar_arrive<NB_S, 64>();
      PROFW(1, 2);
      if (w == 0) {
        uint32_t p[5];
        float v[10];
#pragma unroll
        for (int i = 0; i < 10; i++) v[i] = sc[4 * (i >> 1) + (i & 1)];
        softmax_row(v, p);
        const uint32_t a = sb + lane * 4;
        sts32v(a + PM0, p[0]); sts32v(a + PM0 + 128, p[1]); sts32v(a + PM1, p[2]); sts32v(a + PM1 + 128, p[3]); sts32v(a + PM2, p[4]);
      }
      if (more) {
        float rs[4], ot[2][4];
        uint32_t one[4];
#pragma unroll
        for (int i = 0; i < 4; i++) one[i] = 0x3F803F80u + ((uint32_t)budget >> (31 - i));
        typedef Op<PM0, 128, 128, 0, 0> P0; typedef Op<PM1, 128, 128, 0, 0> P1; typedef Op<PM2, 0, 128, 0, 0> P2;
        fence_proxy_async();
        nbar_sync<NB_P, 128>();
        PROFW(0, 3);
        wg_fence();
        wg_rs8<0, P0>(rs, one, d0); wg_rs8<1, P1>(rs, one, d0); wg_rs8<1, P2>(rs, one, d0);
        wg_commit();
        sfor<0, 2>([&](auto T) {
          constexpr int t = T;
          wg_ss8<0, Op<QB + 8 * RG + t * 1024, 2 * RG, 128, 0, 0>, P0>(ot[t], d0, d0);
          wg_ss8<1, Op<QB + 12 * RG + t * 1024, RG, 128, 0, 0>, P1>(ot[t], d0, d0);
          wg_ss8<1, Op<QB + 14 * RG + t * 1024, 0, 128, 0, 0>, P2>(ot[t], d0, d0);
        });
        wg_commit();
        if (P_G2 < 16 && !P_G2L) nbar_arrive<NB_G2, 384>();
        const uint32_t oa = w * 256 + lane * 4, r1 = mapr(h, sb, rank ^ 1), r2 = mapr(h, sb, 2);
        mbar_wait(sb + B_SDONE, sp, budget);
        wg_wait<1>();
        pin<4>(rs);
        float i0, i1;
        asm volatile("rcp.approx.ftz.f32 %0, %1;" : "=f"(i0) : "f"(rs[0]));
        asm volatile("rcp.approx.ftz.f32 %0, %1;" : "=f"(i1) : "f"(rs[1]));
        wg_wait<0>();
        pin<4>(ot[0]); pin<4>(ot[1]);
        uint32_t x[4];
#pragma unroll
        for (int j = 0; j < 4; j++) {
          x[j] = pack_bf16(ot[j >> 1][2 * (j & 1)] * i0, ot[j >> 1][2 * (j & 1) + 1] * i1);
          sts32v(sb + OM + rank * OMS + oa + (j >> 1) * 1024 + (j & 1) * 128, x[j]);
        }
        fence_proxy_async();
#pragma unroll
        for (int j = 0; j < 8; j++) {
          const int i = P_OS ? j >> 1 : j & 3;
          if (P_OS ? j & 1 : j >> 2) st_async32(r1 + OM + rank * OMS + oa + (i >> 1) * 1024 + (i & 1) * 128, x[i], r1 + B_OM);
          else st_async32(r2 + OM2 + rank * OM2S + oa + (i >> 1) * 1024 + (i & 1) * 128, x[i], r2 + B_OM);
        }
        e_arrive(sb + B_OM);
        if (P_G2 < 16 && P_G2L) nbar_arrive<NB_G2, 384>();
        PROFW(0, 4);
      }
#pragma unroll
      for (int i = 0; i < 10; i++) hold[i] = w ? sc[4 * (i >> 1) + (i & 1)] : sc[4 * (i >> 1) + 2 + (i & 1)];
    }
    if (more && s >= 0) {
      LANE_NOW;
      char* const pw = (char*)g_part + (uint32_t)((t0 * 16 + w * 4 + (lane >> 3)) * 4096 + h * 128 + ((lane ^ h) & 7) * 16);
      mbar_wait(sb + B_OM, sp, budget);
      if (w == 0) nbar_arrive<NB_G, 128>();
      PROFW(1, 5);
      if (!ATT) fence_proxy_async();
      float acc[3][8];
      auto store = [&](auto J) {
        constexpr int j = J;
        float* d = acc[j % 3];
        pin<8>(d);
        uint32_t x[4];
#pragma unroll
        for (int i = 0; i < 4; i++) { const uint32_t m = (h >> 3) == i; x[i] = (pack_bf16(d[2*i], d[2*i+1]) & ~m) | (m & ~sp); }
        stg_rlx128(pw + j * (48 * 4096), x[0], x[1], x[2], x[3]);
        if constexpr (ATT && j == JA) nbar_arrive<NB_TR, 160>();
        if constexpr (j == 2) PROFW(3, 26);
      };
      sfor<0, NT>([&](auto J) {
        constexpr int j = J;
        if constexpr (ATT && j == JA) { mbar_wait(sb + B_WA, sp, budget); PROFW(2, 0); }
        wg_fence();
        sfor<0, 8>([&](auto K) {
          constexpr int k = K;
          typedef Op<(ATT ? OM : OM2) + k * 256, 128, ATT ? OMS : OM2S, 0, 1> OB;
          if constexpr (j == 5 && k < 4) wg_rs16<k ? 1 : 2, OB>(acc[j % 3], wl + 4 * k, d0);
          else wg_ss16<k ? 1 : j < 3 ? 0 : 2, Op<(j == JA ? WA : j < 5 ? WO + (j - (j > JA)) * 16384 : WH - 8192) + k * 2048, 16, 1024, 1, 1>, OB>(acc[j % 3], d0, d0);
        });
        wg_commit();
        if constexpr (j == 0) { if (w == 3) e_expect_tx(sb + B_OM, ATT ? 2048 : 4096); }
        if constexpr (j == NT - 1 && !P_WOL) nbar_arrive<NB_WO, 384>();
        if constexpr (j > 0 && j != P_WB + 1) { wg_wait<1>(); store(IC<j - 1>{}); }
        if constexpr (j == P_WB || j == NT - 1) { wg_wait<0>(); store(IC<j>{}); }
        if constexpr (j == P_WB) {
          const uint32_t t = clock32();
          if (ATT) {
            if (w == 3 && lane < 14) sts128(sb + PM1 + lane * 16, (lane >> 1) == 3 ? 0x3F803F80u : 0);
            if (w == 3 || P_MB) fence_proxy_async();
            nbar_sync<NB_P, 128>();
          } else if (P_MB) fence_proxy_async();
          spin_until(t, TUN(8, 100));
        }
      });
      if (P_WOL) { spin_until(clock32(), TUN(9, 0)); nbar_arrive<NB_WO, 384>(); }
    } else if (more) nbar_arrive<NB_WO, 384>();
    PROFW(0, 6);
    asm volatile("" : "+r"(h), "+r"(rank), "+r"(w));
#pragma unroll 1
    for (int pass = 0; ATT && pass < 2; pass++)
    if (pass != rank) {
      LANE_NOW;
      const int lim = 8 * (g >> 1) + (g & 1) + 2 * w - 8 * c;
      uint32_t p[5];
#pragma unroll
      for (int i = 0; i < 8; i++) hold[2+i] = i <= lim ? hold[2+i] : -INFINITY;
      const float psum = softmax_row(hold, p);
#pragma unroll
      for (int i = 0; i < 5; i++) hold[i] = __uint_as_float(p[i]);
      hold[5] = psum;
    } else if (more) {
      LANE_NOW;
      const int blk = rank * 32 + h;
      char* const mw = (char*)g_mem + (uint32_t)(sp * 32768 + blk * 512 + w * 128 + lane * 4);
      uint32_t v0 = 0;
      if (s == -1 || (s == LAG - 1 && (w & 1))) {
        const unsigned short* q = (const unsigned short*)mem0 + c * 2 * DM + blk * 16 + (w >> 1) * 8 + g;
        v0 = q[0] | (uint32_t)q[DM] << 16;
        if (v0 == 0) v0 = 0x8000u;
      }
      keep(mw);
      if (s >= 0) {
        const uint32_t ca = sb + WA + lane * 128 + (((2 * w) ^ lane) & 7) * 16 + (lane >> 3) * 4;
        const uint32_t sa = sb + OM + (((g >> 1) & 1) * 2 + (g >> 2)) * 128 + (2 * c + (w >> 1)) * 16 + (w & 1) * 8 + (g & 1) * 2;
        const bool g4l = P_G4L == 1 || (P_G4L == 2 && single(s));
        for (bool first = true; ; first = false) {
          float r[4];
          mbar_wait(sb + B_PART, pph, budget);
          PROFW(0, 11);
          pph ^= 1;
          wg_fence();
          sfor<0, 8>([&](auto K) { constexpr int k = K; wg_ss8<k != 0, Op<WA + k * 2048, 16, 1024, 1, 1>, Op<PM1 + (6 - (k & 6)) * 16, 0, 128, 0, 0>>(r, d0, d0); });
          wg_commit();
          if (!g4l && first) nbar_arrive<NB_G4, 384>();
          const uint32_t x0 = lds32v(ca), x1 = lds32v(ca + 4096), x2 = lds32v(ca + 8192), x3 = lds32v(ca + 12288);
          bool bad = __any_sync(0xffffffffu, (sp ? x0 | x1 | x2 | x3 : ~(x0 & x1 & x2 & x3)) & 1) && budget > 0;
          wg_wait<0>();
          pin<4>(r);
          uint32_t y = pack_bf16(r[0], r[2]);
          y |= (y & 0xffffu) ? 0 : 0x8000u;
          y |= (y >> 16) ? 0 : 0x80000000u;
          if (bad) y = 0;
          sts16(sa, y); sts16(sa + 4, y >> 16);
          nbar_sync<NB_P, 128>();
          y = lds32v(sb + OM + w * 128 + lane * 4);
          const bool ok = !__any_sync(0xffffffffu, y == 0);
          if (ok) stg_rlx32(mw, v0 ? v0 : y);
          if (g4l && first) nbar_arrive<NB_G4, 384>();
          if (ok) break;
          nbar_sync<NB_P, 128>();
          budget--;
          if (w == 0) { e_expect_tx(sb + B_PART, 16384); e_bulk_g2s(sb + WA, (const char*)g_part + blk * 16384, 16384, sb + B_PART); }
          __syncwarp();
        }
        nbar_sync<NB_P, 128>();
        if (w < 2) e_arrive_cl(mapr(h, sb + B_BFREE, w));
      } else stg_rlx32(mw, v0);
      stg_rlx32(mw + (sp ? -32768 : 32768), 0);
      PROFW(1, 8);
    }
    if (ATT && s >= 0) {
      const int seg = s - (rank ? LAG : 0);
      const bool act = (unsigned)seg < NSEG;
      LANE_NOW;
      uint32_t a[12];
#pragma unroll
      for (int i = 0; i < 12; i++) a[i] = __float_as_uint(hold[i < 10 ? i >> 1 : 4]) + ((uint32_t)budget >> (31 - (i & 3)));
      float o[32], inv, psum = hold[5];
      char* const ob = (char*)g_o[rank] + ((size_t)(seg * 32 + 8 * (g >> 1) + (g & 1) + 2 * w) * (NH * DH) + h * DH + c * 8) * 2;
      sfor<0, 2>([&](auto HF) {
        constexpr int hf = HF;
        wg_fence();
        wg_rs64<hf * 2, Op<QB + 8 * RG + hf * 1024, 2 * RG, 128, 0, 0>>(o, a, d0);
        wg_rs64<1, Op<QB + 12 * RG + hf * 1024, RG, 128, 0, 0>>(o, a + 4, d0);
        wg_rs64<1, Op<QB + 14 * RG + hf * 1024, 0, 128, 0, 0>>(o, a + 8, d0);
        wg_commit();
        if constexpr (hf == 0) {
          psum += __shfl_xor_sync(0xffffffffu, psum, 1);
          psum += __shfl_xor_sync(0xffffffffu, psum, 2);
          asm("rcp.approx.ftz.f32 %0, %1;" : "=f"(inv) : "f"(psum));
        }
        wg_wait<0>();
        pin<32>(o);
        if constexpr (hf == 1) { if (w == 2 && more) e_arrive_cl(mapr(h, sb + B_BFREE, 2)); }
        if (act) {
#pragma unroll
          for (int i = 0; i < 2; i++)
            stg128(ob + (hf * 2 + i) * 64, pack_bf16(o[16*i] * inv, o[16*i+1] * inv), pack_bf16(o[16*i+4] * inv, o[16*i+5] * inv),
                   pack_bf16(o[16*i+8] * inv, o[16*i+9] * inv), pack_bf16(o[16*i+12] * inv, o[16*i+13] * inv));
        }
      });
      PROFW(0, 7);
      if (act && (seg & 3) == 3) {
        nbar_sync<NB_P, 128>();
        if (w == 0) e_flag_add(g_fl.dep + grp(0, rank, seg >> 2), 4);
      }
    } else if (!ATT && w == 3) {
      if (s + 4 < NSEG) e_prefetch(g_xn[0] + (size_t)((s + 4) * 32 + h) * DM, 2048);
    }
  }
  cluster_arrive(); cluster_wait();
  char* const pw = (char*)g_part + (size_t)((ATT ? rank + 1 : 0) * 16 + w * 4 + (lane0 >> 3)) * 4096 + h * 128 + (lane0 & 7) * 16;
#pragma unroll
  for (int j = 0; j < NT; j++) stg_rlx128(pw + j * (48 * 4096), 0, 0, 0, 0);
}

DEVI void rec_load(const uint32_t sb, const int h, const int rank, const int w, const CUtensorMap* mX, const CUtensorMap* mWo) {
  using namespace rec;
  static_assert(((NSTEP - 1) & 31) != 1 && ((NSTEP - 2) & 31) != 2, "stale time stamps of the previous launch never match");
  const int lane0 = lane_reg(), mq = (w + 3) & 3;
  int budget = SPIN_BUDGET;
  if (w == 0) { e_flag_add(g_fl.xn[0][0]); flag_wait(g_fl.xn[0][0], 96, budget); }
  bool late = false;
  cluster_arrive(); cluster_wait();
  if (w == 0) { if (lane0 < 4) mbar_arrive(sb + B_FULL + 8 * lane0); __syncwarp(); }
  uint32_t lph = 0;
#pragma unroll 1
  for (int s = -1; s < NSTEP - 1; s++) {
    if (w == 0) {
      if (late) flag_wait(g_fl.xn[1][(s + 1 - LAG) >> 2], 128, budget);
      if (single(s)) {
#pragma unroll 1
        for (int i = 0; i < 8; i++) {
          const int k = i < 5 ? (0x21430 >> (4 * i)) & 15 : i;
          const int sl = (SLOT1 >> (4 * k)) & 15;
          mbar_wait(sb + B_EMPTY + 8 * sl, (((USE1 >> (4 * k)) ^ (sl >> 1 == 1 ? s + 1 : 0)) & 1) ^ 1, budget);
          e_expect_tx(sb + B_FULL + 8 * sl, 8192);
          e_tma_3d(sb + RING + sl * 8192, mX + 1, 0, (s + 1 + (s < LAG ? 0 : NSTEP)) * 32, k * 2, sb + B_FULL + 8 * sl);
        }
      } else {
        int sl = 4, ph = 1;
#pragma unroll 1
        for (int i = 0; i < 16; i++) {
          mbar_wait(sb + B_EMPTY + 8 * sl, ph, budget);
          e_expect_tx(sb + B_FULL + 8 * sl, 8192);
          e_tma_3d(sb + RING + sl * 8192, mX, i * 64, (s + 1) * 32, 0, sb + B_FULL + 8 * sl);
          if (++sl == 5) { sl = 0; ph ^= 1; }
        }
      }
      nbar_arrive<NB_X, 128>();
      const int sn = s + 2 - LAG;
      late = (sn & 3) == 0 && (unsigned)sn < NSEG && ld_acquire(g_fl.xn[1][sn >> 2]) < 128;
      asm volatile("fence.proxy.async.global;" ::: "memory");
    }
    uint32_t t = gtime();
    if (s >= 0) {
      uint2 a;
      if (w == 2 && rank < 2) {
        nbar_sync<NB_S, 64>();
        e_expect_tx(sb + B_WA, 16384);
        e_tma_2d(sb + WA, mWo, (3 * JA + 1 + rank) * 64, h * DH, sb + B_WA);
        e_tma_2d(sb + WA + 8192, mWo, (3 * JA + 1 + rank) * 64, h * DH + 64, sb + B_WA);
        e_arrive_cl(mapr(h, sb + B_SDONE, rank ^ 1));
        stg_rlx32(&g_ann[s & 1][lane0][h * 2 + rank], (gtime() & ~31u) | ((s + 1) & 31));
        e_expect_tx(sb + B_QK, 10240);
        e_expect_tx(sb + B_V, 10240);
      }
      if (w) nbar_sync<NB_G, 128>();
      do { a = ldg_rlx64(&g_ann[s & 1][h][lane0 * 2]); } while (__any_sync(0xffffffffu, ((a.x ^ (s + 1)) | (a.y ^ (s + 1))) & 31) && --budget > 0);
      t += __reduce_max_sync(0xffffffffu, max((int)(a.x - t), (int)(a.y - t)));
      t &= ~31u;
      PROFW(1, 12);
      if (w == 1 && rank < 2) {
        nbar_sync<NB_TR, 160>();
        wait_time(t + (single(s) ? (rank ? TUN(11, 1650) : TUN(10, 1250)) : rank ? TUN(1, 1750) : TUN(0, 1350)), budget);
        e_expect_tx(sb + B_PART, 16384);
        e_bulk_g2s(sb + WA, (const char*)g_part + (rank * 32 + h) * 16384, 16384, sb + B_PART);
        PROFW(1, 21);
      }
      t += single(s) ? (mq == 0 ? TUN(12, 2200) : mq == 1 ? TUN(13, 2300) : mq == 2 ? TUN(14, 2700) : TUN(15, 2800))
                     : (mq == 0 ? TUN(2, 2350) : mq == 1 ? TUN(3, 2450) : mq == 2 ? TUN(4, 2850) : TUN(5, 2950));
    }
    if (w) nbar_sync<NB_X, 128>();
    mbar_wait(sb + B_EMPTY + 8 * mq, mq >= 2 && single(s) ? (s + 1) & 1 : 1, budget);
    PROFW(1, 9);
    wait_time(t, budget);
    PROFW(1, 22); PROFW(3, 23);
    while (true) {
      e_expect_tx(sb + B_MLAND + 8 * mq, 8192);
      e_bulk_g2s(sb + RING + mq * 8192, (const char*)g_mem + (s & 1) * 32768 + mq * 8192, 8192, sb + B_MLAND + 8 * mq);
      const uint32_t a = sb + RING + mq * 8192 + lane0 * 32 + (lane0 >> 2) * 4;
      mbar_wait(sb + B_MLAND + 8 * mq, lph, budget);
      lph ^= 1;
      PROFW(1, 24);
      uint32_t mn = 0xffffffffu;
#pragma unroll
      for (int i = 0; i < 8; i++) mn = min(mn, lds32v(a + i * 1024));
      if (!__any_sync(0xffffffffu, mn == 0) || --budget <= 0) break;
    }
    e_arrive(sb + B_FULL + 8 * mq);
    PROFW(1, 10); PROFW(2, 13); PROFW(3, 14); PROFW(0, 15);
  }
}

DEVI void ln_row(const uint4* u, bf16* dst, int lane) {
  const uint32_t* x = (const uint32_t*)u;
  float mean = 0, q = 0;
#pragma unroll
  for (int i = 0; i < 16; i++) mean += bf_lo(x[i]) + bf_hi(x[i]);
  mean *= 1.f / 32;
#pragma unroll
  for (int i = 0; i < 16; i++) { const float a = bf_lo(x[i]) - mean, b = bf_hi(x[i]) - mean; q = fmaf(a, a, fmaf(b, b, q)); }
#pragma unroll
  for (int o = 1; o < 32; o *= 2) {
    const float m2 = __shfl_xor_sync(0xffffffffu, mean, o), q2 = __shfl_xor_sync(0xffffffffu, q, o), dl = m2 - mean;
    q = fmaf(dl * dl, 16.f * o, q + q2);
    mean = 0.5f * (mean + m2);
  }
  const float rs = rsqrtf(q * (1.f / DM) + 1e-5f), mr = -mean * rs;
#pragma unroll
  for (int i = 0; i < 4; i++) {
    uint32_t y[4];
#pragma unroll
    for (int k = 0; k < 4; k++) y[k] = pack_bf16(fmaf(bf_lo(x[4*i+k]), rs, mr), fmaf(bf_hi(x[4*i+k]), rs, mr));
    stg128((uint4*)dst + i * 32 + lane, y[0], y[1], y[2], y[3]);
  }
}

struct RecMaps { CUtensorMap w[3], wo, x[2]; };
__global__ void __cluster_dims__(R_CL, 1, 1) __launch_bounds__(512, 1)
rec_kernel(const __grid_constant__ RecMaps M, const bf16* __restrict__ Wo, const bf16* __restrict__ mem0, const bf16* __restrict__ x, uint32_t zero) {
  using namespace rec;
  extern __shared__ __align__(1024) uint8_t smem[];
  const uint32_t sb = smem_u32(smem);
  const int tid = threadIdx.x, warp = __shfl_sync(0xffffffffu, tid >> 5, 0), wg = warp >> 2, lane = tid & 31;
  const int h = blockIdx.x / 3, rank = blockIdx.x % 3;
  if (warp == 0) {
    if (lane < 20) mbar_init(sb + BARS + 8 * lane, (lane >= 5 && lane < 10) || lane == 19 ? 2 : lane == 14 ? 9 : lane == 16 && rank < 2 ? 5 : 1);
    else if (lane < 23) mbar_init(sb + B_W1 + 8 * (lane - 20), 1);
    else if (lane == 23) mbar_init(sb + B_PART, 1);
    fence_mbar_init();
    __syncwarp();
    if (lane == 0) { mbar_expect_tx(sb + B_W1, (NSS + R1) * 4096); mbar_expect_tx(sb + B_QK, 10240); mbar_expect_tx(sb + B_V, 10240); mbar_expect_tx(sb + B_OM, rank < 2 ? 2048 : 4096); }
    __syncwarp();
    for (int i = lane; i < 128; i += 32) {
      const int j = i >> 1, t = i & 1, r = reg_idx(j);
      if (is_ss(j)) tma_load_2d(sb + WS + (t * NSS + ss_before(j)) * 2048, &M.w[rank], h * DH + t * 64, j * 16, sb + B_W1);
      else if (r < R1) tma_load_2d(sb + WO + (t * R1 + r) * 2048, &M.w[rank], h * DH + t * 64, j * 16, sb + B_W1);
      else tma_prefetch_2d(&M.w[rank], h * DH + t * 64, j * 16);
    }
  } else if (warp == 1) {
    constexpr int N = (sizeof(Flags) - sizeof(g_fl.xn)) / 16;
    if (lane < 8 && blockIdx.x * 8 + lane < N) ((uint4*)g_fl.dep)[blockIdx.x * 8 + lane] = make_uint4(0, 0, 0, 0);
    static_assert(N <= 96 * 8, "flag reset");
    if (blockIdx.x < 32) ((uint4*)g_stat[2])[blockIdx.x * 32 + lane] = make_uint4(0, 0, 0, 0);
    __threadfence();
    __syncwarp();
    asm volatile("griddepcontrol.launch_dependents;" ::: "memory");
  } else if (warp >= 5 && blockIdx.x * 11 + warp - 5 < SEQ / 2) {
    const size_t o = (size_t)(blockIdx.x * 11 + warp - 5) * (2 * DM);
    uint4 u[8];
#pragma unroll
    for (int i = 0; i < 8; i++) u[i] = __ldg((const uint4*)(x + o) + i * 32 + lane);
    ln_row(u, g_xn[0] + o, lane);
    ln_row(u + 4, g_xn[0] + o + DM, lane);
  }
  __syncthreads();
  if (wg == 3) {
    reg_dec<24>();
    rec_load(sb, h, rank, warp & 3, M.x, &M.wo);
    cluster_arrive(); cluster_wait();
  } else if (wg == 2) {
    reg_dec<72>();
    if (rank < 2) rec_attn<true>(sb, h, rank, warp & 3, Wo, mem0);
    else rec_attn<false>(sb, h, rank, warp & 3, Wo, mem0);
  } else {
    reg_inc<208>();
    rec_proj(sb, h, rank, warp, &M.w[rank], &M.wo, zero);
    cluster_arrive(); cluster_wait();
  }
}

namespace gm {
constexpr int STAGES = 6, STAGE_BYTES = 32768;
constexpr uint32_t SO = STAGES * STAGE_BYTES, B_FULL = SO + 32768, B_TRIG = B_FULL + 56, B_EMPTY = B_FULL + 64, B_JOB = B_FULL + 128,
                   B_MSG = B_FULL + 144, B_XF = B_FULL + 160, B_SF = B_FULL + 176, JOB = B_FULL + 192, MSG = JOB + 8, SMEM = B_FULL + 256;
constexpr int T_O = 0, T_GU = 1, T_D = 2, T_END = 3;
#define G_LOOK 8
#define G_FILL 7
#define G_SLEEP 200
#define G_SLEEP2 500
#define G_SLEEP3 200
#define G_DF 0
#define G_FL 15
#define G_DS 14
DEVI bool is_split(int ty, int l, int cb) { return ty == T_O || (ty == T_D && (!l || cb >= G_DS)); }
struct Pipe { int s, ph; DEVI void next() { if (++s == STAGES) { s = 0; ph ^= 1; } } };
}
struct GemmMaps { CUtensorMap o, wo, x, x1, x1s, xm, xms, xn, wg, wu, h, hs, wd, x2, out, outs; };

DEVI float geglu(float g, float u) {
  const float z = g * (0.7978845608028654f + 0.035677408136300125f * g * g);
  float t; asm("tanh.approx.f32 %0, %1;" : "=f"(t) : "f"(z));
  const float hg = 0.5f * g;
  return fmaf(hg, t, hg) * u;
}
DEVI int h_ready(int v) { const int t = v ^ 0x101414; return t ? ((__ffs(t) - 1) >> 3) * 20 : 56; }
DEVI int a_ready(int ty, int l, int cb) {
  const int v = ld_acquire(g_fl.dep + grp(ty, l, cb));
  asm volatile("fence.proxy.async.global;" ::: "memory");
  return ty == gm::T_D ? h_ready(v) : v >= 128 ? 64 : 0;
}

__global__ void __cluster_dims__(2, 1, 1) __launch_bounds__(512, 1) gemm_kernel(const __grid_constant__ GemmMaps M) {
  using namespace gm;
  extern __shared__ __align__(1024) uint8_t smem[];
  const uint32_t sb = smem_u32(smem);
  const int tid = threadIdx.x, wid = __shfl_sync(0xffffffffu, tid >> 5, 0), wg = wid >> 2, warp = wid & 3;
  int budget = SPIN_BUDGET;
  const int rank = blockIdx.x & 1;
  const uint32_t peer = mapa(sb, rank ^ 1);
  if (tid < 24) mbar_init(sb + B_FULL + 8 * tid, tid >> 3 == 1 ? 2 : 1);
  fence_mbar_init();
  if (wid == 1 && rank == 0) sts32v(sb + JOB + 16, bcast(e_ticket(g_fl.ticket)));
  cluster_arrive(); cluster_wait();
  int pair;
  asm volatile("ld.shared::cluster.u32 %0, [%1];" : "=r"(pair) : "r"(mapa(sb + JOB + 16, 0)) : "memory");
  pair = __shfl_sync(0xffffffffu, pair, 0);
  const int cta = pair * 2 + rank, lane = lane_reg();
  if (wg >= 2) {
    reg_dec<72>();
    if (wid == 8 || wid == 10) {
      Pipe p; p.s = 0; p.ph = 1;
      for (int n = 0; ; n++) {
        if (wid == 8) e_expect_tx(sb + B_MSG + 8 * (n & 1), 4);
        mbar_wait(sb + B_MSG + 8 * (n & 1), (n >> 1) & 1, budget);
        const int msg = __shfl_sync(0xffffffffu, lds32v(sb + MSG + 4 * (n & 1)), 0);
        const int ty = (msg >> 11) & 3, l = (msg >> 10) & 1;
        const bool shb = ty == T_GU && l, spl = is_split(ty, l, (msg >> 6) & 15);
        const int cb = ((msg >> 6) & 15) + (shb ? rank : 0), j = (msg & 63) + (ty == T_END || shb ? 0 : rank);
        const int ke = ty == T_O ? 64 : ty == T_GU ? 16 : 56, k0 = spl ? rank : 0, dk = spl ? 2 : 1;
        const int c0 = ty == T_GU ? j * 64 : spl ? (j >> 1) * 128 : j * 128, c1 = ty == T_GU ? c0 : c0 + 64;
        mbar_wait(sb + B_EMPTY + 8 * p.s, p.ph, budget);
        trap_if_spent(budget);
        auto stages = [&](auto f) {
#pragma unroll 1
          for (int k = k0; k < ke; k += dk) {
            mbar_wait(sb + B_EMPTY + 8 * p.s, p.ph, budget);
            f(k, sb + p.s * STAGE_BYTES, sb + B_FULL + 8 * p.s);
            p.next();
          }
        };
        if (wid == 8) {
          const int job = ty << 11 | l << 10 | cb << 6 | j;
          sts32v(sb + JOB + 4 * (n & 1), job | p.s << 16 | (p.ph ^ 1) << 20);
          e_arrive(sb + B_JOB + 8 * (n & 1));
          if (ty == T_END) break;
          if (ty != T_GU) { e_expect_tx(sb + B_FULL + 8 * p.s, spl ? 16384 : STAGE_BYTES); p.next(); }
          const CUtensorMap* const m0 = ty == T_D ? &M.wd : shb && rank ? &M.wu : &M.wg, * const m1 = ty == T_D ? &M.wd : &M.wu;
          if (ty == T_O) stages([&](int k, uint32_t a, uint32_t fb) { e_expect_tx(fb, STAGE_BYTES); e_tma_5d(a + 16384, &M.wo, c0, k * 2, fb); e_tma_5d(a + 24576, &M.wo, c1, k * 2, fb); });
          else if (shb) stages([&](int k, uint32_t a, uint32_t fb) { e_expect_tx(fb, STAGE_BYTES); e_tma_2d_mc(a + 16384 + rank * 8192, m0, c0, k * 64, fb); });
          else stages([&](int k, uint32_t a, uint32_t fb) { e_expect_tx(fb, STAGE_BYTES); e_tma_2d(a + 16384, m0, c0, k * 64, fb); e_tma_2d(a + 24576, m1, c1, k * 64, fb); });
        } else {
          if (ty == T_END) break;
          const int row = l * SEQ + cb * 128, kt = ke + k0 - G_LOOK * dk;
          int rdy = msg >> 16;
          auto need = [&](int k) {
            if (k == kt) e_arrive(sb + B_TRIG);
            while (k >= rdy && k >= (rdy = a_ready(ty, l, cb))) { __nanosleep(G_SLEEP); trap_if_spent(--budget); }
          };
          if (ty != T_GU) {
            need(0);
            const uint32_t a = sb + p.s * STAGE_BYTES, fb = sb + B_FULL + 8 * p.s;
            const CUtensorMap* const m = ty == T_D ? (spl ? &M.x1 : &M.x1s) : l ? &M.x2 : &M.x;
            const int r = (ty == T_D ? row : cb * 128) + (spl ? rank * 64 : 0);
            e_tma_2d(a, m, c0, r, fb); e_tma_2d(a + 16384, m, c1, r, fb);
            p.next();
          }
          if (shb || spl) {
            const CUtensorMap* const ma = ty == T_O ? &M.o : ty == T_GU ? &M.xms : &M.hs;
            stages([&](int k, uint32_t a, uint32_t fb) { need(k); e_tma_2d(a, ma, k * 64, row, fb); });
          } else {
            const CUtensorMap* const ma = ty == T_GU ? &M.xm : &M.h;
            stages([&](int k, uint32_t a, uint32_t fb) { need(k); e_tma_2d_mc(a + rank * 8192, ma, k * 64, row + rank * 64, fb); });
          }
        }
      }
    } else if (wid == 9 && rank == 0) {
      int k1 = pair < 18 ? 0 : 68;
      bool late = false;
      for (int n = 0, ty = 0; ty != T_END; n++) {
        mbar_wait(sb + B_TRIG, (n & 1) ^ 1, budget);
        int l, cb, j, rdy = 64;
        while (true) {
          const int ph = k1 & 3;
          const bool gap = ph == 3;
          if (k1 < 68) {
            cb = (k1++ >> 2) - (pair < 8 ? ph : 0);
            if ((unsigned)cb >= 16 || (ph == 2 && pair >> 3 != 1) || (gap && (pair < 8 || late || !(G_FILL & (pair >> 3))))) continue;
            if (!gap) {
              l = 0;
              ty = pair < 8 ? (ph ? T_D : T_O) : T_GU;
              j = 2 * (pair < 8 ? pair : pair - 8 + 10 * ph);
              rdy = a_ready(ty, 0, cb);
              if (ph == 0) late = rdy != 0;
              break;
            }
          }
          int d0 = ld_relaxed(g_fl.dep + lane), d1 = ld_relaxed(g_fl.dep + 32 + lane);
          const int t0 = ld_relaxed(g_fl.taken + lane), t1 = ld_relaxed(g_fl.taken + 32 + lane);
          const bool l0 = t0 < (lane < 16 ? 8 : lane & 1 ? 0 : 56), l1 = lane < 16 && t1 < (lane < G_DS ? 4 : 8);
          const uint32_t rd = __ballot_sync(0xffffffffu, d0 >= 128);
          uint32_t ok0 = __ballot_sync(0xffffffffu, l0) & rd & (rd >> 1 | 0xffff), ok1 = __ballot_sync(0xffffffffu, l1 && h_ready(d1) > 0);
          if (gap) { ok1 = 0; if (pair < 16) ok0 &= G_FILL & 8 ? ((k1 >> 2 ^ pair) & 1 ? ~0u : 0u) : G_FILL & 4 ? 0xffff0003u : 0xffff0000u; }
          ty = T_END; l = 1; cb = j = 0;
          if (!gap && !__any_sync(0xffffffffu, l0 || l1)) break;
          if (ok1 & ((1u << G_DS) - 1)) ok1 &= (1u << G_DS) - 1;
          const uint32_t dfirst = ok1 & __ballot_sync(0xffffffffu, lane < G_DF && d1 == 0x101414);
          if (dfirst && !(ok0 & 0xffff)) { ok0 = 0; ok1 = dfirst; }
          uint32_t m = ok0 ? ok0 : ok1;
          if (!m && !gap) __nanosleep(100);
          while (m) {
            const int nth = ok0 ? 0 : pair % __popc(m);
            const int b = __ffs(__ballot_sync(0xffffffffu, __popc(m << (31 - lane)) > nth)) - 1, gn = b + (ok0 ? 0 : 32);
            const int t = bcast(e_ticket(g_fl.taken + gn));
            if (t < (gn < 16 ? 8 : gn < 32 ? 56 : gn < 32 + G_DS ? 4 : 8)) { ty = gn >> 4; cb = gn & 15; j = ty == T_GU ? t : 2 * t; break; }
            m &= ~(1u << b);
          }
          if (ty != T_END) {
            rdy = a_ready(ty, 1, cb);
            if (ty == T_GU) a_ready(ty, 1, cb + 1);
            break;
          }
          trap_if_spent(--budget);
        }
        const int msg = rdy << 16 | ty << 11 | l << 10 | cb << 6 | j;
        e_st_async32(peer + MSG + 4 * (n & 1), msg, peer + B_MSG + 8 * (n & 1));
        e_st_async32(sb + MSG + 4 * (n & 1), msg, sb + B_MSG + 8 * (n & 1));
      }
    } else if (wg == 3) {
      bool open = lane < G_FL && ld_relaxed(g_fl.rows + lane) < 128;
      while (__any_sync(0xffffffffu, open)) {
        int v = 0;
        if (open) asm volatile("ld.acquire.gpu.global.s32 %0, [%1];" : "=r"(v) : "l"(g_fl.part + lane) : "memory");
        const uint32_t ok = __ballot_sync(0xffffffffu, open && v >= 128);
        if (!ok) {
          if (--budget <= 0) break;
          __nanosleep(G_SLEEP2);
          continue;
        }
        const int cb = __ffs(__ballot_sync(0xffffffffu, __popc(ok << (31 - lane)) > (cta >> 5) % __popc(ok))) - 1;
        const int r = bcast(e_ticket(g_fl.rows + cb));
        if (r >= 128) { open = open && lane != cb; continue; }
        uint4 u[4];
#pragma unroll
        for (int i = 0; i < 4; i++) u[i] = ldg_rlx128((const uint4*)(g_x1[1] + (size_t)(cb * 128 + r) * DM) + i * 32 + lane);
        ln_row(u, g_xm[1] + (size_t)(cb * 128 + r) * DM, lane);
        __syncwarp();
        e_flag_add(g_fl.dep + grp(T_GU, 1, cb));
      }
      if (cta == 0 && wid == 12) {
        asm volatile("griddepcontrol.wait;" ::: "memory");
        g_fl.xn[lane >> 4][lane & 15][0] = 0;
      }
    }
    cluster_arrive(); cluster_wait();
  } else {
    reg_inc<184>();
    const bool lead = warp == 0;
    const uint32_t eb = (warp == 1 ? peer : sb) + B_EMPTY;
    const int rl = warp < 2 ? 0 : -1;
    const uint32_t so = sb + SO + wg * 16384;
    const int r0 = warp * 16 + (lane & 7) + ((lane >> 3) & 1) * 8;
    const uint32_t sw = r0 * 128 + (((lane >> 4) ^ (r0 & 7)) << 4);
    int xph = 0;
    for (int n = wg; ; n += 2) {
      float d0[64], d1[64];
      mbar_wait(sb + B_JOB + 8 * wg, (n >> 1) & 1, budget);
      fault_if_spent(budget);
      const int job = __shfl_sync(0xffffffffu, lds32v(sb + JOB + 4 * wg), 0);
      const int ty = (job >> 11) & 3, l = (job >> 10) & 1, cb = (job >> 6) & 15, j = job & 63;
      if (ty == T_END) {
        if (n > 0) nbar_sync_r(1 + wg, 256);
        if (lead && !(job & 1)) { sts32v(sb + JOB + 4 * (wg ^ 1), job | 1); e_arrive(sb + B_JOB + 8 * (wg ^ 1)); }
        if (!(job & 1)) nbar_arrive_r(1 + (wg ^ 1), 256);
        break;
      }
      Pipe q; q.s = (job >> 16) & 15; q.ph = job >> 20;
      const bool spl = is_split(ty, l, cb);
      if (ty != T_GU) mbar_wait(sb + B_FULL + 8 * q.s, q.ph, budget);
#pragma unroll
      for (int m = 0; m < 2; m++) {
        float* d = m ? d1 : d0;
        if (ty != T_GU && !(m && spl)) {
#pragma unroll
          for (int c = 0; c < 8; c++) {
            uint32_t r[4];
            ldsm4(sb + q.s * STAGE_BYTES + (c >> 2) * 16384 + m * 8192 + (sw ^ ((c & 3) << 5)), r[0], r[1], r[2], r[3]);
#pragma unroll
            for (int i = 0; i < 4; i++) { d[8*c+2*i] = bf_lo(r[i]); d[8*c+2*i+1] = bf_hi(r[i]); }
          }
        } else {
#pragma unroll
          for (int i = 0; i < 64; i++) d[i] = 0.f;
        }
      }
      if (ty != T_GU) {
        fence_proxy_async();
        nbar_sync_r(3 + wg, 128);
        arrive_cl_if_eq(eb + 8 * q.s, lane, rl);
        q.next();
      }
      pin<64>(d0); pin<64>(d1);
      if (n > 0) nbar_sync_r(1 + wg, 256);
      const int nk = ty == T_O ? 32 : ty == T_GU ? 16 : spl ? 28 : 56;
      const uint32_t ro = spl ? rank * 512 : 0;
      int prev = 0;
      for (int i = 0; i < nk; i++) {
        mbar_wait(sb + B_FULL + 8 * q.s, q.ph, budget);
        const uint32_t da = desc_base(sb) + q.s * (STAGE_BYTES / 16);
        wg_fence();
        sfor<0, 4>([&](auto K) {
          constexpr int k = K;
          typedef Op<16384 + k * 2048, 8192, 1024, 1, 1> OB;
          wg_ss128<1, Op<k * 32, 16, 1024, 1, 0>, OB>(d0, da + ro, da);
          wg_ss128<1, Op<8192 + k * 32, 16, 1024, 1, 0>, OB>(d1, da - ro, da);
        });
        wg_commit();
        wg_wait<1>();
        arrive_cl_if_eq(eb + 8 * prev, lane, i ? rl : -1);
        prev = q.s;
        q.next();
      }
      nbar_arrive_r(1 + (wg ^ 1), 256);
      wg_wait<0>();
      pin<64>(d0); pin<64>(d1);
      arrive_cl_if_eq(eb + 8 * prev, lane, rl);
      if (spl) {
        const uint32_t xa = SO + wg * 16384 + warp * 512 + lane * 16;
        if (lead) e_expect_tx(sb + B_XF + 8 * wg, 16384);
        mbar_wait(sb + B_SF + 8 * wg, ((n >> 1) & 1) ^ 1, budget);
#pragma unroll
        for (int i = 0; i < 8; i++) {
          const float* d = d1 + 8 * i;
          st_async128(peer + xa + i * 2048, pack_bf16(d[0], d[1]), pack_bf16(d[2], d[3]), pack_bf16(d[4], d[5]), pack_bf16(d[6], d[7]), peer + B_XF + 8 * wg);
        }
        mbar_wait(sb + B_XF + 8 * wg, xph, budget);
        xph ^= 1;
        uint32_t y[32];
#pragma unroll
        for (int i = 0; i < 8; i++) {
          const float* d = d0 + 8 * i;
          const uint4 v = lds128(sb + xa + i * 2048);
          y[4*i] = pack_bf16(d[0] + bf_lo(v.x), d[1] + bf_hi(v.x)); y[4*i+1] = pack_bf16(d[2] + bf_lo(v.y), d[3] + bf_hi(v.y));
          y[4*i+2] = pack_bf16(d[4] + bf_lo(v.z), d[5] + bf_hi(v.z)); y[4*i+3] = pack_bf16(d[6] + bf_lo(v.w), d[7] + bf_hi(v.w));
        }
        const bool fuse = !l || (ty == T_O && cb >= G_FL);
        float2* const st = &g_stat[l ? 2 : ty >> 1][cb & 1][0][rank * 64 + warp * 16 + (lane >> 2) * 2];
        if (fuse) {
          float mn[2], sq[2];
#pragma unroll
          for (int z = 0; z < 2; z++) {
            float m = 0, s2 = 0;
#pragma unroll
            for (int i = 0; i < 16; i++) m += bf_lo(y[2*i+z]) + bf_hi(y[2*i+z]);
            m += __shfl_xor_sync(0xffffffffu, m, 1); m += __shfl_xor_sync(0xffffffffu, m, 2);
            m *= 1.f / 128;
#pragma unroll
            for (int i = 0; i < 16; i++) { const float a = bf_lo(y[2*i+z]) - m, b = bf_hi(y[2*i+z]) - m; s2 = fmaf(a, a, fmaf(b, b, s2)); }
            s2 += __shfl_xor_sync(0xffffffffu, s2, 1); s2 += __shfl_xor_sync(0xffffffffu, s2, 2);
            mn[z] = m; sq[z] = s2;
          }
          if ((lane & 3) == 0) stg_rlx128(st + (j >> 1) * 128, __float_as_uint(mn[0]), (__float_as_uint(sq[0]) & ~31u) | (cb + 1), __float_as_uint(mn[1]), __float_as_uint(sq[1]));
          __syncwarp();
        }
        auto put = [&](const CUtensorMap* mo, int row) {
          nbar_sync_r(3 + wg, 128);
#pragma unroll
          for (int c = 0; c < 8; c++) stsm4(so + (c >> 2) * 8192 + (sw ^ ((c & 3) << 5)), y[4*c], y[4*c+1], y[4*c+2], y[4*c+3]);
          fence_proxy_async();
          nbar_sync_r(3 + wg, 128);
          if (lead) { e_tma_store_2d(mo, so, (j >> 1) * 128, row); e_tma_store_2d(mo, so + 8192, (j >> 1) * 128 + 64, row); bulk_commit(); }
        };
        const int row = (ty == T_O ? l * SEQ : 0) + cb * 128 + rank * 64;
        put(ty == T_O ? &M.x1 : l ? &M.out : &M.x2, row);
        if (fuse) {
          uint4 u[2];
          while (true) {
            u[0] = ldg_rlx128(st + (lane & 3) * 256); u[1] = ldg_rlx128(st + (lane & 3) * 256 + 128);
            if (!__any_sync(0xffffffffu, ((u[0].y ^ (cb + 1)) | (u[1].y ^ (cb + 1))) & 31) || --budget <= 0) break;
            __nanosleep(G_SLEEP3);
          }
#pragma unroll
          for (int z = 0; z < 2; z++) {
            const float ma = __uint_as_float(z ? u[0].z : u[0].x), mb = __uint_as_float(z ? u[1].z : u[1].x);
            float m = ma + mb;
            m += __shfl_xor_sync(0xffffffffu, m, 1); m += __shfl_xor_sync(0xffffffffu, m, 2);
            m *= 0.125f;
            float s2 = __uint_as_float(z ? u[0].w : u[0].y & ~31u) + __uint_as_float(z ? u[1].w : u[1].y & ~31u) + 128.f * ((ma - m) * (ma - m) + (mb - m) * (mb - m));
            s2 += __shfl_xor_sync(0xffffffffu, s2, 1); s2 += __shfl_xor_sync(0xffffffffu, s2, 2);
            const float rs = rsqrtf(s2 * (1.f / DM) + 1e-5f), mr = -m * rs;
#pragma unroll
            for (int i = 0; i < 16; i++) y[2*i+z] = pack_bf16(fmaf(bf_lo(y[2*i+z]), rs, mr), fmaf(bf_hi(y[2*i+z]), rs, mr));
          }
          if (lead) bulk_wait_read<0>();
          put(ty == T_O ? &M.xm : &M.xn, row);
        }
      } else {
        if (ty == T_GU) {
#pragma unroll
          for (int i = 0; i < 32; i++) { d0[i] = geglu(d0[i], d0[32 + i]); d1[i] = geglu(d1[i], d1[32 + i]); }
        }
#pragma unroll
        for (int hf = 0; hf < 2; hf++) {
          if (hf) {
            if (ty == T_GU) break;
            if (lead) bulk_wait_read<0>();
            nbar_sync_r(3 + wg, 128);
          }
#pragma unroll
          for (int m = 0; m < 2; m++)
#pragma unroll
            for (int c = 0; c < 4; c++) {
              const float* d = (m ? d1 : d0) + 32 * hf + 8 * c;
              stsm4(so + m * 8192 + (sw ^ (c << 5)), pack_bf16(d[0], d[1]), pack_bf16(d[2], d[3]), pack_bf16(d[4], d[5]), pack_bf16(d[6], d[7]));
            }
          fence_proxy_async();
          nbar_sync_r(3 + wg, 128);
          if (lead) {
            if (ty == T_GU) e_tma_store_2d(&M.hs, so, j * 64, l * SEQ + cb * 128); else e_tma_store_2d(&M.outs, so, j * 128 + hf * 64, cb * 128);
            bulk_commit();
          }
        }
      }
      if (lead) {
        bulk_wait<0>();
        e_arrive_cl(peer + B_SF + 8 * wg);
        if (ty == T_GU) e_flag_add(g_fl.dep + grp(T_D, l, cb), 1 << (j / 20 * 8));
        else if (ty == T_O || !l) e_flag_add(ty == T_D ? g_fl.xn[1][cb] : l && cb < G_FL ? g_fl.part + cb : g_fl.dep + grp(T_GU, l, cb), 8);
      }
    }
    cluster_arrive(); cluster_wait();
  }
}

typedef CUresult (*PFN_encodeTiled)(CUtensorMap*, CUtensorMapDataType, cuuint32_t, void*, const cuuint64_t*, const cuuint64_t*,
                                    const cuuint32_t*, const cuuint32_t*, CUtensorMapInterleave, CUtensorMapSwizzle,
                                    CUtensorMapL2promotion, CUtensorMapFloatOOBfill);
static PFN_encodeTiled g_encode = nullptr;
static int g_sms = 0;
static CUtensorMap encode(const void* ptr, int rank, const cuuint64_t* dims, const cuuint64_t* strides, const cuuint32_t* box) {
  CUtensorMap m;
  const cuuint32_t es[5] = {1, 1, 1, 1, 1};
  g_encode(&m, CU_TENSOR_MAP_DATA_TYPE_BFLOAT16, rank, (void*)ptr, dims, strides, box, es, CU_TENSOR_MAP_INTERLEAVE_NONE,
           CU_TENSOR_MAP_SWIZZLE_128B, CU_TENSOR_MAP_L2_PROMOTION_L2_256B, CU_TENSOR_MAP_FLOAT_OOB_FILL_NONE);
  return m;
}
static CUtensorMap make_map(const void* ptr, uint64_t rows, uint64_t cols, uint32_t box_rows) {
  const cuuint64_t dims[2] = {cols, rows}, strides[1] = {cols * 2};
  const cuuint32_t box[2] = {64, box_rows};
  return encode(ptr, 2, dims, strides, box);
}
static CUtensorMap make_map_x(const void* ptr) {
  const cuuint64_t dims[3] = {DM, NSTEP * 32, 2}, strides[2] = {DM * 2, (cuuint64_t)NSTEP * 32 * DM * 2};
  const cuuint32_t box[3] = {64, 32, 2};
  return encode(ptr, 3, dims, strides, box);
}
static CUtensorMap make_map_x1(const void* ptr) {
  const cuuint64_t dims[3] = {64, 2 * NSTEP * 32, DM / 64}, strides[2] = {DM * 2, 128};
  const cuuint32_t box[3] = {64, 32, 2};
  return encode(ptr, 3, dims, strides, box);
}
static CUtensorMap make_map_wo(const void* ptr) {
  const cuuint64_t dims[5] = {DM, 2, 4, 4, NH * DH / 32}, strides[4] = {DM * 2, 8 * DM * 2, 2 * DM * 2, 32 * DM * 2};
  const cuuint32_t box[5] = {64, 2, 4, 4, 2};
  return encode(ptr, 5, dims, strides, box);
}

extern "C" void kernel_launch(void* const* d_in, const int* in_sizes, int n_in, void* d_out, int out_size) {
  const bf16 *x = (const bf16*)d_in[0], *mem0 = (const bf16*)d_in[1], *Wo = (const bf16*)d_in[5];
  if (!g_encode) {
    void* p = nullptr; cudaDriverEntryPointQueryResult q;
    cudaGetDriverEntryPoint("cuTensorMapEncodeTiled", &p, cudaEnableDefault, &q);
    g_encode = (PFN_encodeTiled)p;
    int dev = 0;
    cudaGetDevice(&dev);
    cudaDeviceGetAttribute(&g_sms, cudaDevAttrMultiProcessorCount, dev);
    cudaFuncSetAttribute(rec_kernel, cudaFuncAttributeMaxDynamicSharedMemorySize, rec::SMEM);
    cudaFuncSetAttribute(gemm_kernel, cudaFuncAttributeMaxDynamicSharedMemorySize, gm::SMEM);
  }
  void *xn, *o, *x1, *xm, *x2, *hh;
  cudaGetSymbolAddress(&xn, g_xn); cudaGetSymbolAddress(&o, g_o); cudaGetSymbolAddress(&x1, g_x1);
  cudaGetSymbolAddress(&xm, g_xm); cudaGetSymbolAddress(&x2, g_x2); cudaGetSymbolAddress(&hh, g_h);
  RecMaps R;
  for (int i = 0; i < 3; i++) R.w[i] = make_map(d_in[2 + i], DM, NH * DH, 16);
  R.wo = make_map(Wo, NH * DH, DM, 64); R.x[0] = make_map_x(xn); R.x[1] = make_map_x1(xn);
  rec_kernel<<<96, 512, rec::SMEM>>>(R, Wo, mem0, x, 0);
  GemmMaps G;
  G.o = make_map(o, 2 * SEQ, NH * DH, 128); G.wo = make_map_wo(Wo);
  G.x1 = make_map(x1, 2 * SEQ, DM, 64); G.x1s = make_map(x1, 2 * SEQ, DM, 128);
  G.xn = make_map((bf16*)xn + (NSTEP + LAG) * 32 * DM, SEQ, DM, 64);
  G.xm = make_map(xm, 2 * SEQ, DM, 64); G.xms = make_map(xm, 2 * SEQ, DM, 128);
  G.wg = make_map(d_in[8], DM, DF, 64); G.wu = make_map(d_in[9], DM, DF, 64); G.wd = make_map(d_in[10], DF, DM, 64);
  G.h = make_map(hh, 2 * SEQ, DF, 64); G.hs = make_map(hh, 2 * SEQ, DF, 128);
  G.x = make_map(x, SEQ, DM, 64); G.x2 = make_map(x2, SEQ, DM, 64); G.out = make_map(d_out, SEQ, DM, 64); G.outs = make_map(d_out, SEQ, DM, 128);
  cudaLaunchConfig_t cfg = {};
  cfg.gridDim = dim3(g_sms & ~1); cfg.blockDim = dim3(512); cfg.dynamicSmemBytes = gm::SMEM; cfg.stream = cudaStreamPerThread;
  cudaLaunchAttribute at;
  at.id = cudaLaunchAttributeProgrammaticStreamSerialization; at.val.programmaticStreamSerializationAllowed = 1;
  cfg.attrs = &at; cfg.numAttrs = 1;
  cudaLaunchKernelEx(&cfg, gemm_kernel, G);
}
```

```cpp
#include <cuda_runtime.h>
#include <cuda_bf16.h>
#include <cuda.h>
#include <stdint.h>

#define DEVI __device__ __forceinline__
typedef __nv_bfloat16 bf16;

#define LAG 14
constexpr int SEQ = 2048, DM = 1024, NH = 32, DH = 128, DF = 3584, NSEG = 64, NSTEP = NSEG + LAG;
static_assert(NSTEP % 2 == 0, "tags and slots of the exchange buffers return to their initial state");

__device__ __align__(1024) bf16 g_xn[2][NSTEP * 32 * DM];
__device__ __align__(1024) bf16 g_o[2][SEQ * NH * DH];
__device__ __align__(1024) bf16 g_x1[2][SEQ * DM];
__device__ __align__(1024) bf16 g_xm[2][SEQ * DM];
__device__ __align__(1024) bf16 g_x2[SEQ * DM];
__device__ __align__(1024) bf16 g_h[2][SEQ * DF];
__device__ __align__(1024) uint4 g_part[256 * 32 * 8];
__device__ __align__(1024) uint32_t g_ann[2][32][64];
__device__ __align__(1024) uint4 g_mem[2][2048];
__device__ __align__(128) float2 g_stat[12][8][128];
__host__ __device__ constexpr int grp(int type, int layer, int blk) { return layer ? 16 * type + blk : 64 + (16 * type + blk) * 32; }
struct Flags {
  int xn[2][16][32];
  int dep[64 + 48 * 32];
  int taken[64];
  int rows[32];
  int part[32];
  int ticket[32];
};
__device__ __align__(128) Flags g_fl;

DEVI uint32_t smem_u32(const void* p) { return (uint32_t)__cvta_generic_to_shared(p); }
DEVI void mbar_init(uint32_t bar, uint32_t cnt) { asm volatile("mbarrier.init.shared::cta.b64 [%0], %1;" :: "r"(bar), "r"(cnt) : "memory"); }
DEVI void mbar_expect_tx(uint32_t bar, uint32_t bytes) { asm volatile("mbarrier.arrive.expect_tx.shared::cta.b64 _, [%0], %1;" :: "r"(bar), "r"(bytes) : "memory"); }
DEVI void mbar_arrive(uint32_t bar) { asm volatile("mbarrier.arrive.shared::cta.b64 _, [%0];" :: "r"(bar) : "memory"); }
DEVI bool mbar_try(uint32_t bar, uint32_t parity) {
  uint32_t p;
  asm volatile("{.reg .pred p; mbarrier.try_wait.parity.shared::cta.b64 p, [%1], %2; selp.u32 %0, 1, 0, p;}" : "=r"(p) : "r"(bar), "r"(parity) : "memory");
  return p;
}
DEVI bool mbar_test(uint32_t bar, uint32_t parity) {
  uint32_t p;
  asm volatile("{.reg .pred p; mbarrier.test_wait.parity.shared::cta.b64 p, [%1], %2; selp.u32 %0, 1, 0, p;}" : "=r"(p) : "r"(bar), "r"(parity) : "memory");
  return p;
}
constexpr int SPIN_BUDGET = 1 << 20;
DEVI void mbar_wait(uint32_t bar, uint32_t parity, int& budget) {
  while (!mbar_try(bar, parity)) { if (--budget < 0) break; }
}
DEVI void trap_if_spent(int budget) { asm volatile("{.reg .pred p; setp.le.s32 p, %0, 0; @p trap;}" :: "r"(budget) : "memory"); }
DEVI void fault_if_spent(int budget) { asm volatile("{.reg .pred p; setp.le.s32 p, %0, 0; @p st.global.u32 [%1], 0;}" :: "r"(budget), "l"(0ull) : "memory"); }
DEVI uint32_t mapa(uint32_t addr, uint32_t rank) { uint32_t r; asm("mapa.shared::cluster.u32 %0, %1, %2;" : "=r"(r) : "r"(addr), "r"(rank)); return r; }
DEVI void cluster_arrive() { asm volatile("barrier.cluster.arrive.release.aligned;" ::: "memory"); }
DEVI void cluster_wait() { asm volatile("barrier.cluster.wait.acquire.aligned;" ::: "memory"); }
DEVI void fence_mbar_init() { asm volatile("fence.mbarrier_init.release.cluster;" ::: "memory"); }
DEVI void fence_proxy_async() { asm volatile("fence.proxy.async.shared::cta;" ::: "memory"); }
DEVI void tma_load_2d(uint32_t dst, const CUtensorMap* m, int c0, int c1, uint32_t bar) {
  asm volatile("cp.async.bulk.tensor.2d.shared::cluster.global.mbarrier::complete_tx::bytes [%0], [%1, {%3, %4}], [%2];"
    :: "r"(dst), "l"(m), "r"(bar), "r"(c0), "r"(c1) : "memory");
}
DEVI void tma_load_5d(uint32_t dst, const CUtensorMap* m, int c0, int c4, uint32_t bar) {
  asm volatile("cp.async.bulk.tensor.5d.shared::cluster.global.mbarrier::complete_tx::bytes [%0], [%1, {%3, %5, %5, %5, %4}], [%2];"
    :: "r"(dst), "l"(m), "r"(bar), "r"(c0), "r"(c4), "r"(0) : "memory");
}
DEVI void tma_prefetch_2d(const CUtensorMap* m, int c0, int c1) {
  asm volatile("cp.async.bulk.prefetch.tensor.2d.L2.global [%0, {%1, %2}];" :: "l"(m), "r"(c0), "r"(c1) : "memory");
}
DEVI void tma_prefetch_5d(const CUtensorMap* m, int c0, int c4) {
  asm volatile("cp.async.bulk.prefetch.tensor.5d.L2.global [%0, {%1, %3, %3, %3, %2}];" :: "l"(m), "r"(c0), "r"(c4), "r"(0) : "memory");
}
#define ELECT "{.reg .pred p; elect.sync _|p, 0xffffffff;\n @p "
DEVI void e_expect_tx(uint32_t bar, uint32_t bytes) { asm volatile(ELECT "mbarrier.arrive.expect_tx.shared::cta.b64 _, [%0], %1;}" :: "r"(bar), "r"(bytes) : "memory"); }
DEVI void e_arrive(uint32_t bar) { asm volatile(ELECT "mbarrier.arrive.shared::cta.b64 _, [%0];}" :: "r"(bar) : "memory"); }
DEVI void e_arrive_cl(uint32_t bar) { asm volatile(ELECT "mbarrier.arrive.shared::cluster.b64 _, [%0];}" :: "r"(bar) : "memory"); }
DEVI void e_tma_2d(uint32_t dst, const CUtensorMap* m, int c0, int c1, uint32_t bar) {
  asm volatile(ELECT "cp.async.bulk.tensor.2d.shared::cluster.global.mbarrier::complete_tx::bytes [%0], [%1, {%3, %4}], [%2];}"
    :: "r"(dst), "l"(m), "r"(bar), "r"(c0), "r"(c1) : "memory");
}
DEVI void e_tma_2d_mc(uint32_t dst, const CUtensorMap* m, int c0, int c1, uint32_t bar) {
  asm volatile(ELECT "cp.async.bulk.tensor.2d.shared::cluster.global.mbarrier::complete_tx::bytes.multicast::cluster [%0], [%1, {%3, %4}], [%2], %5;}"
    :: "r"(dst), "l"(m), "r"(bar), "r"(c0), "r"(c1), "h"((unsigned short)3) : "memory");
}
DEVI void e_st_async32(uint32_t a, uint32_t x, uint32_t bar) {
  asm volatile(ELECT "st.async.weak.shared::cluster.mbarrier::complete_tx::bytes.b32 [%0], %1, [%2];}" :: "r"(a), "r"(x), "r"(bar) : "memory");
}
DEVI void e_tma_store_2d(const CUtensorMap* m, uint32_t src, int c0, int c1) {
  asm volatile(ELECT "cp.async.bulk.tensor.2d.global.shared::cta.bulk_group [%0, {%2, %3}], [%1];}" :: "l"(m), "r"(src), "r"(c0), "r"(c1) : "memory");
}
DEVI void e_flag_add(int* p, int v = 1) {
  asm volatile("{.reg .pred p; elect.sync _|p, 0xffffffff;\n fence.proxy.async.global; @p red.release.gpu.global.add.s32 [%0], %1;}" :: "l"(p), "r"(v) : "memory");
}
DEVI void e_flag_add_bulk(int* p, int v) {
  asm volatile(ELECT "red.relaxed.gpu.global.add.s32 [%0], %1;}" :: "l"(p), "r"(v) : "memory");
}
DEVI int e_ticket(int* p) { int v = 0; asm volatile(ELECT "atom.relaxed.gpu.global.add.s32 %0, [%1], 1;}" : "+r"(v) : "l"(p) : "memory"); __syncwarp(); return v; }
DEVI int bcast(int v) { return __reduce_max_sync(0xffffffffu, v); }
DEVI int ld_relaxed(const int* p) { int v; asm volatile("ld.relaxed.gpu.global.s32 %0, [%1];" : "=r"(v) : "l"(p) : "memory"); return v; }
DEVI int ld_acquire(const int* p) { int v; asm volatile("ld.acquire.gpu.global.s32 %0, [%1];" : "=r"(v) : "l"(p) : "memory"); return __shfl_sync(0xffffffffu, v, 0); }
DEVI void e_tma_3d(uint32_t dst, const CUtensorMap* m, int c0, int c1, int c2, uint32_t bar) {
  asm volatile(ELECT "cp.async.bulk.tensor.3d.shared::cluster.global.mbarrier::complete_tx::bytes [%0], [%1, {%3, %4, %5}], [%2];}"
    :: "r"(dst), "l"(m), "r"(bar), "r"(c0), "r"(c1), "r"(c2) : "memory");
}
DEVI void e_tma_5d(uint32_t dst, const CUtensorMap* m, int c0, int c4, uint32_t bar) {
  asm volatile(ELECT "cp.async.bulk.tensor.5d.shared::cluster.global.mbarrier::complete_tx::bytes [%0], [%1, {%3, %5, %5, %5, %4}], [%2];}"
    :: "r"(dst), "l"(m), "r"(bar), "r"(c0), "r"(c4), "r"(0) : "memory");
}
DEVI void e_bulk_g2s(uint32_t dst, const void* src, uint32_t bytes, uint32_t bar) {
  asm volatile(ELECT "cp.async.bulk.shared::cluster.global.mbarrier::complete_tx::bytes [%0], [%1], %2, [%3];}" :: "r"(dst), "l"(src), "r"(bytes), "r"(bar) : "memory");
}
DEVI void e_prefetch(const void* src, uint32_t bytes) {
  asm volatile(ELECT "cp.async.bulk.prefetch.L2.global [%0], %1;}" :: "l"(src), "r"(bytes) : "memory");
}
DEVI void bulk_commit() { asm volatile("cp.async.bulk.commit_group;" ::: "memory"); }
template<int N> DEVI void bulk_wait_read() { asm volatile("cp.async.bulk.wait_group.read %0;" :: "n"(N) : "memory"); }
template<int N> DEVI void bulk_wait() { asm volatile("cp.async.bulk.wait_group %0;" :: "n"(N) : "memory"); }
template<int ID, int N> DEVI void nbar_sync() { asm volatile("bar.sync %0, %1;" :: "n"(ID), "n"(N) : "memory"); }
template<int ID, int N> DEVI void nbar_arrive() { asm volatile("bar.arrive %0, %1;" :: "n"(ID), "n"(N) : "memory"); }
DEVI void nbar_sync_r(int id, int n) { asm volatile("bar.sync %0, %1;" :: "r"(id), "r"(n) : "memory"); }
DEVI void nbar_arrive_r(int id, int n) { asm volatile("bar.arrive %0, %1;" :: "r"(id), "r"(n) : "memory"); }
template<int R> DEVI void reg_inc() { asm volatile("setmaxnreg.inc.sync.aligned.u32 %0;" :: "n"(R)); }
template<int R> DEVI void reg_dec() { asm volatile("setmaxnreg.dec.sync.aligned.u32 %0;" :: "n"(R)); }
DEVI void wg_fence() { asm volatile("wgmma.fence.sync.aligned;" ::: "memory"); }
DEVI void wg_commit() { asm volatile("wgmma.commit_group.sync.aligned;" ::: "memory"); }
template<int N> DEVI void wg_wait() { asm volatile("wgmma.wait_group.sync.aligned %0;" :: "n"(N) : "memory"); }
DEVI uint32_t pack_bf16(float lo, float hi) { uint32_t r; asm("cvt.rn.bf16x2.f32 %0, %1, %2;" : "=r"(r) : "f"(hi), "f"(lo)); return r; }
DEVI float bf_lo(uint32_t v) { return __uint_as_float(v << 16); }
DEVI float bf_hi(uint32_t v) { return __uint_as_float(v & 0xffff0000u); }
DEVI uint32_t movmat(uint32_t a) { uint32_t r; asm volatile("movmatrix.sync.aligned.m8n8.trans.b16 %0, %1;" : "=r"(r) : "r"(a)); return r; }
DEVI void ldsm4(uint32_t addr, uint32_t& r0, uint32_t& r1, uint32_t& r2, uint32_t& r3) {
  asm volatile("ldmatrix.sync.aligned.m8n8.x4.shared.b16 {%0,%1,%2,%3}, [%4];" : "=r"(r0), "=r"(r1), "=r"(r2), "=r"(r3) : "r"(addr) : "memory");
}
DEVI void ldsm4t(uint32_t addr, uint32_t& r0, uint32_t& r1, uint32_t& r2, uint32_t& r3) {
  asm volatile("ldmatrix.sync.aligned.m8n8.x4.trans.shared.b16 {%0,%1,%2,%3}, [%4];" : "=r"(r0), "=r"(r1), "=r"(r2), "=r"(r3) : "r"(addr) : "memory");
}
DEVI void stsm4(uint32_t addr, uint32_t r0, uint32_t r1, uint32_t r2, uint32_t r3) {
  asm volatile("stmatrix.sync.aligned.m8n8.x4.shared.b16 [%0], {%1,%2,%3,%4};" :: "r"(addr), "r"(r0), "r"(r1), "r"(r2), "r"(r3) : "memory");
}
DEVI uint4 lds128(uint32_t a) { uint4 v; asm volatile("ld.shared.v4.u32 {%0,%1,%2,%3}, [%4];" : "=r"(v.x), "=r"(v.y), "=r"(v.z), "=r"(v.w) : "r"(a) : "memory"); return v; }
DEVI uint32_t lds32v(uint32_t a) { uint32_t v; asm volatile("ld.volatile.shared.u32 %0, [%1];" : "=r"(v) : "r"(a) : "memory"); return v; }
DEVI void sts32v(uint32_t a, uint32_t v) { asm volatile("st.volatile.shared.u32 [%0], %1;" :: "r"(a), "r"(v) : "memory"); }
DEVI void st_async128(uint32_t a, uint32_t x, uint32_t y, uint32_t z, uint32_t w, uint32_t bar) {
  asm volatile("st.async.weak.shared::cluster.mbarrier::complete_tx::bytes.v4.b32 [%0], {%1,%2,%3,%4}, [%5];" :: "r"(a), "r"(x), "r"(y), "r"(z), "r"(w), "r"(bar) : "memory");
}
DEVI void st_async32(uint32_t a, uint32_t x, uint32_t bar) {
  asm volatile("st.async.weak.shared::cluster.mbarrier::complete_tx::bytes.b32 [%0], %1, [%2];" :: "r"(a), "r"(x), "r"(bar) : "memory");
}
DEVI void st_cl128(bool own, uint32_t a, uint32_t x, uint32_t y, uint32_t z, uint32_t w, uint32_t bar) {
  asm volatile("{.reg .pred p; setp.ne.u32 p, %6, 0; @p st.shared.v4.b32 [%0], {%1,%2,%3,%4};\n"
               "@!p st.async.weak.shared::cluster.mbarrier::complete_tx::bytes.v4.b32 [%0], {%1,%2,%3,%4}, [%5];}"
               :: "r"(a), "r"(x), "r"(y), "r"(z), "r"(w), "r"(bar), "r"((uint32_t)own) : "memory");
}
DEVI void st_cl32(bool own, uint32_t a, uint32_t x, uint32_t bar) {
  asm volatile("{.reg .pred p; setp.ne.u32 p, %3, 0; @p st.shared.b32 [%0], %1;\n"
               "@!p st.async.weak.shared::cluster.mbarrier::complete_tx::bytes.b32 [%0], %1, [%2];}" :: "r"(a), "r"(x), "r"(bar), "r"((uint32_t)own) : "memory");
}
DEVI uint4 ldg_rlx128(const void* p) {
  uint4 v;
  asm volatile("ld.relaxed.gpu.global.v4.b32 {%0,%1,%2,%3}, [%4];" : "=r"(v.x), "=r"(v.y), "=r"(v.z), "=r"(v.w) : "l"(p) : "memory");
  return v;
}
DEVI void stg_rlx128(void* p, uint32_t x, uint32_t y, uint32_t z, uint32_t w) {
  asm volatile("st.relaxed.gpu.global.v4.b32 [%0], {%1,%2,%3,%4};" :: "l"(p), "r"(x), "r"(y), "r"(z), "r"(w) : "memory");
}
DEVI void stg128(void* p, uint32_t x, uint32_t y, uint32_t z, uint32_t w) {
  asm volatile("st.global.v4.b32 [%0], {%1,%2,%3,%4};" :: "l"(p), "r"(x), "r"(y), "r"(z), "r"(w) : "memory");
}
DEVI void stg_rlx64(void* p, uint32_t x, uint32_t y) { asm volatile("st.relaxed.gpu.global.v2.b32 [%0], {%1,%2};" :: "l"(p), "r"(x), "r"(y) : "memory"); }
DEVI void stg_rlx32(void* p, uint32_t x) { asm volatile("st.relaxed.gpu.global.b32 [%0], %1;" :: "l"(p), "r"(x) : "memory"); }
DEVI uint32_t clock32() { uint32_t c; asm volatile("mov.u32 %0, %%clock;" : "=r"(c) :: "memory"); return c; }
DEVI uint32_t gtime() { uint32_t c; asm volatile("mov.u32 %0, %%globaltimer_lo;" : "=r"(c) :: "memory"); return c; }
DEVI void wait_time(uint32_t t, int& budget) { while ((int)(gtime() - t) < 0 && --budget > 0) {} }
DEVI uint2 ldg_rlx64(const void* p) { uint2 v; asm volatile("ld.relaxed.gpu.global.v2.b32 {%0,%1}, [%2];" : "=r"(v.x), "=r"(v.y) : "l"(p) : "memory"); return v; }
DEVI void sts16(uint32_t a, uint32_t x) { asm volatile("st.shared.b16 [%0], %1;" :: "r"(a), "h"((unsigned short)x) : "memory"); }
DEVI void sts128(uint32_t a, uint32_t x) { asm volatile("st.shared.v4.b32 [%0], {%1,%1,%1,%1};" :: "r"(a), "r"(x) : "memory"); }
DEVI void arrive_if_eq(uint32_t bar, int a, int b) { asm volatile("{.reg .pred p; setp.eq.s32 p, %1, %2; @p mbarrier.arrive.shared::cta.b64 _, [%0];}" :: "r"(bar), "r"(a), "r"(b) : "memory"); }
DEVI void arrive_cl_if_eq(uint32_t bar, int a, int b) { asm volatile("{.reg .pred p; setp.eq.s32 p, %1, %2; @p mbarrier.arrive.shared::cluster.b64 _, [%0];}" :: "r"(bar), "r"(a), "r"(b) : "memory"); }
template<int ID, int N> DEVI bool nbar_or(bool x) {
  uint32_t r;
  asm volatile("{.reg .pred p, q; setp.ne.u32 p, %1, 0; bar.red.or.pred q, %2, %3, p; selp.u32 %0, 1, 0, q;}" : "=r"(r) : "r"((uint32_t)x), "n"(ID), "n"(N) : "memory");
  return __any_sync(0xffffffffu, r);
}
DEVI void spin_until(uint32_t t0, int d) { while ((int)(clock32() - t0) < d) {} }
DEVI void flag_wait(const int* p, int n, int& budget) {
  while (ld_acquire(p) < n && --budget > 0) __nanosleep(128);
  asm volatile("fence.proxy.async.global;" ::: "memory");
}

#define F4(C, o)  C(d[o+0]), C(d[o+1]), C(d[o+2]), C(d[o+3])
#define F8(C, o)  F4(C, o), F4(C, o+4)
#define F32(C, o) F8(C, o), F8(C, o+8), F8(C, o+16), F8(C, o+24)
#define R4  "{%0,%1,%2,%3}"
#define R8  "{%0,%1,%2,%3,%4,%5,%6,%7}"
#define R16 "{%0,%1,%2,%3,%4,%5,%6,%7,%8,%9,%10,%11,%12,%13,%14,%15}"
#define R20 "{%0,%1,%2,%3,%4,%5,%6,%7,%8,%9,%10,%11,%12,%13,%14,%15,%16,%17,%18,%19}"
#define R32 "{%0,%1,%2,%3,%4,%5,%6,%7,%8,%9,%10,%11,%12,%13,%14,%15,%16,%17,%18,%19,%20,%21,%22,%23,%24,%25,%26,%27,%28,%29,%30,%31}"
#define R64 "{%0,%1,%2,%3,%4,%5,%6,%7,%8,%9,%10,%11,%12,%13,%14,%15,%16,%17,%18,%19,%20,%21,%22,%23,%24,%25,%26,%27,%28,%29,%30,%31," \
  "%32,%33,%34,%35,%36,%37,%38,%39,%40,%41,%42,%43,%44,%45,%46,%47,%48,%49,%50,%51,%52,%53,%54,%55,%56,%57,%58,%59,%60,%61,%62,%63}"
template<uint32_t OFF, uint32_t LBO, uint32_t SBO, uint32_t SW, int T> struct Op {
  static constexpr uint32_t lo = (OFF >> 4) | ((LBO >> 4) << 16), hi = (SBO >> 4) | (SW << 30);
  static constexpr int t = T;
};
DEVI uint32_t desc_base(uint32_t addr) { return (addr & 0x3FFFF) >> 4; }
#define RS_ASM(SHAPE, REGS, A0, A1, A2, A3, B, LO, HI, T, SD) \
  "{.reg .b64 tb; .reg .b32 lb; add.u32 lb, " B ", " LO "; mov.b64 tb, {lb, " HI "};\n" \
  "wgmma.mma_async.sync.aligned." SHAPE ".f32.bf16.bf16 " REGS ", {" A0 "," A1 "," A2 "," A3 "}, tb, " SD ", 1, 1, " T ";}"
#define WG_RS(NAME, SHAPE, REGS, LIST, ...) \
  template<int ACC, class OB> DEVI void NAME(float* d, const uint32_t* a, uint32_t b) { \
    if (ACC) asm volatile(RS_ASM(SHAPE, REGS, __VA_ARGS__) \
      : LIST("+f") : "r"(a[0]), "r"(a[1]), "r"(a[2]), "r"(a[3]), "r"(b), "n"(OB::lo), "n"(OB::hi), "n"(OB::t), "n"(ACC & 1)); \
    else asm volatile(RS_ASM(SHAPE, REGS, __VA_ARGS__) \
      : LIST("=f") : "r"(a[0]), "r"(a[1]), "r"(a[2]), "r"(a[3]), "r"(b), "n"(OB::lo), "n"(OB::hi), "n"(OB::t), "n"(0)); \
  }
#define SS_ASM(SHAPE, REGS, A, B, LA, HA, TA, LB, HB, TB, SD) \
  "{.reg .b64 ta, tb; .reg .b32 la, lb; add.u32 la, " A ", " LA "; mov.b64 ta, {la, " HA "}; add.u32 lb, " B ", " LB "; mov.b64 tb, {lb, " HB "};\n" \
  "wgmma.mma_async.sync.aligned." SHAPE ".f32.bf16.bf16 " REGS ", ta, tb, " SD ", 1, 1, " TA ", " TB ";}"
#define WG_SS(NAME, SHAPE, REGS, LIST, ...) \
  template<int ACC, class OA, class OB> DEVI void NAME(float* d, uint32_t a, uint32_t b) { \
    if (ACC) asm volatile(SS_ASM(SHAPE, REGS, __VA_ARGS__) \
      : LIST("+f") : "r"(a), "r"(b), "n"(OA::lo), "n"(OA::hi), "n"(OA::t), "n"(OB::lo), "n"(OB::hi), "n"(OB::t), "n"(ACC & 1)); \
    else asm volatile(SS_ASM(SHAPE, REGS, __VA_ARGS__) \
      : LIST("=f") : "r"(a), "r"(b), "n"(OA::lo), "n"(OA::hi), "n"(OA::t), "n"(OB::lo), "n"(OB::hi), "n"(OB::t), "n"(0)); \
  }
#define L4(C)  F4(C, 0)
#define L8(C)  F8(C, 0)
#define L16(C) F8(C, 0), F8(C, 8)
#define L20(C) F8(C, 0), F8(C, 8), F4(C, 16)
#define L32(C) F32(C, 0)
WG_RS(wg_rs8, "m64n8k16", R4, L4, "%4", "%5", "%6", "%7", "%8", "%9", "%10", "%11", "%12")
WG_RS(wg_rs16, "m64n16k16", R8, L8, "%8", "%9", "%10", "%11", "%12", "%13", "%14", "%15", "%16")
WG_RS(wg_rs32, "m64n32k16", R16, L16, "%16", "%17", "%18", "%19", "%20", "%21", "%22", "%23", "%24")
WG_SS(wg_ss32, "m64n32k16", R16, L16, "%16", "%17", "%18", "%19", "%20", "%21", "%22", "%23", "%24")
WG_RS(wg_rs64, "m64n64k16", R32, L32, "%32", "%33", "%34", "%35", "%36", "%37", "%38", "%39", "%40")
WG_SS(wg_ss8, "m64n8k16", R4, L4, "%4", "%5", "%6", "%7", "%8", "%9", "%10", "%11", "%12")
WG_SS(wg_ss16, "m64n16k16", R8, L8, "%8", "%9", "%10", "%11", "%12", "%13", "%14", "%15", "%16")
WG_SS(wg_ss40, "m64n40k16", R20, L20, "%20", "%21", "%22", "%23", "%24", "%25", "%26", "%27", "%28")
WG_SS(wg_ss64, "m64n64k16", R32, L32, "%32", "%33", "%34", "%35", "%36", "%37", "%38", "%39", "%40")
#define L64(C) F32(C, 0), F32(C, 32)
WG_SS(wg_ss128, "m64n128k16", R64, L64, "%64", "%65", "%66", "%67", "%68", "%69", "%70", "%71", "%72")
template<int I> struct IC { __host__ __device__ constexpr operator int() const { return I; } };
template<int I, int N, class F> DEVI void sfor(F&& f) {
  if constexpr (I < N) { f(IC<I>{}); sfor<I + 1, N>(f); }
}

#define R_CL 6
namespace rec {
constexpr int NHI = 36, NLO = 5, NRS = NHI + NLO, NSS = 64 - NRS;
constexpr uint32_t WS = 0;
constexpr uint32_t WO = 2 * NSS * 2048;
constexpr uint32_t RING = WO + 65536;
constexpr uint32_t QB = RING + 40960, RG = 2080, POSQ = 0x64210, POSK = 0xB9753, POSV = 0xEDCA8;
#define JA 2
constexpr uint32_t WA = QB;
constexpr uint32_t OM = QB + 9 * RG, OMS = 2 * RG;
constexpr uint32_t OM2 = QB + 16384, OM2S = 2048;
constexpr uint32_t WH = QB + 20480;
constexpr uint32_t B_PART = QB + 15 * RG - 32;
constexpr uint32_t PM0 = QB + 16384, PM1 = QB + 15 * RG, PM2 = PM1 + 256;
constexpr uint32_t BARS = PM2 + 128;
constexpr uint32_t B_FULL = BARS, B_EMPTY = BARS + 40, B_MLAND = BARS + 80, B_QK = BARS + 112, B_V = BARS + 120, B_OM = BARS + 128,
                   B_WA = BARS + 136, B_SDONE = BARS + 144, B_BFREE = BARS + 152, B_W1 = PM1, B_W2 = PM1 + 8, B_WO = PM1 + 16;
constexpr uint32_t SMEM = BARS + 160;
static_assert(SMEM <= 232448 && QB % 1024 == 0, "smem map");
constexpr int R1 = (PM1 - WO) / 4096;
constexpr int NB_WO = 1, NB_ST = 2, NB_P = 3, NB_TR = 4, NB_X = 5, NB_G = 6, NB_G1 = 7, NB_G2 = 8, NB_G4 = 9, NB_S = 10;
__host__ __device__ constexpr bool is_lo(int j) { return j % 12 == 8; }
__host__ __device__ constexpr int lo_before(int j) { return (j + 3) / 12; }
__host__ __device__ constexpr int ss_before(int j) { return (j - lo_before(j)) * NSS / (64 - NLO); }
__host__ __device__ constexpr bool is_ss(int j) { return ss_before(j + 1) != ss_before(j); }
__host__ __device__ constexpr int reg_idx(int j) { return is_lo(j) ? NHI + lo_before(j) : j - ss_before(j) - lo_before(j); }
#define LOQ(i) ((0x12010 >> (4 * (i))) & 3)
template<int j> using OpW = Op<WS + ss_before(j) * 2048, 16, 1024, 1, 1>;
#define P_G1 1
#define P_G2 3
#define P_G2L 0
#define P_OS 1
#define P_NA 6
#define P_G4 10
#define P_G5 12
#define P_FW 0
#define P_SEND 0xff3f2f10u
#define P_WB 2
#define P_WOL 0
#define P_G4L 0
#define P_S1 1
#define P_S2 2
#define P_S0 3
#define P_MB 0
#define P_S4 5
#define P_S5 6
constexpr uint32_t SLOT1 = 0x32410324, USE1 = 0x22111110;
DEVI bool single(int s) { return s < LAG - 1 || s >= NSEG - 1; }
#define TUN(i, v) (v)
}
#define PROFW(wq, i)
DEVI uint32_t mapr(int h, uint32_t addr, int rank) { return mapa(addr, rank + (R_CL == 6 ? (h & 1) * 3 : 0)); }
template<int N> DEVI void pin(float* d) {
#pragma unroll
  for (int i = 0; i < N; i++) asm volatile("" : "+f"(d[i]) :: "memory");
}
DEVI void keep(const void* a) { asm volatile("{.reg .pred p; setp.eq.u64 p, %0, 0; vote.sync.any.pred p, p, 0xffffffff; @p exit;}" :: "l"(a) : "memory"); }
DEVI int lane_reg() { return __shfl_sync(0xffffffffu, threadIdx.x & 31, threadIdx.x & 31); }
#define LANE_NOW [[maybe_unused]] const int lane = lane0 + ((uint32_t)budget >> 30), g = lane >> 2, c = lane & 3

DEVI void rec_proj(const uint32_t sb, const int h, const int rank, const int w, const CUtensorMap* mW, const CUtensorMap* mWo, const uint32_t zero) {
  using namespace rec;
  const int lane0 = lane_reg(), wg = w >> 2, ww = w & 3;
  int budget = SPIN_BUDGET;
  uint32_t wr[NRS * 4];
  {
    LANE_NOW;
    const uint32_t wsw = ((lane & 7) + (lane >> 4) * 8) * 128 + (((ww * 2 + ((lane >> 3) & 1)) ^ (lane & 7)) << 4);
    mbar_wait(sb + B_W1, 0, budget);
#pragma unroll
    for (int r = 0; r < R1; r++) ldsm4t(sb + WO + (wg * R1 + r) * 2048 + wsw, wr[4*r], wr[4*r+1], wr[4*r+2], wr[4*r+3]);
    fence_proxy_async();
    nbar_sync<NB_ST, 256>();
    if (w == 0) {
      if (lane == 0) { mbar_expect_tx(sb + B_W2, (NRS - R1) * 4096); mbar_expect_tx(sb + B_WO, rank == 2 ? 65536 + 16384 + 8192 : 65536); }
      __syncwarp();
      for (int i = lane; i < 128; i += 32) {
        const int j = i & 63, t = i >> 6, r = reg_idx(j);
        if (!is_ss(j) && r >= R1) tma_load_2d(sb + RING + (t * (NRS - R1) + r - R1) * 2048, mW, h * DH + t * 64, j * 16, sb + B_W2);
      }
      const int t0 = (rank + 1) % 3;
      if (lane < 8) tma_load_2d(sb + WO + lane * 8192, mWo, (3 * ((lane >> 1) + (lane >> 1 >= JA)) + t0) * 64, h * DH + (lane & 1) * 64, sb + B_WO);
      else if (rank < 2 && lane < 10) tma_prefetch_2d(mWo, (3 * JA + t0) * 64, h * DH + (lane & 1) * 64);
      else if (rank == 2 && lane < 11) tma_load_2d(lane < 10 ? sb + WA + (lane - 8) * 8192 : sb + WH, mWo, lane < 10 ? 3 * JA * 64 : 15 * 64, h * DH + (lane > 8) * 64, sb + B_WO);
    }
    mbar_wait(sb + B_W2, 0, budget);
#pragma unroll
    for (int r = R1; r < NRS; r++) ldsm4t(sb + RING + (wg * (NRS - R1) + r - R1) * 2048 + wsw, wr[4*r], wr[4*r+1], wr[4*r+2], wr[4*r+3]);
    fence_proxy_async();
    cluster_arrive(); cluster_wait();
  }
  const uint32_t d0 = desc_base(sb), da = d0 + wg * (NSS * 128);
  const uint32_t pos = rank == 0 ? POSQ : rank == 1 ? POSK : POSV, bar = rank == 2 ? B_V : B_QK;
  uint32_t stg[3][4] = {}, pk[16] = {};
  auto stage = [&](uint32_t* t, int r) {
#pragma unroll
    for (int i = 0; i < 4; i++) asm volatile("xor.b32 %0, %1, %2;" : "+r"(t[i]) : "r"(wr[4 * r + i]), "r"(zero));
  };
#pragma unroll 1
  for (int s = -1; s < NSTEP; s++) {
    const uint32_t fl = single(s) ? (s + 1) & 1 : 0;
    if (s >= 0) {
      float d[8];
      stage(stg[0], NHI);
      mbar_wait(sb + B_FULL, 0, budget);
      PROFW(0, 16);
      sfor<0, 8>([&](auto E) {
        constexpr int e = E, q = e >> 1;
        wg_fence();
        sfor<8 * e, 8 * e + 8>([&](auto J) {
          constexpr int j = J;
          typedef Op<RING + j * 512, 256, 128, 0, 1> OB;
          if constexpr (is_ss(j)) wg_ss16<j != 0, OpW<j>, OB>(d, da, d0);
          else wg_rs16<j != 0, OB>(d, is_lo(j) ? stg[LOQ(lo_before(j))] : wr + 4 * reg_idx(j), d0);
        });
        wg_commit();
        if constexpr (e == 0) { if (s > 0) mbar_wait(sb + B_BFREE, (s & 1) ^ 1, budget); }
        if constexpr (e > 0 && !(e & 1)) {
          wg_wait<1>();
          arrive_if_eq(sb + B_EMPTY + 8 * (q - 1), lane0, ww * 32);
        }
        if constexpr (e < 6 && !(e & 1)) sfor<lo_before(16 * q + 16), lo_before(16 * q + 32)>([&](auto I) { constexpr int i = I; stage(stg[LOQ(i)], NHI + i); });
        if constexpr (e < 6 && (e & 1) == P_FW) mbar_wait(sb + B_FULL + 8 * (q + 1), q ? fl : 0, budget);
        if constexpr (((P_SEND >> (4 * e)) & 15) < 4) {
          constexpr int n = (P_SEND >> (4 * e)) & 15;
          LANE_NOW;
          const uint32_t r = mapr(h, sb, n >> 1);
          uint32_t t[4];
#pragma unroll
          for (int i = 0; i < 4; i++) { if (n == 0) t[i] = pk[i]; else asm volatile("xor.b32 %0, %1, %2;" : "=r"(t[i]) : "r"(pk[4*n+i]), "r"(zero)); }
          st_cl128(rank == n >> 1, r + QB + ((pos >> (4 + 4 * c)) & 15) * RG + w * 256 + (n & 1) * 128 + g * 16, t[0], t[1], t[2], t[3], r + bar);
        }
      });
      LANE_NOW;
      const uint32_t dst = QB + (pos & 15) * RG + w * 256 + lane * 4;
      wg_wait<0>();
      pin<8>(d);
      {
        const uint32_t x0 = pack_bf16(d[0], d[1]), x1 = pack_bf16(d[2], d[3]), y0 = pack_bf16(d[4], d[5]), y1 = pack_bf16(d[6], d[7]);
        const uint32_t r = mapr(h, sb, rank == 0);
        if (rank < 2) { sts32v(sb + dst, rank ? y0 : x0); sts32v(sb + dst + 128, rank ? y1 : x1); fence_proxy_async(); }
        st_async32(r + dst, rank ? x0 : y0, r + bar); st_async32(r + dst + 128, rank ? x1 : y1, r + bar);
        if (rank < 2) e_arrive(sb + B_QK);
        else { const uint32_t r1 = mapr(h, sb, 1); st_async32(r1 + dst, y0, r1 + bar); st_async32(r1 + dst + 128, y1, r1 + bar); }
      }
      PROFW(0, 17);
      if (s == NSTEP - 1) break;
      arrive_if_eq(sb + B_EMPTY + 24, lane0, ww * 32);
    } else e_arrive(sb + B_EMPTY + 8 * ww);
    const bool gate = rank < 2 && s >= 0;
    if (single(s)) {
      float d[16];
      sfor<0, 8>([&](auto C) {
        constexpr int cc = C, sl = (SLOT1 >> (4 * cc)) & 15;
        if constexpr (cc == 0) mbar_wait(sb + B_FULL + 8 * sl, 0, budget);
        if constexpr (cc == P_S1) { if (gate) nbar_sync<NB_G1, 384>(); }
        if constexpr (cc == P_S2) { if (gate) nbar_sync<NB_G2, 384>(); }
        if constexpr (cc == P_S0) nbar_sync<NB_WO, 384>();
        if constexpr (cc == P_S4 || cc == P_S5) { if (gate && cc == (rank ? P_S5 : P_S4)) nbar_sync<NB_G4, 384>(); }
        if constexpr (lo_before(cc * 8 + 8) != lo_before(cc * 8)) stage(stg[0], NHI + lo_before(cc * 8));
        wg_fence();
        sfor<0, 8>([&](auto I) {
          constexpr int i = I, j = cc * 8 + i;
          typedef Op<RING + sl * 8192 + (i >> 2) * 4096 + (i & 3) * 32, 16, 1024, 1, 0> OB;
          if constexpr (is_ss(j)) wg_ss32<j != 0, OpW<j>, OB>(d, da, d0);
          else wg_rs32<j != 0, OB>(d, is_lo(j) ? stg[0] : wr + 4 * reg_idx(j), d0);
        });
        wg_commit();
        if constexpr (cc < 7) {
          constexpr int sn = (SLOT1 >> (4 * cc + 4)) & 15;
          mbar_wait(sb + B_FULL + 8 * sn, ((USE1 >> (4 * cc + 4)) & 1) ^ (sn >> 1 == 1 ? fl : 0), budget);
        }
        wg_wait<0>();
        arrive_if_eq(sb + B_EMPTY + 8 * sl, lane0, ww * 32);
      });
      pin<16>(d);
      PROFW(0, 20);
#pragma unroll
      for (int i = 0; i < 8; i++) pk[i] = pk[8 + i] = pack_bf16(d[4 * (i & 3) + ((i >> 1) & 2)], d[4 * (i & 3) + ((i >> 1) & 2) + 1]);
      continue;
    }
    float d[32];
    sfor<0, 16>([&](auto C) {
      constexpr int cc = C, sl = (cc + 4) % 5;
      if constexpr (cc == 0) mbar_wait(sb + B_FULL + 8 * sl, 0, budget);
      if constexpr (cc == P_G1) { if (gate) nbar_sync<NB_G1, 384>(); }
      if constexpr (cc == P_G2) { if (gate) nbar_sync<NB_G2, 384>(); }
      if constexpr (cc == P_NA) {
        PROFW(0, 18);
        nbar_sync<NB_WO, 384>();
      }
      if constexpr (cc == P_G4 || cc == P_G5) { if (gate && cc == (rank ? P_G5 : P_G4)) nbar_sync<NB_G4, 384>(); }
      wg_fence();
      sfor<0, 4>([&](auto I) {
        constexpr int i = I, j = cc * 4 + i;
        typedef Op<RING + sl * 8192 + i * 32, 16, 1024, 1, 0> OB;
        if constexpr (is_ss(j)) wg_ss64<j != 0, OpW<j>, OB>(d, da, d0);
        else wg_rs64<j != 0, OB>(d, is_lo(j) ? stg[0] : wr + 4 * reg_idx(j), d0);
      });
      wg_commit();
      if constexpr (cc == P_NA) PROFW(0, 19);
      if constexpr (cc < 15) {
        if constexpr (is_lo(cc * 4 + 4)) stage(stg[0], reg_idx(cc * 4 + 4));
        mbar_wait(sb + B_FULL + 8 * ((sl + 1) % 5), ((cc + 5) / 5) & 1, budget);
      }
      wg_wait<0>();
      arrive_if_eq(sb + B_EMPTY + 8 * sl, lane0, ww * 32);
    });
    pin<32>(d);
    PROFW(0, 20);
#pragma unroll
    for (int i = 0; i < 16; i++) pk[i] = pack_bf16(d[16 * (i >> 3) + 4 * (i & 3) + ((i >> 1) & 2)], d[16 * (i >> 3) + 4 * (i & 3) + ((i >> 1) & 2) + 1]);
  }
}

DEVI float softmax_row(float* v, uint32_t* p) {
  constexpr float SC = 0.08838834764831845f * 1.4426950408889634f;
  float m = fmaxf(fmaxf(fmaxf(fmaxf(v[0], v[1]), fmaxf(v[2], v[3])), fmaxf(fmaxf(v[4], v[5]), fmaxf(v[6], v[7]))), fmaxf(v[8], v[9]));
  m = fmaxf(m, __shfl_xor_sync(0xffffffffu, m, 1));
  m = fmaxf(m, __shfl_xor_sync(0xffffffffu, m, 2));
  const float ms = -m * SC, mh = fmaf(m, -SC, -1.f);
#pragma unroll
  for (int i = 0; i < 10; i++) asm("ex2.approx.ftz.f32 %0, %1;" : "=f"(v[i]) : "f"(fmaf(v[i], SC, i < 8 ? ms : mh)));
#pragma unroll
  for (int n = 0; n < 5; n++) p[n] = pack_bf16(v[2*n], v[2*n+1]);
  return fmaf(v[8] + v[9], 2.f, ((v[0] + v[1]) + (v[2] + v[3])) + ((v[4] + v[5]) + (v[6] + v[7])));
}

template<bool ATT>
DEVI void rec_attn(const uint32_t sb, int h, int rank, int w, const bf16* __restrict__ Wo, const bf16* __restrict__ mem0) {
  using namespace rec;
  const int lane0 = lane_reg();
  int budget = SPIN_BUDGET;
  constexpr int NT = ATT ? 5 : 6;
  uint32_t wl[16];
  if (!ATT) {
    LANE_NOW;
#pragma unroll
    for (int i = 0; i < 16; i++) {
      const int dh = 8 * (i >> 1) + 2 * c;
      const unsigned short* p = (const unsigned short*)Wo + (size_t)(h * DH + dh) * DM + 15 * 64 + 16 * w + 8 * (i & 1) + g;
      wl[i] = p[0] | (uint32_t)p[DM] << 16;
    }
  }
  cluster_arrive(); cluster_wait();
  const uint32_t d0 = desc_base(sb);
  uint32_t pph = 0;
#pragma unroll 1
  for (int s = -1; s < NSTEP; s++) {
    asm volatile("" : "+r"(h), "+r"(rank), "+r"(w));
    const uint32_t sp = s & 1;
    const int t0 = ATT ? rank + 1 : 0;
    const bool more = s + 1 < NSTEP;
    if (s == 0) mbar_wait(sb + B_WO, 0, budget);
    float hold[10] = {0, 0, 0, 0, 0, 0, 0, 0, 0, 0};
    if (ATT && s >= 0) {
      float sc[20];
      LANE_NOW;
      mbar_wait(sb + B_QK, sp, budget);
      PROFW(0, 1);
      fence_proxy_async();
      wg_fence();
      sfor<0, 8>([&](auto K) { constexpr int k = K; wg_ss40<k != 0, Op<QB + k * 256, 128, RG, 0, 1>, Op<QB + 3 * RG + k * 256, 128, 2 * RG, 0, 1>>(sc, d0, d0); });
      wg_commit();
      if (P_G1 < 16 && more) nbar_arrive<NB_G1, 384>();
      mbar_wait(sb + B_V, sp, budget);
      wg_wait<0>();
      pin<20>(sc);
      if (w == 3 && more) nbar_arrive<NB_S, 64>();
      PROFW(1, 2);
      if (w == 0) {
        uint32_t p[5];
        float v[10];
#pragma unroll
        for (int i = 0; i < 10; i++) v[i] = sc[4 * (i >> 1) + (i & 1)];
        softmax_row(v, p);
        const uint32_t a = sb + lane * 4;
        sts32v(a + PM0, p[0]); sts32v(a + PM0 + 128, p[1]); sts32v(a + PM1, p[2]); sts32v(a + PM1 + 128, p[3]); sts32v(a + PM2, p[4]);
      }
      if (more) {
        float rs[4], ot[2][4];
        uint32_t one[4];
#pragma unroll
        for (int i = 0; i < 4; i++) one[i] = 0x3F803F80u + ((uint32_t)budget >> (31 - i));
        typedef Op<PM0, 128, 128, 0, 0> P0; typedef Op<PM1, 128, 128, 0, 0> P1; typedef Op<PM2, 0, 128, 0, 0> P2;
        fence_proxy_async();
        nbar_sync<NB_P, 128>();
        PROFW(0, 3);
        wg_fence();
        wg_rs8<0, P0>(rs, one, d0); wg_rs8<1, P1>(rs, one, d0); wg_rs8<1, P2>(rs, one, d0);
        wg_commit();
        sfor<0, 2>([&](auto T) {
          constexpr int t = T;
          wg_ss8<0, Op<QB + 8 * RG + t * 1024, 2 * RG, 128, 0, 0>, P0>(ot[t], d0, d0);
          wg_ss8<1, Op<QB + 12 * RG + t * 1024, RG, 128, 0, 0>, P1>(ot[t], d0, d0);
          wg_ss8<1, Op<QB + 14 * RG + t * 1024, 0, 128, 0, 0>, P2>(ot[t], d0, d0);
        });
        wg_commit();
        if (P_G2 < 16 && !P_G2L) nbar_arrive<NB_G2, 384>();
        const uint32_t oa = w * 256 + lane * 4, r1 = mapr(h, sb, rank ^ 1), r2 = mapr(h, sb, 2);
        mbar_wait(sb + B_SDONE, sp, budget);
        wg_wait<1>();
        pin<4>(rs);
        float i0, i1;
        asm volatile("rcp.approx.ftz.f32 %0, %1;" : "=f"(i0) : "f"(rs[0]));
        asm volatile("rcp.approx.ftz.f32 %0, %1;" : "=f"(i1) : "f"(rs[1]));
        wg_wait<0>();
        pin<4>(ot[0]); pin<4>(ot[1]);
        uint32_t x[4];
#pragma unroll
        for (int j = 0; j < 4; j++) {
          x[j] = pack_bf16(ot[j >> 1][2 * (j & 1)] * i0, ot[j >> 1][2 * (j & 1) + 1] * i1);
          sts32v(sb + OM + rank * OMS + oa + (j >> 1) * 1024 + (j & 1) * 128, x[j]);
        }
        fence_proxy_async();
#pragma unroll
        for (int j = 0; j < 8; j++) {
          const int i = P_OS ? j >> 1 : j & 3;
          if (P_OS ? j & 1 : j >> 2) st_async32(r1 + OM + rank * OMS + oa + (i >> 1) * 1024 + (i & 1) * 128, x[i], r1 + B_OM);
          else st_async32(r2 + OM2 + rank * OM2S + oa + (i >> 1) * 1024 + (i & 1) * 128, x[i], r2 + B_OM);
        }
        e_arrive(sb + B_OM);
        if (P_G2 < 16 && P_G2L) nbar_arrive<NB_G2, 384>();
        PROFW(0, 4);
      }
#pragma unroll
      for (int i = 0; i < 10; i++) hold[i] = w ? sc[4 * (i >> 1) + (i & 1)] : sc[4 * (i >> 1) + 2 + (i & 1)];
    }
    if (more && s >= 0) {
      LANE_NOW;
      char* const pw = (char*)g_part + (uint32_t)((t0 * 16 + w * 4 + (lane >> 3)) * 4096 + h * 128 + ((lane ^ h) & 7) * 16);
      mbar_wait(sb + B_OM, sp, budget);
      if (w == 0) nbar_arrive<NB_G, 128>();
      PROFW(1, 5);
      if (!ATT) fence_proxy_async();
      float acc[3][8];
      auto store = [&](auto J) {
        constexpr int j = J;
        float* d = acc[j % 3];
        pin<8>(d);
        uint32_t x[4];
#pragma unroll
        for (int i = 0; i < 4; i++) { const uint32_t m = (h >> 3) == i; x[i] = (pack_bf16(d[2*i], d[2*i+1]) & ~m) | (m & ~sp); }
        stg_rlx128(pw + j * (48 * 4096), x[0], x[1], x[2], x[3]);
        if constexpr (ATT && j == JA) nbar_arrive<NB_TR, 160>();
        if constexpr (j == 2) PROFW(3, 26);
      };
      sfor<0, NT>([&](auto J) {
        constexpr int j = J;
        if constexpr (ATT && j == JA) { mbar_wait(sb + B_WA, sp, budget); PROFW(2, 0); }
        wg_fence();
        sfor<0, 8>([&](auto K) {
          constexpr int k = K;
          typedef Op<(ATT ? OM : OM2) + k * 256, 128, ATT ? OMS : OM2S, 0, 1> OB;
          if constexpr (j == 5 && k < 4) wg_rs16<k ? 1 : 2, OB>(acc[j % 3], wl + 4 * k, d0);
          else wg_ss16<k ? 1 : j < 3 ? 0 : 2, Op<(j == JA ? WA : j < 5 ? WO + (j - (j > JA)) * 16384 : WH - 8192) + k * 2048, 16, 1024, 1, 1>, OB>(acc[j % 3], d0, d0);
        });
        wg_commit();
        if constexpr (j == 0) { if (w == 3) e_expect_tx(sb + B_OM, ATT ? 2048 : 4096); }
        if constexpr (j == NT - 1 && !P_WOL) nbar_arrive<NB_WO, 384>();
        if constexpr (j > 0 && j != P_WB + 1) { wg_wait<1>(); store(IC<j - 1>{}); }
        if constexpr (j == P_WB || j == NT - 1) { wg_wait<0>(); store(IC<j>{}); }
        if constexpr (j == P_WB) {
          const uint32_t t = clock32();
          if (ATT) {
            if (w == 3 && lane < 14) sts128(sb + PM1 + lane * 16, (lane >> 1) == 3 ? 0x3F803F80u : 0);
            if (w == 3 || P_MB) fence_proxy_async();
            nbar_sync<NB_P, 128>();
          } else if (P_MB) fence_proxy_async();
          spin_until(t, TUN(8, 100));
        }
      });
      if (P_WOL) { spin_until(clock32(), TUN(9, 0)); nbar_arrive<NB_WO, 384>(); }
    } else if (more) nbar_arrive<NB_WO, 384>();
    PROFW(0, 6);
    asm volatile("" : "+r"(h), "+r"(rank), "+r"(w));
#pragma unroll 1
    for (int pass = 0; ATT && pass < 2; pass++)
    if (pass != rank) {
      LANE_NOW;
      const int lim = 8 * (g >> 1) + (g & 1) + 2 * w - 8 * c;
      uint32_t p[5];
#pragma unroll
      for (int i = 0; i < 8; i++) hold[2+i] = i <= lim ? hold[2+i] : -INFINITY;
      const float psum = softmax_row(hold, p);
#pragma unroll
      for (int i = 0; i < 5; i++) hold[i] = __uint_as_float(p[i]);
      hold[5] = psum;
    } else if (more) {
      LANE_NOW;
      const int blk = rank * 32 + h;
      char* const mw = (char*)g_mem + (uint32_t)(sp * 32768 + blk * 512 + w * 128 + lane * 4);
      uint32_t v0 = 0;
      if (s == -1 || (s == LAG - 1 && (w & 1))) {
        const unsigned short* q = (const unsigned short*)mem0 + c * 2 * DM + blk * 16 + (w >> 1) * 8 + g;
        v0 = q[0] | (uint32_t)q[DM] << 16;
        if (v0 == 0) v0 = 0x8000u;
      }
      keep(mw);
      if (s >= 0) {
        const uint32_t ca = sb + WA + lane * 128 + (((2 * w) ^ lane) & 7) * 16 + (lane >> 3) * 4;
        const uint32_t sa = sb + OM + (((g >> 1) & 1) * 2 + (g >> 2)) * 128 + (2 * c + (w >> 1)) * 16 + (w & 1) * 8 + (g & 1) * 2;
        const bool g4l = P_G4L == 1 || (P_G4L == 2 && single(s));
        for (bool first = true; ; first = false) {
          float r[4];
          mbar_wait(sb + B_PART, pph, budget);
          PROFW(0, 11);
          pph ^= 1;
          wg_fence();
          sfor<0, 8>([&](auto K) { constexpr int k = K; wg_ss8<k != 0, Op<WA + k * 2048, 16, 1024, 1, 1>, Op<PM1 + (6 - (k & 6)) * 16, 0, 128, 0, 0>>(r, d0, d0); });
          wg_commit();
          if (!g4l && first) nbar_arrive<NB_G4, 384>();
          const uint32_t x0 = lds32v(ca), x1 = lds32v(ca + 4096), x2 = lds32v(ca + 8192), x3 = lds32v(ca + 12288);
          bool bad = __any_sync(0xffffffffu, (sp ? x0 | x1 | x2 | x3 : ~(x0 & x1 & x2 & x3)) & 1) && budget > 0;
          wg_wait<0>();
          pin<4>(r);
          uint32_t y = pack_bf16(r[0], r[2]);
          y |= (y & 0xffffu) ? 0 : 0x8000u;
          y |= (y >> 16) ? 0 : 0x80000000u;
          if (bad) y = 0;
          sts16(sa, y); sts16(sa + 4, y >> 16);
          nbar_sync<NB_P, 128>();
          y = lds32v(sb + OM + w * 128 + lane * 4);
          const bool ok = !__any_sync(0xffffffffu, y == 0);
          if (ok) stg_rlx32(mw, v0 ? v0 : y);
          if (g4l && first) nbar_arrive<NB_G4, 384>();
          if (ok) break;
          nbar_sync<NB_P, 128>();
          budget--;
          if (w == 0) { e_expect_tx(sb + B_PART, 16384); e_bulk_g2s(sb + WA, (const char*)g_part + blk * 16384, 16384, sb + B_PART); }
          __syncwarp();
        }
        nbar_sync<NB_P, 128>();
        if (w < 2) e_arrive_cl(mapr(h, sb + B_BFREE, w));
      } else stg_rlx32(mw, v0);
      stg_rlx32(mw + (sp ? -32768 : 32768), 0);
      PROFW(1, 8);
    }
    if (ATT && s >= 0) {
      const int seg = s - (rank ? LAG : 0);
      const bool act = (unsigned)seg < NSEG;
      LANE_NOW;
      uint32_t a[12];
#pragma unroll
      for (int i = 0; i < 12; i++) a[i] = __float_as_uint(hold[i < 10 ? i >> 1 : 4]) + ((uint32_t)budget >> (31 - (i & 3)));
      float o[32], inv, psum = hold[5];
      char* const ob = (char*)g_o[rank] + ((size_t)(seg * 32 + 8 * (g >> 1) + (g & 1) + 2 * w) * (NH * DH) + h * DH + c * 8) * 2;
      sfor<0, 2>([&](auto HF) {
        constexpr int hf = HF;
        wg_fence();
        wg_rs64<hf * 2, Op<QB + 8 * RG + hf * 1024, 2 * RG, 128, 0, 0>>(o, a, d0);
        wg_rs64<1, Op<QB + 12 * RG + hf * 1024, RG, 128, 0, 0>>(o, a + 4, d0);
        wg_rs64<1, Op<QB + 14 * RG + hf * 1024, 0, 128, 0, 0>>(o, a + 8, d0);
        wg_commit();
        if constexpr (hf == 0) {
          psum += __shfl_xor_sync(0xffffffffu, psum, 1);
          psum += __shfl_xor_sync(0xffffffffu, psum, 2);
          asm("rcp.approx.ftz.f32 %0, %1;" : "=f"(inv) : "f"(psum));
        }
        wg_wait<0>();
        pin<32>(o);
        if constexpr (hf == 1) { if (w == 2 && more) e_arrive_cl(mapr(h, sb + B_BFREE, 2)); }
        if (act) {
#pragma unroll
          for (int i = 0; i < 2; i++)
            stg128(ob + (hf * 2 + i) * 64, pack_bf16(o[16*i] * inv, o[16*i+1] * inv), pack_bf16(o[16*i+4] * inv, o[16*i+5] * inv),
                   pack_bf16(o[16*i+8] * inv, o[16*i+9] * inv), pack_bf16(o[16*i+12] * inv, o[16*i+13] * inv));
        }
      });
      PROFW(0, 7);
      if (act && (seg & 3) == 3) {
        nbar_sync<NB_P, 128>();
        if (w == 0) e_flag_add(g_fl.dep + grp(0, rank, seg >> 2), 4);
      }
    } else if (!ATT && w == 3) {
      if (s + 4 < NSEG) e_prefetch(g_xn[0] + (size_t)((s + 4) * 32 + h) * DM, 2048);
    }
  }
  cluster_arrive(); cluster_wait();
  char* const pw = (char*)g_part + (size_t)((ATT ? rank + 1 : 0) * 16 + w * 4 + (lane0 >> 3)) * 4096 + h * 128 + (lane0 & 7) * 16;
#pragma unroll
  for (int j = 0; j < NT; j++) stg_rlx128(pw + j * (48 * 4096), 0, 0, 0, 0);
}

DEVI void rec_load(const uint32_t sb, const int h, const int rank, const int w, const CUtensorMap* mX, const CUtensorMap* mWo) {
  using namespace rec;
  static_assert(((NSTEP - 1) & 31) != 1 && ((NSTEP - 2) & 31) != 2, "stale time stamps of the previous launch never match");
  const int lane0 = lane_reg(), mq = (w + 3) & 3;
  int budget = SPIN_BUDGET;
  if (w == 0) { e_flag_add(g_fl.xn[0][0]); flag_wait(g_fl.xn[0][0], 96, budget); }
  bool late = false;
  cluster_arrive(); cluster_wait();
  if (w == 0) { if (lane0 < 4) mbar_arrive(sb + B_FULL + 8 * lane0); __syncwarp(); }
  uint32_t lph = 0;
#pragma unroll 1
  for (int s = -1; s < NSTEP - 1; s++) {
    if (w == 0) {
      if (late) flag_wait(g_fl.xn[1][(s + 1 - LAG) >> 2], 128, budget);
      if (single(s)) {
#pragma unroll 1
        for (int i = 0; i < 8; i++) {
          const int k = i < 5 ? (0x21430 >> (4 * i)) & 15 : i;
          const int sl = (SLOT1 >> (4 * k)) & 15;
          mbar_wait(sb + B_EMPTY + 8 * sl, (((USE1 >> (4 * k)) ^ (sl >> 1 == 1 ? s + 1 : 0)) & 1) ^ 1, budget);
          e_expect_tx(sb + B_FULL + 8 * sl, 8192);
          e_tma_3d(sb + RING + sl * 8192, mX + 1, 0, (s + 1 + (s < LAG ? 0 : NSTEP)) * 32, k * 2, sb + B_FULL + 8 * sl);
        }
      } else {
        int sl = 4, ph = 1;
#pragma unroll 1
        for (int i = 0; i < 16; i++) {
          mbar_wait(sb + B_EMPTY + 8 * sl, ph, budget);
          e_expect_tx(sb + B_FULL + 8 * sl, 8192);
          e_tma_3d(sb + RING + sl * 8192, mX, i * 64, (s + 1) * 32, 0, sb + B_FULL + 8 * sl);
          if (++sl == 5) { sl = 0; ph ^= 1; }
        }
      }
      nbar_arrive<NB_X, 128>();
      const int sn = s + 2 - LAG;
      late = (sn & 3) == 0 && (unsigned)sn < NSEG && ld_acquire(g_fl.xn[1][sn >> 2]) < 128;
      asm volatile("fence.proxy.async.global;" ::: "memory");
    }
    uint32_t t = gtime();
    if (s >= 0) {
      uint2 a;
      if (w == 2 && rank < 2) {
        nbar_sync<NB_S, 64>();
        e_expect_tx(sb + B_WA, 16384);
        e_tma_2d(sb + WA, mWo, (3 * JA + 1 + rank) * 64, h * DH, sb + B_WA);
        e_tma_2d(sb + WA + 8192, mWo, (3 * JA + 1 + rank) * 64, h * DH + 64, sb + B_WA);
        e_arrive_cl(mapr(h, sb + B_SDONE, rank ^ 1));
        stg_rlx32(&g_ann[s & 1][lane0][h * 2 + rank], (gtime() & ~31u) | ((s + 1) & 31));
        e_expect_tx(sb + B_QK, 10240);
        e_expect_tx(sb + B_V, 10240);
      }
      if (w) nbar_sync<NB_G, 128>();
      do { a = ldg_rlx64(&g_ann[s & 1][h][lane0 * 2]); } while (__any_sync(0xffffffffu, ((a.x ^ (s + 1)) | (a.y ^ (s + 1))) & 31) && --budget > 0);
      t += __reduce_max_sync(0xffffffffu, max((int)(a.x - t), (int)(a.y - t)));
      t &= ~31u;
      PROFW(1, 12);
      if (w == 1 && rank < 2) {
        nbar_sync<NB_TR, 160>();
        wait_time(t + (single(s) ? (rank ? TUN(11, 1650) : TUN(10, 1250)) : rank ? TUN(1, 1750) : TUN(0, 1350)), budget);
        e_expect_tx(sb + B_PART, 16384);
        e_bulk_g2s(sb + WA, (const char*)g_part + (rank * 32 + h) * 16384, 16384, sb + B_PART);
        PROFW(1, 21);
      }
      t += single(s) ? (mq == 0 ? TUN(12, 2200) : mq == 1 ? TUN(13, 2300) : mq == 2 ? TUN(14, 2700) : TUN(15, 2800))
                     : (mq == 0 ? TUN(2, 2350) : mq == 1 ? TUN(3, 2450) : mq == 2 ? TUN(4, 2850) : TUN(5, 2950));
    }
    if (w) nbar_sync<NB_X, 128>();
    mbar_wait(sb + B_EMPTY + 8 * mq, mq >= 2 && single(s) ? (s + 1) & 1 : 1, budget);
    PROFW(1, 9);
    wait_time(t, budget);
    PROFW(1, 22); PROFW(3, 23);
    while (true) {
      e_expect_tx(sb + B_MLAND + 8 * mq, 8192);
      e_bulk_g2s(sb + RING + mq * 8192, (const char*)g_mem + (s & 1) * 32768 + mq * 8192, 8192, sb + B_MLAND + 8 * mq);
      const uint32_t a = sb + RING + mq * 8192 + lane0 * 32 + (lane0 >> 2) * 4;
      mbar_wait(sb + B_MLAND + 8 * mq, lph, budget);
      lph ^= 1;
      PROFW(1, 24);
      uint32_t mn = 0xffffffffu;
#pragma unroll
      for (int i = 0; i < 8; i++) mn = min(mn, lds32v(a + i * 1024));
      if (!__any_sync(0xffffffffu, mn == 0) || --budget <= 0) break;
    }
    e_arrive(sb + B_FULL + 8 * mq);
    PROFW(1, 10); PROFW(2, 13); PROFW(3, 14); PROFW(0, 15);
  }
}

DEVI void ln_row(const uint4* u, bf16* dst, int lane) {
  const uint32_t* x = (const uint32_t*)u;
  float mean = 0, q = 0;
#pragma unroll
  for (int i = 0; i < 16; i++) mean += bf_lo(x[i]) + bf_hi(x[i]);
  mean *= 1.f / 32;
#pragma unroll
  for (int i = 0; i < 16; i++) { const float a = bf_lo(x[i]) - mean, b = bf_hi(x[i]) - mean; q = fmaf(a, a, fmaf(b, b, q)); }
#pragma unroll
  for (int o = 1; o < 32; o *= 2) {
    const float m2 = __shfl_xor_sync(0xffffffffu, mean, o), q2 = __shfl_xor_sync(0xffffffffu, q, o), dl = m2 - mean;
    q = fmaf(dl * dl, 16.f * o, q + q2);
    mean = 0.5f * (mean + m2);
  }
  const float rs = rsqrtf(q * (1.f / DM) + 1e-5f), mr = -mean * rs;
#pragma unroll
  for (int i = 0; i < 4; i++) {
    uint32_t y[4];
#pragma unroll
    for (int k = 0; k < 4; k++) y[k] = pack_bf16(fmaf(bf_lo(x[4*i+k]), rs, mr), fmaf(bf_hi(x[4*i+k]), rs, mr));
    stg128((uint4*)dst + i * 32 + lane, y[0], y[1], y[2], y[3]);
  }
}

struct RecMaps { CUtensorMap w[3], wo, x[2]; };
__global__ void __cluster_dims__(R_CL, 1, 1) __launch_bounds__(512, 1)
rec_kernel(const __grid_constant__ RecMaps M, const bf16* __restrict__ Wo, const bf16* __restrict__ mem0, const bf16* __restrict__ x, uint32_t zero) {
  using namespace rec;
  extern __shared__ __align__(1024) uint8_t smem[];
  const uint32_t sb = smem_u32(smem);
  const int tid = threadIdx.x, warp = __shfl_sync(0xffffffffu, tid >> 5, 0), wg = warp >> 2, lane = tid & 31;
  const int h = blockIdx.x / 3, rank = blockIdx.x % 3;
  if (warp == 0) {
    if (lane < 20) mbar_init(sb + BARS + 8 * lane, (lane >= 5 && lane < 10) || lane == 19 ? 2 : lane == 14 ? 9 : lane == 16 && rank < 2 ? 5 : 1);
    else if (lane < 23) mbar_init(sb + B_W1 + 8 * (lane - 20), 1);
    else if (lane == 23) mbar_init(sb + B_PART, 1);
    fence_mbar_init();
    __syncwarp();
    if (lane == 0) { mbar_expect_tx(sb + B_W1, (NSS + R1) * 4096); mbar_expect_tx(sb + B_QK, 10240); mbar_expect_tx(sb + B_V, 10240); mbar_expect_tx(sb + B_OM, rank < 2 ? 2048 : 4096); }
    __syncwarp();
    for (int i = lane; i < 128; i += 32) {
      const int j = i >> 1, t = i & 1, r = reg_idx(j);
      if (is_ss(j)) tma_load_2d(sb + WS + (t * NSS + ss_before(j)) * 2048, &M.w[rank], h * DH + t * 64, j * 16, sb + B_W1);
      else if (r < R1) tma_load_2d(sb + WO + (t * R1 + r) * 2048, &M.w[rank], h * DH + t * 64, j * 16, sb + B_W1);
      else tma_prefetch_2d(&M.w[rank], h * DH + t * 64, j * 16);
    }
  } else if (warp == 1) {
    constexpr int N = (sizeof(Flags) - sizeof(g_fl.xn)) / 16;
    if (lane < 8 && blockIdx.x * 8 + lane < N) ((uint4*)g_fl.dep)[blockIdx.x * 8 + lane] = make_uint4(0, 0, 0, 0);
    static_assert(N <= 96 * 8, "flag reset");
    if (blockIdx.x < 64) ((uint4*)g_stat[4])[blockIdx.x * 64 + lane] = ((uint4*)g_stat[4])[blockIdx.x * 64 + 32 + lane] = make_uint4(0, 0, 0, 0);
    __threadfence();
    __syncwarp();
    asm volatile("griddepcontrol.launch_dependents;" ::: "memory");
  } else if (warp >= 5 && blockIdx.x * 11 + warp - 5 < SEQ / 2) {
    const size_t o = (size_t)(blockIdx.x * 11 + warp - 5) * (2 * DM);
    uint4 u[8];
#pragma unroll
    for (int i = 0; i < 8; i++) u[i] = __ldg((const uint4*)(x + o) + i * 32 + lane);
    ln_row(u, g_xn[0] + o, lane);
    ln_row(u + 4, g_xn[0] + o + DM, lane);
  }
  __syncthreads();
  if (wg == 3) {
    reg_dec<24>();
    rec_load(sb, h, rank, warp & 3, M.x, &M.wo);
    cluster_arrive(); cluster_wait();
  } else if (wg == 2) {
    reg_dec<72>();
    if (rank < 2) rec_attn<true>(sb, h, rank, warp & 3, Wo, mem0);
    else rec_attn<false>(sb, h, rank, warp & 3, Wo, mem0);
  } else {
    reg_inc<208>();
    rec_proj(sb, h, rank, warp, &M.w[rank], &M.wo, zero);
    cluster_arrive(); cluster_wait();
  }
}

namespace gm {
constexpr int STAGES = 6, STAGE_BYTES = 32768;
constexpr uint32_t SO = STAGES * STAGE_BYTES, B_FULL = SO + 32768, B_TRIG = B_FULL + 56, B_EMPTY = B_FULL + 64, B_JOB = B_FULL + 128,
                   B_MSG = B_FULL + 144, B_XF = B_FULL + 160, B_SF = B_FULL + 176, JOB = B_FULL + 192, MSG = JOB + 8, SMEM = B_FULL + 256;
constexpr int T_O = 0, T_GU = 1, T_D = 2, T_END = 3;
#define G_LOOK 8
#define G_FILL 7
#define G_SLEEP 100
#define G_SLEEP2 500
#define G_SLEEP3 100
#define G_DF 0
#define G_FL 10
#define G_DE 0
#define G_DS 16
DEVI bool is_split(int ty, int l, int cb) { return ty == T_O || (ty == T_D && (!l || cb >= G_DS)); }
struct Pipe { int s, ph; DEVI void next() { if (++s == STAGES) { s = 0; ph ^= 1; } } };
}
struct GemmMaps { CUtensorMap o, wo, x, x1, x1s, xm, xms, xn, wg, wu, h, hs, wd, x2, out, outs; };

DEVI float geglu(float g, float u) {
  const float z = g * (0.7978845608028654f + 0.035677408136300125f * g * g);
  float t; asm("tanh.approx.f32 %0, %1;" : "=f"(t) : "f"(z));
  const float hg = 0.5f * g;
  return fmaf(hg, t, hg) * u;
}
DEVI int h_ready(int v) { const int t = v ^ 0x10101414; return t >> 24 ? 0 : t ? ((__ffs(t) - 1) >> 3) * 20 : 56; }
DEVI int a_ready(int ty, int l, int cb) {
  const int v = ld_acquire(g_fl.dep + grp(ty, l, cb));
  asm volatile("fence.proxy.async.global;" ::: "memory");
  return ty == gm::T_D ? h_ready(v) : v >= (ty == gm::T_O && l ? 256 : 128) ? 64 : 0;
}

__global__ void __cluster_dims__(2, 1, 1) __launch_bounds__(512, 1) gemm_kernel(const __grid_constant__ GemmMaps M) {
  using namespace gm;
  extern __shared__ __align__(1024) uint8_t smem[];
  const uint32_t sb = smem_u32(smem);
  const int tid = threadIdx.x, wid = __shfl_sync(0xffffffffu, tid >> 5, 0), wg = wid >> 2, warp = wid & 3;
  int budget = SPIN_BUDGET;
  const int rank = blockIdx.x & 1;
  const uint32_t peer = mapa(sb, rank ^ 1);
  if (tid < 24) mbar_init(sb + B_FULL + 8 * tid, tid >> 3 == 1 ? 2 : 1);
  fence_mbar_init();
  if (wid == 1 && rank == 0) sts32v(sb + JOB + 16, bcast(e_ticket(g_fl.ticket)));
  cluster_arrive(); cluster_wait();
  int pair;
  asm volatile("ld.shared::cluster.u32 %0, [%1];" : "=r"(pair) : "r"(mapa(sb + JOB + 16, 0)) : "memory");
  pair = __shfl_sync(0xffffffffu, pair, 0);
  const int cta = pair * 2 + rank, lane = lane_reg();
  if (wg >= 2) {
    reg_dec<72>();
    if (wid == 8 || wid == 10) {
      Pipe p; p.s = 0; p.ph = 1;
      for (int n = 0; ; n++) {
        if (wid == 8) e_expect_tx(sb + B_MSG + 8 * (n & 1), 4);
        mbar_wait(sb + B_MSG + 8 * (n & 1), (n >> 1) & 1, budget);
        const int msg = __shfl_sync(0xffffffffu, lds32v(sb + MSG + 4 * (n & 1)), 0);
        const int ty = (msg >> 11) & 3, l = (msg >> 10) & 1;
        const bool shb = ty == T_GU && l, spl = is_split(ty, l, (msg >> 6) & 15);
        const int cb = ((msg >> 6) & 15) + (shb ? rank : 0), j = (msg & 63) + (ty == T_END || shb ? 0 : rank);
        const int ke = ty == T_O ? 64 : ty == T_GU ? 16 : 56, k0 = spl ? rank : 0, dk = spl ? 2 : 1;
        const int c0 = ty == T_GU ? j * 64 : spl ? (j >> 1) * 128 : j * 128, c1 = ty == T_GU ? c0 : c0 + 64;
        mbar_wait(sb + B_EMPTY + 8 * p.s, p.ph, budget);
        trap_if_spent(budget);
        auto stages = [&](auto f) {
#pragma unroll 1
          for (int k = k0; k < ke; k += dk) {
            mbar_wait(sb + B_EMPTY + 8 * p.s, p.ph, budget);
            f(k, sb + p.s * STAGE_BYTES, sb + B_FULL + 8 * p.s);
            p.next();
          }
        };
        if (wid == 8) {
          const int job = ty << 11 | l << 10 | cb << 6 | j;
          sts32v(sb + JOB + 4 * (n & 1), job | p.s << 16 | (p.ph ^ 1) << 20);
          e_arrive(sb + B_JOB + 8 * (n & 1));
          if (ty == T_END) break;
          if (ty != T_GU) { e_expect_tx(sb + B_FULL + 8 * p.s, spl ? 16384 : STAGE_BYTES); p.next(); }
          const CUtensorMap* const m0 = ty == T_D ? &M.wd : shb && rank ? &M.wu : &M.wg, * const m1 = ty == T_D ? &M.wd : &M.wu;
          if (ty == T_O) stages([&](int k, uint32_t a, uint32_t fb) { e_expect_tx(fb, STAGE_BYTES); e_tma_5d(a + 16384, &M.wo, c0, k * 2, fb); e_tma_5d(a + 24576, &M.wo, c1, k * 2, fb); });
          else if (shb) stages([&](int k, uint32_t a, uint32_t fb) { e_expect_tx(fb, STAGE_BYTES); e_tma_2d_mc(a + 16384 + rank * 8192, m0, c0, k * 64, fb); });
          else stages([&](int k, uint32_t a, uint32_t fb) { e_expect_tx(fb, STAGE_BYTES); e_tma_2d(a + 16384, m0, c0, k * 64, fb); e_tma_2d(a + 24576, m1, c1, k * 64, fb); });
        } else {
          if (ty == T_END) break;
          const int row = l * SEQ + cb * 128, kt = ke + k0 - G_LOOK * dk;
          int rdy = msg >> 16;
          auto need = [&](int k) {
            if (k == kt) e_arrive(sb + B_TRIG);
            while (k >= rdy && k >= (rdy = a_ready(ty, l, cb))) { __nanosleep(G_SLEEP); trap_if_spent(--budget); }
          };
          if (ty != T_GU) {
            need(0);
            const uint32_t a = sb + p.s * STAGE_BYTES, fb = sb + B_FULL + 8 * p.s;
            const CUtensorMap* const m = ty == T_D ? (spl ? &M.x1 : &M.x1s) : l ? &M.x2 : &M.x;
            const int r = (ty == T_D ? row : cb * 128) + (spl ? rank * 64 : 0);
            e_tma_2d(a, m, c0, r, fb); e_tma_2d(a + 16384, m, c1, r, fb);
            p.next();
          }
          if (shb || spl) {
            const CUtensorMap* const ma = ty == T_O ? &M.o : ty == T_GU ? &M.xms : &M.hs;
            stages([&](int k, uint32_t a, uint32_t fb) { need(k); e_tma_2d(a, ma, k * 64, row, fb); });
          } else {
            const CUtensorMap* const ma = ty == T_GU ? &M.xm : &M.h;
            stages([&](int k, uint32_t a, uint32_t fb) { need(k); e_tma_2d_mc(a + rank * 8192, ma, k * 64, row + rank * 64, fb); });
          }
        }
      }
    } else if (wid == 9 && rank == 0) {
      int k1 = pair < 18 ? 0 : 68;
      bool late = false;
      for (int n = 0, ty = 0; ty != T_END; n++) {
        mbar_wait(sb + B_TRIG, (n & 1) ^ 1, budget);
        int l, cb, j, rdy = 64;
        while (true) {
          const int ph = k1 & 3;
          const bool gap = ph == 3;
          if (k1 < 68) {
            cb = (k1++ >> 2) - (pair < 8 ? ph : 0);
            if ((unsigned)cb >= 16 || (ph == 2 && pair >> 3 != 1) || (gap && (pair < 8 || late || !(G_FILL & (pair >> 3))))) continue;
            if (!gap) {
              l = 0;
              ty = pair < 8 ? (ph ? T_D : T_O) : T_GU;
              j = 2 * (pair < 8 ? pair : pair - 8 + 10 * ph);
              rdy = a_ready(ty, 0, cb);
              if (ph == 0) late = rdy != 0;
              break;
            }
          }
          int d0 = ld_relaxed(g_fl.dep + lane), d1 = ld_relaxed(g_fl.dep + 32 + lane);
          const int t0 = ld_relaxed(g_fl.taken + lane), t1 = ld_relaxed(g_fl.taken + 32 + lane);
          const bool l0 = t0 < (lane < 16 ? 8 : lane & 1 ? 0 : 56), l1 = lane < 16 && t1 < (lane < G_DS ? 4 : 8);
          const uint32_t rd = __ballot_sync(0xffffffffu, d0 >= (lane < 16 ? 256 : 128));
          uint32_t ok0 = __ballot_sync(0xffffffffu, l0) & rd & (rd >> 1 | 0xffff), ok1 = __ballot_sync(0xffffffffu, l1 && h_ready(d1) > 0);
          if (gap) { ok1 = 0; if (pair < 16) ok0 &= G_FILL & 8 ? ((k1 >> 2 ^ pair) & 1 ? ~0u : 0u) : G_FILL & 4 ? 0xffff0003u : 0xffff0000u; }
          ty = T_END; l = 1; cb = j = 0;
          if (!gap && !__any_sync(0xffffffffu, l0 || l1)) break;
          if (ok1 & ((1u << G_DS) - 1)) ok1 &= (1u << G_DS) - 1;
          const uint32_t dfirst = ok1 & __ballot_sync(0xffffffffu, lane < G_DF && d1 == 0x10101414);
          if (dfirst && !(ok0 & 0xffff)) { ok0 = 0; ok1 = dfirst; }
          else if (__any_sync(0xffffffffu, l0)) ok1 &= (1u << G_DE) - 1;
          uint32_t m = ok0 ? ok0 : ok1;
          if (!m && !gap) __nanosleep(100);
          while (m) {
            const int nth = ok0 ? 0 : pair % __popc(m);
            const int b = __ffs(__ballot_sync(0xffffffffu, __popc(m << (31 - lane)) > nth)) - 1, gn = b + (ok0 ? 0 : 32);
            const int t = bcast(e_ticket(g_fl.taken + gn));
            if (t < (gn < 16 ? 8 : gn < 32 ? 56 : gn < 32 + G_DS ? 4 : 8)) { ty = gn >> 4; cb = gn & 15; j = ty == T_GU ? t : 2 * t; break; }
            m &= ~(1u << b);
          }
          if (ty != T_END) {
            rdy = a_ready(ty, 1, cb);
            if (ty == T_GU) a_ready(ty, 1, cb + 1);
            break;
          }
          trap_if_spent(--budget);
        }
        const int msg = rdy << 16 | ty << 11 | l << 10 | cb << 6 | j;
        e_st_async32(peer + MSG + 4 * (n & 1), msg, peer + B_MSG + 8 * (n & 1));
        e_st_async32(sb + MSG + 4 * (n & 1), msg, sb + B_MSG + 8 * (n & 1));
      }
    } else if (wg == 3) {
      bool open = lane < G_FL && ld_relaxed(g_fl.rows + lane) < 128;
      while (__any_sync(0xffffffffu, open)) {
        int v = 0;
        if (open) asm volatile("ld.acquire.gpu.global.s32 %0, [%1];" : "=r"(v) : "l"(g_fl.part + lane) : "memory");
        const uint32_t ok = __ballot_sync(0xffffffffu, open && v >= 128);
        if (!ok) {
          if (--budget <= 0) break;
          __nanosleep(G_SLEEP2);
          continue;
        }
        const int cb = __ffs(__ballot_sync(0xffffffffu, __popc(ok << (31 - lane)) > (cta >> 5) % __popc(ok))) - 1;
        const int r = bcast(e_ticket(g_fl.rows + cb));
        if (r >= 128) { open = open && lane != cb; continue; }
        uint4 u[4];
#pragma unroll
        for (int i = 0; i < 4; i++) u[i] = ldg_rlx128((const uint4*)(g_x1[1] + (size_t)(cb * 128 + r) * DM) + i * 32 + lane);
        ln_row(u, g_xm[1] + (size_t)(cb * 128 + r) * DM, lane);
        __syncwarp();
        e_flag_add(g_fl.dep + grp(T_GU, 1, cb));
      }
      if (cta == 0 && wid == 12) {
        asm volatile("griddepcontrol.wait;" ::: "memory");
        g_fl.xn[lane >> 4][lane & 15][0] = 0;
      }
    }
    cluster_arrive(); cluster_wait();
  } else {
    reg_inc<184>();
    const bool lead = warp == 0;
    const uint32_t eb = (warp == 1 ? peer : sb) + B_EMPTY;
    const int rl = warp < 2 ? 0 : -1;
    const uint32_t so = sb + SO + wg * 16384;
    const int r0 = warp * 16 + (lane & 7) + ((lane >> 3) & 1) * 8;
    const uint32_t sw = r0 * 128 + (((lane >> 4) ^ (r0 & 7)) << 4);
    int xph = 0;
    for (int n = wg; ; n += 2) {
      float d0[64], d1[64];
      mbar_wait(sb + B_JOB + 8 * wg, (n >> 1) & 1, budget);
      fault_if_spent(budget);
      const int job = __shfl_sync(0xffffffffu, lds32v(sb + JOB + 4 * wg), 0);
      const int ty = (job >> 11) & 3, l = (job >> 10) & 1, cb = (job >> 6) & 15, j = job & 63;
      if (ty == T_END) {
        if (n > 0) nbar_sync_r(1 + wg, 256);
        if (lead && !(job & 1)) { sts32v(sb + JOB + 4 * (wg ^ 1), job | 1); e_arrive(sb + B_JOB + 8 * (wg ^ 1)); }
        if (!(job & 1)) nbar_arrive_r(1 + (wg ^ 1), 256);
        break;
      }
      Pipe q; q.s = (job >> 16) & 15; q.ph = job >> 20;
      const bool spl = is_split(ty, l, cb);
      if (ty != T_GU) mbar_wait(sb + B_FULL + 8 * q.s, q.ph, budget);
#pragma unroll
      for (int m = 0; m < 2; m++) {
        float* d = m ? d1 : d0;
        if (ty != T_GU && !(m && spl)) {
#pragma unroll
          for (int c = 0; c < 8; c++) {
            uint32_t r[4];
            ldsm4(sb + q.s * STAGE_BYTES + (c >> 2) * 16384 + m * 8192 + (sw ^ ((c & 3) << 5)), r[0], r[1], r[2], r[3]);
#pragma unroll
            for (int i = 0; i < 4; i++) { d[8*c+2*i] = bf_lo(r[i]); d[8*c+2*i+1] = bf_hi(r[i]); }
          }
        } else {
#pragma unroll
          for (int i = 0; i < 64; i++) d[i] = 0.f;
        }
      }
      if (ty != T_GU) {
        fence_proxy_async();
        nbar_sync_r(3 + wg, 128);
        arrive_cl_if_eq(eb + 8 * q.s, lane, rl);
        q.next();
      }
      pin<64>(d0); pin<64>(d1);
      if (n > 0) nbar_sync_r(1 + wg, 256);
      const int nk = ty == T_O ? 32 : ty == T_GU ? 16 : spl ? 28 : 56;
      const uint32_t ro = spl ? rank * 512 : 0;
      int prev = 0;
      for (int i = 0; i < nk; i++) {
        mbar_wait(sb + B_FULL + 8 * q.s, q.ph, budget);
        const uint32_t da = desc_base(sb) + q.s * (STAGE_BYTES / 16);
        wg_fence();
        sfor<0, 4>([&](auto K) {
          constexpr int k = K;
          typedef Op<16384 + k * 2048, 8192, 1024, 1, 1> OB;
          wg_ss128<1, Op<k * 32, 16, 1024, 1, 0>, OB>(d0, da + ro, da);
          wg_ss128<1, Op<8192 + k * 32, 16, 1024, 1, 0>, OB>(d1, da - ro, da);
        });
        wg_commit();
        wg_wait<1>();
        arrive_cl_if_eq(eb + 8 * prev, lane, i ? rl : -1);
        prev = q.s;
        q.next();
      }
      nbar_arrive_r(1 + (wg ^ 1), 256);
      wg_wait<0>();
      pin<64>(d0); pin<64>(d1);
      arrive_cl_if_eq(eb + 8 * prev, lane, rl);
      if (spl) {
        const uint32_t xa = SO + wg * 16384 + warp * 512 + lane * 16;
        if (lead) e_expect_tx(sb + B_XF + 8 * wg, 16384);
        mbar_wait(sb + B_SF + 8 * wg, ((n >> 1) & 1) ^ 1, budget);
#pragma unroll
        for (int i = 0; i < 8; i++) {
          const float* d = d1 + 8 * i;
          st_async128(peer + xa + i * 2048, pack_bf16(d[0], d[1]), pack_bf16(d[2], d[3]), pack_bf16(d[4], d[5]), pack_bf16(d[6], d[7]), peer + B_XF + 8 * wg);
        }
        mbar_wait(sb + B_XF + 8 * wg, xph, budget);
        xph ^= 1;
        uint32_t y[32];
#pragma unroll
        for (int i = 0; i < 8; i++) {
          const float* d = d0 + 8 * i;
          const uint4 v = lds128(sb + xa + i * 2048);
          y[4*i] = pack_bf16(d[0] + bf_lo(v.x), d[1] + bf_hi(v.x)); y[4*i+1] = pack_bf16(d[2] + bf_lo(v.y), d[3] + bf_hi(v.y));
          y[4*i+2] = pack_bf16(d[4] + bf_lo(v.z), d[5] + bf_hi(v.z)); y[4*i+3] = pack_bf16(d[6] + bf_lo(v.w), d[7] + bf_hi(v.w));
        }
        const bool fuse = !l || (ty == T_O && cb >= G_FL);
        float2* const st = &g_stat[l ? 4 + (cb & 7) : ty + (cb & 1)][0][rank * 64 + warp * 16 + (lane >> 2) * 2];
        if (fuse) {
          float mn[2], sq[2];
#pragma unroll
          for (int z = 0; z < 2; z++) {
            float m = 0, s2 = 0;
#pragma unroll
            for (int i = 0; i < 16; i++) m += bf_lo(y[2*i+z]) + bf_hi(y[2*i+z]);
            m += __shfl_xor_sync(0xffffffffu, m, 1); m += __shfl_xor_sync(0xffffffffu, m, 2);
            m *= 1.f / 128;
#pragma unroll
            for (int i = 0; i < 16; i++) { const float a = bf_lo(y[2*i+z]) - m, b = bf_hi(y[2*i+z]) - m; s2 = fmaf(a, a, fmaf(b, b, s2)); }
            s2 += __shfl_xor_sync(0xffffffffu, s2, 1); s2 += __shfl_xor_sync(0xffffffffu, s2, 2);
            mn[z] = m; sq[z] = s2;
          }
          if ((lane & 3) == 0) stg_rlx128(st + (j >> 1) * 128, __float_as_uint(mn[0]), (__float_as_uint(sq[0]) & ~31u) | (cb + 1), __float_as_uint(mn[1]), __float_as_uint(sq[1]));
          __syncwarp();
        }
        const int row = (ty == T_O ? l * SEQ : 0) + cb * 128 + rank * 64;
        auto put = [&](const CUtensorMap* mo, auto f) {
          nbar_sync_r(3 + wg, 128);
#pragma unroll
          for (int c = 0; c < 8; c++) stsm4(so + (c >> 2) * 8192 + (sw ^ ((c & 3) << 5)), f(4*c), f(4*c+1), f(4*c+2), f(4*c+3));
          fence_proxy_async();
          nbar_sync_r(3 + wg, 128);
          if (lead) { e_tma_store_2d(mo, so, (j >> 1) * 128, row); e_tma_store_2d(mo, so + 8192, (j >> 1) * 128 + 64, row); bulk_commit(); }
        };
        if (fuse) {
          uint4 u[2];
          while (true) {
            __nanosleep(G_SLEEP3);
            u[0] = ldg_rlx128(st + (lane & 3) * 256); u[1] = ldg_rlx128(st + (lane & 3) * 256 + 128);
            if (!__any_sync(0xffffffffu, ((u[0].y ^ (cb + 1)) | (u[1].y ^ (cb + 1))) & 31) || --budget <= 0) break;
          }
          float rs[2], mr[2];
#pragma unroll
          for (int z = 0; z < 2; z++) {
            const float ma = __uint_as_float(z ? u[0].z : u[0].x), mb = __uint_as_float(z ? u[1].z : u[1].x);
            float m = ma + mb;
            m += __shfl_xor_sync(0xffffffffu, m, 1); m += __shfl_xor_sync(0xffffffffu, m, 2);
            m *= 0.125f;
            float s2 = __uint_as_float(z ? u[0].w : u[0].y & ~31u) + __uint_as_float(z ? u[1].w : u[1].y & ~31u) + 128.f * ((ma - m) * (ma - m) + (mb - m) * (mb - m));
            s2 += __shfl_xor_sync(0xffffffffu, s2, 1); s2 += __shfl_xor_sync(0xffffffffu, s2, 2);
            rs[z] = rsqrtf(s2 * (1.f / DM) + 1e-5f); mr[z] = -m * rs[z];
          }
          put(ty == T_O ? &M.xm : &M.xn, [&](int i) { return pack_bf16(fmaf(bf_lo(y[i]), rs[i & 1], mr[i & 1]), fmaf(bf_hi(y[i]), rs[i & 1], mr[i & 1])); });
          if (lead) {
            bulk_wait<0>();
            e_flag_add_bulk(ty == T_D ? g_fl.xn[1][cb] : g_fl.dep + grp(T_GU, l, cb), 8);
          }
        }
        put(ty == T_O ? &M.x1 : l ? &M.out : &M.x2, [&](int i) { return y[i]; });
      } else {
        if (ty == T_GU) {
#pragma unroll
          for (int i = 0; i < 32; i++) { d0[i] = geglu(d0[i], d0[32 + i]); d1[i] = geglu(d1[i], d1[32 + i]); }
        }
#pragma unroll
        for (int hf = 0; hf < 2; hf++) {
          if (hf) {
            if (ty == T_GU) break;
            if (lead) bulk_wait_read<0>();
            nbar_sync_r(3 + wg, 128);
          }
#pragma unroll
          for (int m = 0; m < 2; m++)
#pragma unroll
            for (int c = 0; c < 4; c++) {
              const float* d = (m ? d1 : d0) + 32 * hf + 8 * c;
              stsm4(so + m * 8192 + (sw ^ (c << 5)), pack_bf16(d[0], d[1]), pack_bf16(d[2], d[3]), pack_bf16(d[4], d[5]), pack_bf16(d[6], d[7]));
            }
          fence_proxy_async();
          nbar_sync_r(3 + wg, 128);
          if (lead) {
            if (ty == T_GU) e_tma_store_2d(&M.hs, so, j * 64, l * SEQ + cb * 128); else e_tma_store_2d(&M.outs, so, j * 128 + hf * 64, cb * 128);
            bulk_commit();
          }
        }
      }
      if (lead) {
        bulk_wait<0>();
        e_arrive_cl(peer + B_SF + 8 * wg);
        if (ty == T_GU) e_flag_add_bulk(g_fl.dep + grp(T_D, l, cb), 1 << (j / 20 * 8));
        else if (ty == T_O) { e_flag_add_bulk(g_fl.dep + grp(T_D, l, cb), 1 << 24); if (l && cb < G_FL) e_flag_add_bulk(g_fl.part + cb, 8); }
        else if (!l) e_flag_add_bulk(g_fl.dep + grp(T_O, 1, cb), 8);
      }
    }
    cluster_arrive(); cluster_wait();
  }
}

typedef CUresult (*PFN_encodeTiled)(CUtensorMap*, CUtensorMapDataType, cuuint32_t, void*, const cuuint64_t*, const cuuint64_t*,
                                    const cuuint32_t*, const cuuint32_t*, CUtensorMapInterleave, CUtensorMapSwizzle,
                                    CUtensorMapL2promotion, CUtensorMapFloatOOBfill);
static PFN_encodeTiled g_encode = nullptr;
static int g_sms = 0;
static CUtensorMap encode(const void* ptr, int rank, const cuuint64_t* dims, const cuuint64_t* strides, const cuuint32_t* box) {
  CUtensorMap m;
  const cuuint32_t es[5] = {1, 1, 1, 1, 1};
  g_encode(&m, CU_TENSOR_MAP_DATA_TYPE_BFLOAT16, rank, (void*)ptr, dims, strides, box, es, CU_TENSOR_MAP_INTERLEAVE_NONE,
           CU_TENSOR_MAP_SWIZZLE_128B, CU_TENSOR_MAP_L2_PROMOTION_L2_256B, CU_TENSOR_MAP_FLOAT_OOB_FILL_NONE);
  return m;
}
static CUtensorMap make_map(const void* ptr, uint64_t rows, uint64_t cols, uint32_t box_rows) {
  const cuuint64_t dims[2] = {cols, rows}, strides[1] = {cols * 2};
  const cuuint32_t box[2] = {64, box_rows};
  return encode(ptr, 2, dims, strides, box);
}
static CUtensorMap make_map_x(const void* ptr) {
  const cuuint64_t dims[3] = {DM, NSTEP * 32, 2}, strides[2] = {DM * 2, (cuuint64_t)NSTEP * 32 * DM * 2};
  const cuuint32_t box[3] = {64, 32, 2};
  return encode(ptr, 3, dims, strides, box);
}
static CUtensorMap make_map_x1(const void* ptr) {
  const cuuint64_t dims[3] = {64, 2 * NSTEP * 32, DM / 64}, strides[2] = {DM * 2, 128};
  const cuuint32_t box[3] = {64, 32, 2};
  return encode(ptr, 3, dims, strides, box);
}
static CUtensorMap make_map_wo(const void* ptr) {
  const cuuint64_t dims[5] = {DM, 2, 4, 4, NH * DH / 32}, strides[4] = {DM * 2, 8 * DM * 2, 2 * DM * 2, 32 * DM * 2};
  const cuuint32_t box[5] = {64, 2, 4, 4, 2};
  return encode(ptr, 5, dims, strides, box);
}

extern "C" void kernel_launch(void* const* d_in, const int* in_sizes, int n_in, void* d_out, int out_size) {
  const bf16 *x = (const bf16*)d_in[0], *mem0 = (const bf16*)d_in[1], *Wo = (const bf16*)d_in[5];
  if (!g_encode) {
    void* p = nullptr; cudaDriverEntryPointQueryResult q;
    cudaGetDriverEntryPoint("cuTensorMapEncodeTiled", &p, cudaEnableDefault, &q);
    g_encode = (PFN_encodeTiled)p;
    int dev = 0;
    cudaGetDevice(&dev);
    cudaDeviceGetAttribute(&g_sms, cudaDevAttrMultiProcessorCount, dev);
    cudaFuncSetAttribute(rec_kernel, cudaFuncAttributeMaxDynamicSharedMemorySize, rec::SMEM);
    cudaFuncSetAttribute(gemm_kernel, cudaFuncAttributeMaxDynamicSharedMemorySize, gm::SMEM);
  }
  void *xn, *o, *x1, *xm, *x2, *hh;
  cudaGetSymbolAddress(&xn, g_xn); cudaGetSymbolAddress(&o, g_o); cudaGetSymbolAddress(&x1, g_x1);
  cudaGetSymbolAddress(&xm, g_xm); cudaGetSymbolAddress(&x2, g_x2); cudaGetSymbolAddress(&hh, g_h);
  RecMaps R;
  for (int i = 0; i < 3; i++) R.w[i] = make_map(d_in[2 + i], DM, NH * DH, 16);
  R.wo = make_map(Wo, NH * DH, DM, 64); R.x[0] = make_map_x(xn); R.x[1] = make_map_x1(xn);
  rec_kernel<<<96, 512, rec::SMEM>>>(R, Wo, mem0, x, 0);
  GemmMaps G;
  G.o = make_map(o, 2 * SEQ, NH * DH, 128); G.wo = make_map_wo(Wo);
  G.x1 = make_map(x1, 2 * SEQ, DM, 64); G.x1s = make_map(x1, 2 * SEQ, DM, 128);
  G.xn = make_map((bf16*)xn + (NSTEP + LAG) * 32 * DM, SEQ, DM, 64);
  G.xm = make_map(xm, 2 * SEQ, DM, 64); G.xms = make_map(xm, 2 * SEQ, DM, 128);
  G.wg = make_map(d_in[8], DM, DF, 64); G.wu = make_map(d_in[9], DM, DF, 64); G.wd = make_map(d_in[10], DF, DM, 64);
  G.h = make_map(hh, 2 * SEQ, DF, 64); G.hs = make_map(hh, 2 * SEQ, DF, 128);
  G.x = make_map(x, SEQ, DM, 64); G.x2 = make_map(x2, SEQ, DM, 64); G.out = make_map(d_out, SEQ, DM, 64); G.outs = make_map(d_out, SEQ, DM, 128);
  cudaLaunchConfig_t cfg = {};
  cfg.gridDim = dim3(g_sms & ~1); cfg.blockDim = dim3(512); cfg.dynamicSmemBytes = gm::SMEM; cfg.stream = cudaStreamPerThread;
  cudaLaunchAttribute at;
  at.id = cudaLaunchAttributeProgrammaticStreamSerialization; at.val.programmaticStreamSerializationAllowed = 1;
  cfg.attrs = &at; cfg.numAttrs = 1;
  cudaLaunchKernelEx(&cfg, gemm_kernel, G);
}
```

```cpp
#include <cuda_runtime.h>
#include <cuda_bf16.h>
#include <cuda.h>
#include <stdint.h>

#define DEVI __device__ __forceinline__
typedef __nv_bfloat16 bf16;

#define LAG 14
constexpr int SEQ = 2048, DM = 1024, NH = 32, DH = 128, DF = 3584, NSEG = 64, NSTEP = NSEG + LAG;

__device__ __align__(1024) bf16 g_xn[2][NSTEP * 32 * DM];
__device__ __align__(1024) bf16 g_o[2][SEQ * NH * DH];
__device__ __align__(1024) bf16 g_x1[2][SEQ * DM];
__device__ __align__(1024) bf16 g_xm[2][SEQ * DM];
__device__ __align__(1024) bf16 g_x2[SEQ * DM];
__device__ __align__(1024) bf16 g_h[2][SEQ * DF];
__device__ __align__(1024) uint4 g_part[256 * 32 * 8];
__device__ __align__(1024) uint32_t g_ann[2][32][64];
__device__ __align__(1024) uint4 g_mem[2][2048];
__device__ __align__(128) float2 g_stat[12][8][128];
__host__ __device__ constexpr int grp(int type, int layer, int blk) { return layer ? 16 * type + blk : 64 + (16 * type + blk) * 32; }
struct Flags {
  int xn[2][16][32];
  int dep[64 + 48 * 32];
  int taken[64];
  int rows[32];
  int part[32];
  int ticket[32];
};
__device__ __align__(128) Flags g_fl;

DEVI uint32_t smem_u32(const void* p) { return (uint32_t)__cvta_generic_to_shared(p); }
DEVI void mbar_init(uint32_t bar, uint32_t cnt) { asm volatile("mbarrier.init.shared::cta.b64 [%0], %1;" :: "r"(bar), "r"(cnt) : "memory"); }
DEVI void mbar_expect_tx(uint32_t bar, uint32_t bytes) { asm volatile("mbarrier.arrive.expect_tx.shared::cta.b64 _, [%0], %1;" :: "r"(bar), "r"(bytes) : "memory"); }
DEVI void mbar_arrive(uint32_t bar) { asm volatile("mbarrier.arrive.shared::cta.b64 _, [%0];" :: "r"(bar) : "memory"); }
DEVI bool mbar_try(uint32_t bar, uint32_t parity) {
  uint32_t p;
  asm volatile("{.reg .pred p; mbarrier.try_wait.parity.shared::cta.b64 p, [%1], %2; selp.u32 %0, 1, 0, p;}" : "=r"(p) : "r"(bar), "r"(parity) : "memory");
  return p;
}
DEVI bool mbar_test(uint32_t bar, uint32_t parity) {
  uint32_t p;
  asm volatile("{.reg .pred p; mbarrier.test_wait.parity.shared::cta.b64 p, [%1], %2; selp.u32 %0, 1, 0, p;}" : "=r"(p) : "r"(bar), "r"(parity) : "memory");
  return p;
}
constexpr int SPIN_BUDGET = 1 << 20;
DEVI void mbar_wait(uint32_t bar, uint32_t parity, int& budget) {
  while (!mbar_try(bar, parity)) { if (--budget < 0) break; }
}
DEVI void trap_if_spent(int budget) { asm volatile("{.reg .pred p; setp.le.s32 p, %0, 0; @p trap;}" :: "r"(budget) : "memory"); }
DEVI void fault_if_spent(int budget) { asm volatile("{.reg .pred p; setp.le.s32 p, %0, 0; @p st.global.u32 [%1], 0;}" :: "r"(budget), "l"(0ull) : "memory"); }
DEVI uint32_t mapa(uint32_t addr, uint32_t rank) { uint32_t r; asm("mapa.shared::cluster.u32 %0, %1, %2;" : "=r"(r) : "r"(addr), "r"(rank)); return r; }
DEVI void cluster_arrive() { asm volatile("barrier.cluster.arrive.release.aligned;" ::: "memory"); }
DEVI void cluster_wait() { asm volatile("barrier.cluster.wait.acquire.aligned;" ::: "memory"); }
DEVI void fence_mbar_init() { asm volatile("fence.mbarrier_init.release.cluster;" ::: "memory"); }
DEVI void fence_proxy_async() { asm volatile("fence.proxy.async.shared::cta;" ::: "memory"); }
DEVI void tma_load_2d(uint32_t dst, const CUtensorMap* m, int c0, int c1, uint32_t bar) {
  asm volatile("cp.async.bulk.tensor.2d.shared::cluster.global.mbarrier::complete_tx::bytes [%0], [%1, {%3, %4}], [%2];"
    :: "r"(dst), "l"(m), "r"(bar), "r"(c0), "r"(c1) : "memory");
}
DEVI void tma_load_5d(uint32_t dst, const CUtensorMap* m, int c0, int c4, uint32_t bar) {
  asm volatile("cp.async.bulk.tensor.5d.shared::cluster.global.mbarrier::complete_tx::bytes [%0], [%1, {%3, %5, %5, %5, %4}], [%2];"
    :: "r"(dst), "l"(m), "r"(bar), "r"(c0), "r"(c4), "r"(0) : "memory");
}
DEVI void tma_prefetch_2d(const CUtensorMap* m, int c0, int c1) {
  asm volatile("cp.async.bulk.prefetch.tensor.2d.L2.global [%0, {%1, %2}];" :: "l"(m), "r"(c0), "r"(c1) : "memory");
}
DEVI void tma_prefetch_5d(const CUtensorMap* m, int c0, int c4) {
  asm volatile("cp.async.bulk.prefetch.tensor.5d.L2.global [%0, {%1, %3, %3, %3, %2}];" :: "l"(m), "r"(c0), "r"(c4), "r"(0) : "memory");
}
#define ELECT "{.reg .pred p; elect.sync _|p, 0xffffffff;\n @p "
DEVI void e_expect_tx(uint32_t bar, uint32_t bytes) { asm volatile(ELECT "mbarrier.arrive.expect_tx.shared::cta.b64 _, [%0], %1;}" :: "r"(bar), "r"(bytes) : "memory"); }
DEVI void e_arrive(uint32_t bar) { asm volatile(ELECT "mbarrier.arrive.shared::cta.b64 _, [%0];}" :: "r"(bar) : "memory"); }
DEVI void e_arrive_cl(uint32_t bar) { asm volatile(ELECT "mbarrier.arrive.shared::cluster.b64 _, [%0];}" :: "r"(bar) : "memory"); }
constexpr uint64_t EVICT_NORMAL = 0x1000000000000000ull, EVICT_FIRST = 0x12F0000000000000ull;
DEVI void e_tma_2d(uint32_t dst, const CUtensorMap* m, int c0, int c1, uint32_t bar, uint64_t pol = EVICT_NORMAL) {
  asm volatile(ELECT "cp.async.bulk.tensor.2d.shared::cluster.global.mbarrier::complete_tx::bytes.L2::cache_hint [%0], [%1, {%3, %4}], [%2], %5;}"
    :: "r"(dst), "l"(m), "r"(bar), "r"(c0), "r"(c1), "l"(pol) : "memory");
}
DEVI void e_tma_2d_mc(uint32_t dst, const CUtensorMap* m, int c0, int c1, uint32_t bar, uint64_t pol = EVICT_NORMAL) {
  asm volatile(ELECT "cp.async.bulk.tensor.2d.shared::cluster.global.mbarrier::complete_tx::bytes.multicast::cluster.L2::cache_hint [%0], [%1, {%3, %4}], [%2], %5, %6;}"
    :: "r"(dst), "l"(m), "r"(bar), "r"(c0), "r"(c1), "h"((unsigned short)3), "l"(pol) : "memory");
}
DEVI void e_st_async32(uint32_t a, uint32_t x, uint32_t bar) {
  asm volatile(ELECT "st.async.weak.shared::cluster.mbarrier::complete_tx::bytes.b32 [%0], %1, [%2];}" :: "r"(a), "r"(x), "r"(bar) : "memory");
}
DEVI void e_tma_store_2d(const CUtensorMap* m, uint32_t src, int c0, int c1) {
  asm volatile(ELECT "cp.async.bulk.tensor.2d.global.shared::cta.bulk_group [%0, {%2, %3}], [%1];}" :: "l"(m), "r"(src), "r"(c0), "r"(c1) : "memory");
}
DEVI void e_flag_add(int* p, int v = 1) {
  asm volatile("{.reg .pred p; elect.sync _|p, 0xffffffff;\n fence.proxy.async.global; @p red.release.gpu.global.add.s32 [%0], %1;}" :: "l"(p), "r"(v) : "memory");
}
DEVI void e_flag_add_bulk(int* p, int v) {
  asm volatile(ELECT "red.relaxed.gpu.global.add.s32 [%0], %1;}" :: "l"(p), "r"(v) : "memory");
}
DEVI int e_ticket(int* p) { int v = 0; asm volatile(ELECT "atom.relaxed.gpu.global.add.s32 %0, [%1], 1;}" : "+r"(v) : "l"(p) : "memory"); __syncwarp(); return v; }
DEVI int bcast(int v) { return __reduce_max_sync(0xffffffffu, v); }
DEVI int ld_relaxed(const int* p) { int v; asm volatile("ld.relaxed.gpu.global.s32 %0, [%1];" : "=r"(v) : "l"(p) : "memory"); return v; }
DEVI int ld_acquire(const int* p) { int v; asm volatile("ld.acquire.gpu.global.s32 %0, [%1];" : "=r"(v) : "l"(p) : "memory"); return __shfl_sync(0xffffffffu, v, 0); }
DEVI void e_tma_3d(uint32_t dst, const CUtensorMap* m, int c0, int c1, int c2, uint32_t bar) {
  asm volatile(ELECT "cp.async.bulk.tensor.3d.shared::cluster.global.mbarrier::complete_tx::bytes [%0], [%1, {%3, %4, %5}], [%2];}"
    :: "r"(dst), "l"(m), "r"(bar), "r"(c0), "r"(c1), "r"(c2) : "memory");
}
DEVI void e_tma_5d(uint32_t dst, const CUtensorMap* m, int c0, int c4, uint32_t bar) {
  asm volatile(ELECT "cp.async.bulk.tensor.5d.shared::cluster.global.mbarrier::complete_tx::bytes [%0], [%1, {%3, %5, %5, %5, %4}], [%2];}"
    :: "r"(dst), "l"(m), "r"(bar), "r"(c0), "r"(c4), "r"(0) : "memory");
}
DEVI void e_bulk_g2s(uint32_t dst, const void* src, uint32_t bytes, uint32_t bar) {
  asm volatile(ELECT "cp.async.bulk.shared::cluster.global.mbarrier::complete_tx::bytes [%0], [%1], %2, [%3];}" :: "r"(dst), "l"(src), "r"(bytes), "r"(bar) : "memory");
}
DEVI void e_prefetch(const void* src, uint32_t bytes) {
  asm volatile(ELECT "cp.async.bulk.prefetch.L2.global [%0], %1;}" :: "l"(src), "r"(bytes) : "memory");
}
DEVI void bulk_commit() { asm volatile("cp.async.bulk.commit_group;" ::: "memory"); }
template<int N> DEVI void bulk_wait_read() { asm volatile("cp.async.bulk.wait_group.read %0;" :: "n"(N) : "memory"); }
template<int N> DEVI void bulk_wait() { asm volatile("cp.async.bulk.wait_group %0;" :: "n"(N) : "memory"); }
template<int ID, int N> DEVI void nbar_sync() { asm volatile("bar.sync %0, %1;" :: "n"(ID), "n"(N) : "memory"); }
template<int ID, int N> DEVI void nbar_arrive() { asm volatile("bar.arrive %0, %1;" :: "n"(ID), "n"(N) : "memory"); }
DEVI void nbar_sync_r(int id, int n) { asm volatile("bar.sync %0, %1;" :: "r"(id), "r"(n) : "memory"); }
DEVI void nbar_arrive_r(int id, int n) { asm volatile("bar.arrive %0, %1;" :: "r"(id), "r"(n) : "memory"); }
template<int R> DEVI void reg_inc() { asm volatile("setmaxnreg.inc.sync.aligned.u32 %0;" :: "n"(R)); }
template<int R> DEVI void reg_dec() { asm volatile("setmaxnreg.dec.sync.aligned.u32 %0;" :: "n"(R)); }
DEVI void wg_fence() { asm volatile("wgmma.fence.sync.aligned;" ::: "memory"); }
DEVI void wg_commit() { asm volatile("wgmma.commit_group.sync.aligned;" ::: "memory"); }
template<int N> DEVI void wg_wait() { asm volatile("wgmma.wait_group.sync.aligned %0;" :: "n"(N) : "memory"); }
DEVI uint32_t pack_bf16(float lo, float hi) { uint32_t r; asm("cvt.rn.bf16x2.f32 %0, %1, %2;" : "=r"(r) : "f"(hi), "f"(lo)); return r; }
DEVI float bf_lo(uint32_t v) { return __uint_as_float(v << 16); }
DEVI float bf_hi(uint32_t v) { return __uint_as_float(v & 0xffff0000u); }
DEVI uint32_t movmat(uint32_t a) { uint32_t r; asm volatile("movmatrix.sync.aligned.m8n8.trans.b16 %0, %1;" : "=r"(r) : "r"(a)); return r; }
DEVI void ldsm4(uint32_t addr, uint32_t& r0, uint32_t& r1, uint32_t& r2, uint32_t& r3) {
  asm volatile("ldmatrix.sync.aligned.m8n8.x4.shared.b16 {%0,%1,%2,%3}, [%4];" : "=r"(r0), "=r"(r1), "=r"(r2), "=r"(r3) : "r"(addr) : "memory");
}
DEVI void ldsm4t(uint32_t addr, uint32_t& r0, uint32_t& r1, uint32_t& r2, uint32_t& r3) {
  asm volatile("ldmatrix.sync.aligned.m8n8.x4.trans.shared.b16 {%0,%1,%2,%3}, [%4];" : "=r"(r0), "=r"(r1), "=r"(r2), "=r"(r3) : "r"(addr) : "memory");
}
DEVI void stsm4(uint32_t addr, uint32_t r0, uint32_t r1, uint32_t r2, uint32_t r3) {
  asm volatile("stmatrix.sync.aligned.m8n8.x4.shared.b16 [%0], {%1,%2,%3,%4};" :: "r"(addr), "r"(r0), "r"(r1), "r"(r2), "r"(r3) : "memory");
}
DEVI uint4 lds128(uint32_t a) { uint4 v; asm volatile("ld.shared.v4.u32 {%0,%1,%2,%3}, [%4];" : "=r"(v.x), "=r"(v.y), "=r"(v.z), "=r"(v.w) : "r"(a) : "memory"); return v; }
DEVI uint32_t lds32v(uint32_t a) { uint32_t v; asm volatile("ld.volatile.shared.u32 %0, [%1];" : "=r"(v) : "r"(a) : "memory"); return v; }
DEVI void sts32v(uint32_t a, uint32_t v) { asm volatile("st.volatile.shared.u32 [%0], %1;" :: "r"(a), "r"(v) : "memory"); }
DEVI void st_async128(uint32_t a, uint32_t x, uint32_t y, uint32_t z, uint32_t w, uint32_t bar) {
  asm volatile("st.async.weak.shared::cluster.mbarrier::complete_tx::bytes.v4.b32 [%0], {%1,%2,%3,%4}, [%5];" :: "r"(a), "r"(x), "r"(y), "r"(z), "r"(w), "r"(bar) : "memory");
}
DEVI void st_async32(uint32_t a, uint32_t x, uint32_t bar) {
  asm volatile("st.async.weak.shared::cluster.mbarrier::complete_tx::bytes.b32 [%0], %1, [%2];" :: "r"(a), "r"(x), "r"(bar) : "memory");
}
DEVI void st_cl128(bool own, uint32_t a, uint32_t x, uint32_t y, uint32_t z, uint32_t w, uint32_t bar) {
  asm volatile("{.reg .pred p; setp.ne.u32 p, %6, 0; @p st.shared.v4.b32 [%0], {%1,%2,%3,%4};\n"
               "@!p st.async.weak.shared::cluster.mbarrier::complete_tx::bytes.v4.b32 [%0], {%1,%2,%3,%4}, [%5];}"
               :: "r"(a), "r"(x), "r"(y), "r"(z), "r"(w), "r"(bar), "r"((uint32_t)own) : "memory");
}
DEVI void st_cl32(bool own, uint32_t a, uint32_t x, uint32_t bar) {
  asm volatile("{.reg .pred p; setp.ne.u32 p, %3, 0; @p st.shared.b32 [%0], %1;\n"
               "@!p st.async.weak.shared::cluster.mbarrier::complete_tx::bytes.b32 [%0], %1, [%2];}" :: "r"(a), "r"(x), "r"(bar), "r"((uint32_t)own) : "memory");
}
DEVI uint4 ldg_rlx128(const void* p) {
  uint4 v;
  asm volatile("ld.relaxed.gpu.global.v4.b32 {%0,%1,%2,%3}, [%4];" : "=r"(v.x), "=r"(v.y), "=r"(v.z), "=r"(v.w) : "l"(p) : "memory");
  return v;
}
DEVI void stg_rlx128(void* p, uint32_t x, uint32_t y, uint32_t z, uint32_t w) {
  asm volatile("st.relaxed.gpu.global.v4.b32 [%0], {%1,%2,%3,%4};" :: "l"(p), "r"(x), "r"(y), "r"(z), "r"(w) : "memory");
}
DEVI void stg128(void* p, uint32_t x, uint32_t y, uint32_t z, uint32_t w) {
  asm volatile("st.global.v4.b32 [%0], {%1,%2,%3,%4};" :: "l"(p), "r"(x), "r"(y), "r"(z), "r"(w) : "memory");
}
DEVI void stg_rlx64(void* p, uint32_t x, uint32_t y) { asm volatile("st.relaxed.gpu.global.v2.b32 [%0], {%1,%2};" :: "l"(p), "r"(x), "r"(y) : "memory"); }
DEVI void stg_rlx32(void* p, uint32_t x) { asm volatile("st.relaxed.gpu.global.b32 [%0], %1;" :: "l"(p), "r"(x) : "memory"); }
DEVI uint32_t clock32() { uint32_t c; asm volatile("mov.u32 %0, %%clock;" : "=r"(c) :: "memory"); return c; }
DEVI uint32_t gtime() { uint32_t c; asm volatile("mov.u32 %0, %%globaltimer_lo;" : "=r"(c) :: "memory"); return c; }
DEVI void wait_time(uint32_t t, int& budget) { while ((int)(gtime() - t) < 0 && --budget > 0) {} }
DEVI uint2 ldg_rlx64(const void* p) { uint2 v; asm volatile("ld.relaxed.gpu.global.v2.b32 {%0,%1}, [%2];" : "=r"(v.x), "=r"(v.y) : "l"(p) : "memory"); return v; }
DEVI void sts16(uint32_t a, uint32_t x) { asm volatile("st.shared.b16 [%0], %1;" :: "r"(a), "h"((unsigned short)x) : "memory"); }
DEVI void sts128(uint32_t a, uint32_t x) { asm volatile("st.shared.v4.b32 [%0], {%1,%1,%1,%1};" :: "r"(a), "r"(x) : "memory"); }
DEVI void arrive_if_eq(uint32_t bar, int a, int b) { asm volatile("{.reg .pred p; setp.eq.s32 p, %1, %2; @p mbarrier.arrive.shared::cta.b64 _, [%0];}" :: "r"(bar), "r"(a), "r"(b) : "memory"); }
DEVI void arrive_cl_if_eq(uint32_t bar, int a, int b) { asm volatile("{.reg .pred p; setp.eq.s32 p, %1, %2; @p mbarrier.arrive.shared::cluster.b64 _, [%0];}" :: "r"(bar), "r"(a), "r"(b) : "memory"); }
template<int ID, int N> DEVI bool nbar_or(bool x) {
  uint32_t r;
  asm volatile("{.reg .pred p, q; setp.ne.u32 p, %1, 0; bar.red.or.pred q, %2, %3, p; selp.u32 %0, 1, 0, q;}" : "=r"(r) : "r"((uint32_t)x), "n"(ID), "n"(N) : "memory");
  return __any_sync(0xffffffffu, r);
}
DEVI void spin_until(uint32_t t0, int d) { while ((int)(clock32() - t0) < d) {} }
DEVI void flag_wait(const int* p, int n, int& budget) {
  while (ld_acquire(p) < n && --budget > 0) __nanosleep(128);
  asm volatile("fence.proxy.async.global;" ::: "memory");
}

#define F4(C, o)  C(d[o+0]), C(d[o+1]), C(d[o+2]), C(d[o+3])
#define F8(C, o)  F4(C, o), F4(C, o+4)
#define F32(C, o) F8(C, o), F8(C, o+8), F8(C, o+16), F8(C, o+24)
#define R4  "{%0,%1,%2,%3}"
#define R8  "{%0,%1,%2,%3,%4,%5,%6,%7}"
#define R16 "{%0,%1,%2,%3,%4,%5,%6,%7,%8,%9,%10,%11,%12,%13,%14,%15}"
#define R20 "{%0,%1,%2,%3,%4,%5,%6,%7,%8,%9,%10,%11,%12,%13,%14,%15,%16,%17,%18,%19}"
#define R32 "{%0,%1,%2,%3,%4,%5,%6,%7,%8,%9,%10,%11,%12,%13,%14,%15,%16,%17,%18,%19,%20,%21,%22,%23,%24,%25,%26,%27,%28,%29,%30,%31}"
#define R64 "{%0,%1,%2,%3,%4,%5,%6,%7,%8,%9,%10,%11,%12,%13,%14,%15,%16,%17,%18,%19,%20,%21,%22,%23,%24,%25,%26,%27,%28,%29,%30,%31," \
  "%32,%33,%34,%35,%36,%37,%38,%39,%40,%41,%42,%43,%44,%45,%46,%47,%48,%49,%50,%51,%52,%53,%54,%55,%56,%57,%58,%59,%60,%61,%62,%63}"
template<uint32_t OFF, uint32_t LBO, uint32_t SBO, uint32_t SW, int T> struct Op {
  static constexpr uint32_t lo = (OFF >> 4) | ((LBO >> 4) << 16), hi = (SBO >> 4) | (SW << 30);
  static constexpr int t = T;
};
DEVI uint32_t desc_base(uint32_t addr) { return (addr & 0x3FFFF) >> 4; }
#define RS_ASM(SHAPE, REGS, A0, A1, A2, A3, B, LO, HI, T, SD) \
  "{.reg .b64 tb; .reg .b32 lb; add.u32 lb, " B ", " LO "; mov.b64 tb, {lb, " HI "};\n" \
  "wgmma.mma_async.sync.aligned." SHAPE ".f32.bf16.bf16 " REGS ", {" A0 "," A1 "," A2 "," A3 "}, tb, " SD ", 1, 1, " T ";}"
#define WG_RS(NAME, SHAPE, REGS, LIST, ...) \
  template<int ACC, class OB> DEVI void NAME(float* d, const uint32_t* a, uint32_t b) { \
    if (ACC) asm volatile(RS_ASM(SHAPE, REGS, __VA_ARGS__) \
      : LIST("+f") : "r"(a[0]), "r"(a[1]), "r"(a[2]), "r"(a[3]), "r"(b), "n"(OB::lo), "n"(OB::hi), "n"(OB::t), "n"(ACC & 1)); \
    else asm volatile(RS_ASM(SHAPE, REGS, __VA_ARGS__) \
      : LIST("=f") : "r"(a[0]), "r"(a[1]), "r"(a[2]), "r"(a[3]), "r"(b), "n"(OB::lo), "n"(OB::hi), "n"(OB::t), "n"(0)); \
  }
#define SS_ASM(SHAPE, REGS, A, B, LA, HA, TA, LB, HB, TB, SD) \
  "{.reg .b64 ta, tb; .reg .b32 la, lb; add.u32 la, " A ", " LA "; mov.b64 ta, {la, " HA "}; add.u32 lb, " B ", " LB "; mov.b64 tb, {lb, " HB "};\n" \
  "wgmma.mma_async.sync.aligned." SHAPE ".f32.bf16.bf16 " REGS ", ta, tb, " SD ", 1, 1, " TA ", " TB ";}"
#define WG_SS(NAME, SHAPE, REGS, LIST, ...) \
  template<int ACC, class OA, class OB> DEVI void NAME(float* d, uint32_t a, uint32_t b) { \
    if (ACC) asm volatile(SS_ASM(SHAPE, REGS, __VA_ARGS__) \
      : LIST("+f") : "r"(a), "r"(b), "n"(OA::lo), "n"(OA::hi), "n"(OA::t), "n"(OB::lo), "n"(OB::hi), "n"(OB::t), "n"(ACC & 1)); \
    else asm volatile(SS_ASM(SHAPE, REGS, __VA_ARGS__) \
      : LIST("=f") : "r"(a), "r"(b), "n"(OA::lo), "n"(OA::hi), "n"(OA::t), "n"(OB::lo), "n"(OB::hi), "n"(OB::t), "n"(0)); \
  }
#define L4(C)  F4(C, 0)
#define L8(C)  F8(C, 0)
#define L16(C) F8(C, 0), F8(C, 8)
#define L20(C) F8(C, 0), F8(C, 8), F4(C, 16)
#define L32(C) F32(C, 0)
WG_RS(wg_rs8, "m64n8k16", R4, L4, "%4", "%5", "%6", "%7", "%8", "%9", "%10", "%11", "%12")
WG_RS(wg_rs16, "m64n16k16", R8, L8, "%8", "%9", "%10", "%11", "%12", "%13", "%14", "%15", "%16")
WG_RS(wg_rs32, "m64n32k16", R16, L16, "%16", "%17", "%18", "%19", "%20", "%21", "%22", "%23", "%24")
WG_SS(wg_ss32, "m64n32k16", R16, L16, "%16", "%17", "%18", "%19", "%20", "%21", "%22", "%23", "%24")
WG_RS(wg_rs64, "m64n64k16", R32, L32, "%32", "%33", "%34", "%35", "%36", "%37", "%38", "%39", "%40")
WG_SS(wg_ss8, "m64n8k16", R4, L4, "%4", "%5", "%6", "%7", "%8", "%9", "%10", "%11", "%12")
WG_SS(wg_ss16, "m64n16k16", R8, L8, "%8", "%9", "%10", "%11", "%12", "%13", "%14", "%15", "%16")
WG_SS(wg_ss40, "m64n40k16", R20, L20, "%20", "%21", "%22", "%23", "%24", "%25", "%26", "%27", "%28")
WG_SS(wg_ss64, "m64n64k16", R32, L32, "%32", "%33", "%34", "%35", "%36", "%37", "%38", "%39", "%40")
#define L64(C) F32(C, 0), F32(C, 32)
WG_SS(wg_ss128, "m64n128k16", R64, L64, "%64", "%65", "%66", "%67", "%68", "%69", "%70", "%71", "%72")
template<int I> struct IC { __host__ __device__ constexpr operator int() const { return I; } };
template<int I, int N, class F> DEVI void sfor(F&& f) {
  if constexpr (I < N) { f(IC<I>{}); sfor<I + 1, N>(f); }
}

#define R_CL 6
namespace rec {
constexpr int NHI = 36, NLO = 5, NRS = NHI + NLO, NSS = 64 - NRS;
constexpr uint32_t WS = 0;
constexpr uint32_t WO = 2 * NSS * 2048;
constexpr uint32_t RING = WO + 65536;
constexpr uint32_t QB = RING + 40960, RG = 2080, POSQ = 0x64210, POSK = 0xB9753, POSV = 0xEDCA8;
#define JA 2
constexpr uint32_t WA = QB;
constexpr uint32_t OM = QB + 9 * RG, OMS = 2 * RG;
constexpr uint32_t OM2 = QB + 16384, OM2S = 2048;
constexpr uint32_t WH = QB + 20480;
constexpr uint32_t B_PART = QB + 15 * RG - 32;
constexpr uint32_t PM0 = QB + 16384, PM1 = QB + 15 * RG, PM2 = PM1 + 256;
constexpr uint32_t BARS = PM2 + 128;
constexpr uint32_t B_FULL = BARS, B_EMPTY = BARS + 40, B_MLAND = BARS + 80, B_QK = BARS + 112, B_V = BARS + 120, B_OM = BARS + 128,
                   B_WA = BARS + 136, B_SDONE = BARS + 144, B_BFREE = BARS + 152, B_W1 = PM1, B_W2 = PM1 + 8, B_WO = PM1 + 16;
constexpr uint32_t SMEM = BARS + 160;
static_assert(SMEM <= 232448 && QB % 1024 == 0, "smem map");
constexpr int R1 = (PM1 - WO) / 4096;
constexpr int NB_WO = 1, NB_ST = 2, NB_P = 3, NB_TR = 4, NB_X = 5, NB_G = 6, NB_G1 = 7, NB_G2 = 8, NB_G4 = 9, NB_S = 10;
__host__ __device__ constexpr bool is_lo(int j) { return j % 12 == 8; }
__host__ __device__ constexpr int lo_before(int j) { return (j + 3) / 12; }
__host__ __device__ constexpr int ss_before(int j) { return (j - lo_before(j)) * NSS / (64 - NLO); }
__host__ __device__ constexpr bool is_ss(int j) { return ss_before(j + 1) != ss_before(j); }
__host__ __device__ constexpr int reg_idx(int j) { return is_lo(j) ? NHI + lo_before(j) : j - ss_before(j) - lo_before(j); }
#define LOQ(i) ((0x12010 >> (4 * (i))) & 3)
template<int j> using OpW = Op<WS + ss_before(j) * 2048, 16, 1024, 1, 1>;
#define P_G1 1
#define P_G2 3
#define P_G2L 0
#define P_OS 1
#define P_NA 6
#define P_G4 10
#define P_G5 12
#define P_FW 0
#define P_SEND 0xff3f2f10u
#define P_WB 2
#define P_WOL 0
#define P_G4L 0
#define P_S1 1
#define P_S2 2
#define P_S0 3
#define P_MB 0
#define P_S4 5
#define P_S5 6
constexpr uint32_t SLOT1 = 0x32410324, USE1 = 0x22111110;
DEVI bool single(int s) { return s < LAG - 1 || s >= NSEG - 1; }
DEVI uint32_t flip(int s) { return (s < LAG - 1 ? s + 1 : s < NSEG - 1 ? LAG : LAG + s + 1) & 1; }
#define TUN(i, v) (v)
}
#define PROFW(wq, i)
DEVI uint32_t mapr(int h, uint32_t addr, int rank) { return mapa(addr, rank + (R_CL == 6 ? (h & 1) * 3 : 0)); }
template<int N> DEVI void pin(float* d) {
#pragma unroll
  for (int i = 0; i < N; i++) asm volatile("" : "+f"(d[i]) :: "memory");
}
DEVI void keep(const void* a) { asm volatile("{.reg .pred p; setp.eq.u64 p, %0, 0; vote.sync.any.pred p, p, 0xffffffff; @p exit;}" :: "l"(a) : "memory"); }
DEVI int lane_reg() { return __shfl_sync(0xffffffffu, threadIdx.x & 31, threadIdx.x & 31); }
#define LANE_NOW [[maybe_unused]] const int lane = lane0 + ((uint32_t)budget >> 30), g = lane >> 2, c = lane & 3

DEVI void rec_proj(const uint32_t sb, const int h, const int rank, const int w, const CUtensorMap* mW, const CUtensorMap* mWo, const uint32_t zero) {
  using namespace rec;
  const int lane0 = lane_reg(), wg = w >> 2, ww = w & 3;
  int budget = SPIN_BUDGET;
  uint32_t wr[NRS * 4];
  {
    LANE_NOW;
    const uint32_t wsw = ((lane & 7) + (lane >> 4) * 8) * 128 + (((ww * 2 + ((lane >> 3) & 1)) ^ (lane & 7)) << 4);
    mbar_wait(sb + B_W1, 0, budget);
#pragma unroll
    for (int r = 0; r < R1; r++) ldsm4t(sb + WO + (wg * R1 + r) * 2048 + wsw, wr[4*r], wr[4*r+1], wr[4*r+2], wr[4*r+3]);
    fence_proxy_async();
    nbar_sync<NB_ST, 256>();
    if (w == 0) {
      if (lane == 0) { mbar_expect_tx(sb + B_W2, (NRS - R1) * 4096); mbar_expect_tx(sb + B_WO, rank == 2 ? 65536 + 16384 + 8192 : 65536); }
      __syncwarp();
      for (int i = lane; i < 128; i += 32) {
        const int j = i & 63, t = i >> 6, r = reg_idx(j);
        if (!is_ss(j) && r >= R1) tma_load_2d(sb + RING + (t * (NRS - R1) + r - R1) * 2048, mW, h * DH + t * 64, j * 16, sb + B_W2);
      }
      const int t0 = (rank + 1) % 3;
      if (lane < 8) tma_load_2d(sb + WO + lane * 8192, mWo, (3 * ((lane >> 1) + (lane >> 1 >= JA)) + t0) * 64, h * DH + (lane & 1) * 64, sb + B_WO);
      else if (rank < 2 && lane < 10) tma_prefetch_2d(mWo, (3 * JA + t0) * 64, h * DH + (lane & 1) * 64);
      else if (rank == 2 && lane < 11) tma_load_2d(lane < 10 ? sb + WA + (lane - 8) * 8192 : sb + WH, mWo, lane < 10 ? 3 * JA * 64 : 15 * 64, h * DH + (lane > 8) * 64, sb + B_WO);
    }
    mbar_wait(sb + B_W2, 0, budget);
#pragma unroll
    for (int r = R1; r < NRS; r++) ldsm4t(sb + RING + (wg * (NRS - R1) + r - R1) * 2048 + wsw, wr[4*r], wr[4*r+1], wr[4*r+2], wr[4*r+3]);
    fence_proxy_async();
    cluster_arrive(); cluster_wait();
  }
  const uint32_t d0 = desc_base(sb), da = d0 + wg * (NSS * 128);
  const uint32_t pos = rank == 0 ? POSQ : rank == 1 ? POSK : POSV, bar = rank == 2 ? B_V : B_QK;
  uint32_t stg[3][4] = {}, pk[16] = {};
  auto stage = [&](uint32_t* t, int r) {
#pragma unroll
    for (int i = 0; i < 4; i++) asm volatile("xor.b32 %0, %1, %2;" : "+r"(t[i]) : "r"(wr[4 * r + i]), "r"(zero));
  };
#pragma unroll 1
  for (int s = -1; s < NSTEP; s++) {
    const uint32_t fl = flip(s);
    if (s >= 0) {
      float d[8];
      stage(stg[0], NHI);
      mbar_wait(sb + B_FULL, 0, budget);
      PROFW(0, 16);
      sfor<0, 8>([&](auto E) {
        constexpr int e = E, q = e >> 1;
        wg_fence();
        sfor<8 * e, 8 * e + 8>([&](auto J) {
          constexpr int j = J;
          typedef Op<RING + j * 512, 256, 128, 0, 1> OB;
          if constexpr (is_ss(j)) wg_ss16<j != 0, OpW<j>, OB>(d, da, d0);
          else wg_rs16<j != 0, OB>(d, is_lo(j) ? stg[LOQ(lo_before(j))] : wr + 4 * reg_idx(j), d0);
        });
        wg_commit();
        if constexpr (e == 0) { if (s > 0) mbar_wait(sb + B_BFREE, (s & 1) ^ 1, budget); }
        if constexpr (e > 0 && !(e & 1)) {
          wg_wait<1>();
          arrive_if_eq(sb + B_EMPTY + 8 * (q - 1), lane0, ww * 32);
        }
        if constexpr (e < 6 && !(e & 1)) sfor<lo_before(16 * q + 16), lo_before(16 * q + 32)>([&](auto I) { constexpr int i = I; stage(stg[LOQ(i)], NHI + i); });
        if constexpr (e < 6 && (e & 1) == P_FW) mbar_wait(sb + B_FULL + 8 * (q + 1), q ? fl : 0, budget);
        if constexpr (((P_SEND >> (4 * e)) & 15) < 4) {
          constexpr int n = (P_SEND >> (4 * e)) & 15;
          LANE_NOW;
          const uint32_t r = mapr(h, sb, n >> 1);
          uint32_t t[4];
#pragma unroll
          for (int i = 0; i < 4; i++) { if (n == 0) t[i] = pk[i]; else asm volatile("xor.b32 %0, %1, %2;" : "=r"(t[i]) : "r"(pk[4*n+i]), "r"(zero)); }
          st_cl128(rank == n >> 1, r + QB + ((pos >> (4 + 4 * c)) & 15) * RG + w * 256 + (n & 1) * 128 + g * 16, t[0], t[1], t[2], t[3], r + bar);
        }
      });
      LANE_NOW;
      const uint32_t dst = QB + (pos & 15) * RG + w * 256 + lane * 4;
      wg_wait<0>();
      pin<8>(d);
      {
        const uint32_t x0 = pack_bf16(d[0], d[1]), x1 = pack_bf16(d[2], d[3]), y0 = pack_bf16(d[4], d[5]), y1 = pack_bf16(d[6], d[7]);
        const uint32_t r = mapr(h, sb, rank == 0);
        if (rank < 2) { sts32v(sb + dst, rank ? y0 : x0); sts32v(sb + dst + 128, rank ? y1 : x1); fence_proxy_async(); }
        st_async32(r + dst, rank ? x0 : y0, r + bar); st_async32(r + dst + 128, rank ? x1 : y1, r + bar);
        if (rank < 2) e_arrive(sb + B_QK);
        else { const uint32_t r1 = mapr(h, sb, 1); st_async32(r1 + dst, y0, r1 + bar); st_async32(r1 + dst + 128, y1, r1 + bar); }
      }
      PROFW(0, 17);
      if (s == NSTEP - 1) break;
      arrive_if_eq(sb + B_EMPTY + 24, lane0, ww * 32);
    } else e_arrive(sb + B_EMPTY + 8 * ww);
    const bool gate = rank < 2 && s >= 0;
    if (single(s)) {
      float d[16];
      sfor<0, 8>([&](auto C) {
        constexpr int cc = C, sl = (SLOT1 >> (4 * cc)) & 15;
        if constexpr (cc == 0) mbar_wait(sb + B_FULL + 8 * sl, 0, budget);
        if constexpr (cc == P_S1) { if (gate) nbar_sync<NB_G1, 384>(); }
        if constexpr (cc == P_S2) { if (gate) nbar_sync<NB_G2, 384>(); }
        if constexpr (cc == P_S0) nbar_sync<NB_WO, 384>();
        if constexpr (cc == P_S4 || cc == P_S5) { if (gate && cc == (rank ? P_S5 : P_S4)) nbar_sync<NB_G4, 384>(); }
        if constexpr (lo_before(cc * 8 + 8) != lo_before(cc * 8)) stage(stg[0], NHI + lo_before(cc * 8));
        wg_fence();
        sfor<0, 8>([&](auto I) {
          constexpr int i = I, j = cc * 8 + i;
          typedef Op<RING + sl * 8192 + (i >> 2) * 4096 + (i & 3) * 32, 16, 1024, 1, 0> OB;
          if constexpr (is_ss(j)) wg_ss32<j != 0, OpW<j>, OB>(d, da, d0);
          else wg_rs32<j != 0, OB>(d, is_lo(j) ? stg[0] : wr + 4 * reg_idx(j), d0);
        });
        wg_commit();
        if constexpr (cc < 7) {
          constexpr int sn = (SLOT1 >> (4 * cc + 4)) & 15;
          mbar_wait(sb + B_FULL + 8 * sn, ((USE1 >> (4 * cc + 4)) & 1) ^ (sn >> 1 == 1 ? fl : 0), budget);
        }
        wg_wait<0>();
        arrive_if_eq(sb + B_EMPTY + 8 * sl, lane0, ww * 32);
      });
      pin<16>(d);
      PROFW(0, 20);
#pragma unroll
      for (int i = 0; i < 8; i++) pk[i] = pk[8 + i] = pack_bf16(d[4 * (i & 3) + ((i >> 1) & 2)], d[4 * (i & 3) + ((i >> 1) & 2) + 1]);
      continue;
    }
    float d[32];
    sfor<0, 16>([&](auto C) {
      constexpr int cc = C, sl = (cc + 4) % 5;
      if constexpr (cc == 0) mbar_wait(sb + B_FULL + 8 * sl, 0, budget);
      if constexpr (cc == P_G1) { if (gate) nbar_sync<NB_G1, 384>(); }
      if constexpr (cc == P_G2) { if (gate) nbar_sync<NB_G2, 384>(); }
      if constexpr (cc == P_NA) {
        PROFW(0, 18);
        nbar_sync<NB_WO, 384>();
      }
      if constexpr (cc == P_G4 || cc == P_G5) { if (gate && cc == (rank ? P_G5 : P_G4)) nbar_sync<NB_G4, 384>(); }
      wg_fence();
      sfor<0, 4>([&](auto I) {
        constexpr int i = I, j = cc * 4 + i;
        typedef Op<RING + sl * 8192 + i * 32, 16, 1024, 1, 0> OB;
        if constexpr (is_ss(j)) wg_ss64<j != 0, OpW<j>, OB>(d, da, d0);
        else wg_rs64<j != 0, OB>(d, is_lo(j) ? stg[0] : wr + 4 * reg_idx(j), d0);
      });
      wg_commit();
      if constexpr (cc == P_NA) PROFW(0, 19);
      if constexpr (cc < 15) {
        if constexpr (is_lo(cc * 4 + 4)) stage(stg[0], reg_idx(cc * 4 + 4));
        mbar_wait(sb + B_FULL + 8 * ((sl + 1) % 5), ((cc + 5) / 5 + (sl == 1 || sl == 2 ? LAG : 0)) & 1, budget);
      }
      wg_wait<0>();
      arrive_if_eq(sb + B_EMPTY + 8 * sl, lane0, ww * 32);
    });
    pin<32>(d);
    PROFW(0, 20);
#pragma unroll
    for (int i = 0; i < 16; i++) pk[i] = pack_bf16(d[16 * (i >> 3) + 4 * (i & 3) + ((i >> 1) & 2)], d[16 * (i >> 3) + 4 * (i & 3) + ((i >> 1) & 2) + 1]);
  }
}

DEVI float softmax_row(float* v, uint32_t* p) {
  constexpr float SC = 0.08838834764831845f * 1.4426950408889634f;
  float m = fmaxf(fmaxf(fmaxf(fmaxf(v[0], v[1]), fmaxf(v[2], v[3])), fmaxf(fmaxf(v[4], v[5]), fmaxf(v[6], v[7]))), fmaxf(v[8], v[9]));
  m = fmaxf(m, __shfl_xor_sync(0xffffffffu, m, 1));
  m = fmaxf(m, __shfl_xor_sync(0xffffffffu, m, 2));
  const float ms = -m * SC, mh = fmaf(m, -SC, -1.f);
#pragma unroll
  for (int i = 0; i < 10; i++) asm("ex2.approx.ftz.f32 %0, %1;" : "=f"(v[i]) : "f"(fmaf(v[i], SC, i < 8 ? ms : mh)));
#pragma unroll
  for (int n = 0; n < 5; n++) p[n] = pack_bf16(v[2*n], v[2*n+1]);
  return fmaf(v[8] + v[9], 2.f, ((v[0] + v[1]) + (v[2] + v[3])) + ((v[4] + v[5]) + (v[6] + v[7])));
}

template<bool ATT>
DEVI void rec_attn(const uint32_t sb, int h, int rank, int w, const bf16* __restrict__ Wo, const bf16* __restrict__ mem0) {
  using namespace rec;
  const int lane0 = lane_reg();
  int budget = SPIN_BUDGET;
  constexpr int NT = ATT ? 5 : 6;
  uint32_t wl[16];
  if (!ATT) {
    LANE_NOW;
#pragma unroll
    for (int i = 0; i < 16; i++) {
      const int dh = 8 * (i >> 1) + 2 * c;
      const unsigned short* p = (const unsigned short*)Wo + (size_t)(h * DH + dh) * DM + 15 * 64 + 16 * w + 8 * (i & 1) + g;
      wl[i] = p[0] | (uint32_t)p[DM] << 16;
    }
  }
  cluster_arrive(); cluster_wait();
  const uint32_t d0 = desc_base(sb);
  uint32_t pph = 0;
#pragma unroll 1
  for (int s = -1; s < NSTEP; s++) {
    asm volatile("" : "+r"(h), "+r"(rank), "+r"(w));
    const uint32_t sp = s & 1;
    const int t0 = ATT ? rank + 1 : 0;
    const bool more = s + 1 < NSTEP;
    if (s == 0) mbar_wait(sb + B_WO, 0, budget);
    float hold[10] = {0, 0, 0, 0, 0, 0, 0, 0, 0, 0};
    if (ATT && s >= 0) {
      float sc[20];
      LANE_NOW;
      mbar_wait(sb + B_QK, sp, budget);
      PROFW(0, 1);
      fence_proxy_async();
      wg_fence();
      sfor<0, 8>([&](auto K) { constexpr int k = K; wg_ss40<k != 0, Op<QB + k * 256, 128, RG, 0, 1>, Op<QB + 3 * RG + k * 256, 128, 2 * RG, 0, 1>>(sc, d0, d0); });
      wg_commit();
      if (P_G1 < 16 && more) nbar_arrive<NB_G1, 384>();
      mbar_wait(sb + B_V, sp, budget);
      wg_wait<0>();
      pin<20>(sc);
      if (w == 3 && more) nbar_arrive<NB_S, 64>();
      PROFW(1, 2);
      if (w == 0) {
        uint32_t p[5];
        float v[10];
#pragma unroll
        for (int i = 0; i < 10; i++) v[i] = sc[4 * (i >> 1) + (i & 1)];
        softmax_row(v, p);
        const uint32_t a = sb + lane * 4;
        sts32v(a + PM0, p[0]); sts32v(a + PM0 + 128, p[1]); sts32v(a + PM1, p[2]); sts32v(a + PM1 + 128, p[3]); sts32v(a + PM2, p[4]);
      }
      if (more) {
        float rs[4], ot[2][4];
        uint32_t one[4];
#pragma unroll
        for (int i = 0; i < 4; i++) one[i] = 0x3F803F80u + ((uint32_t)budget >> (31 - i));
        typedef Op<PM0, 128, 128, 0, 0> P0; typedef Op<PM1, 128, 128, 0, 0> P1; typedef Op<PM2, 0, 128, 0, 0> P2;
        fence_proxy_async();
        nbar_sync<NB_P, 128>();
        PROFW(0, 3);
        wg_fence();
        wg_rs8<0, P0>(rs, one, d0); wg_rs8<1, P1>(rs, one, d0); wg_rs8<1, P2>(rs, one, d0);
        wg_commit();
        sfor<0, 2>([&](auto T) {
          constexpr int t = T;
          wg_ss8<0, Op<QB + 8 * RG + t * 1024, 2 * RG, 128, 0, 0>, P0>(ot[t], d0, d0);
          wg_ss8<1, Op<QB + 12 * RG + t * 1024, RG, 128, 0, 0>, P1>(ot[t], d0, d0);
          wg_ss8<1, Op<QB + 14 * RG + t * 1024, 0, 128, 0, 0>, P2>(ot[t], d0, d0);
        });
        wg_commit();
        if (P_G2 < 16 && !P_G2L) nbar_arrive<NB_G2, 384>();
        const uint32_t oa = w * 256 + lane * 4, r1 = mapr(h, sb, rank ^ 1), r2 = mapr(h, sb, 2);
        mbar_wait(sb + B_SDONE, sp, budget);
        wg_wait<1>();
        pin<4>(rs);
        float i0, i1;
        asm volatile("rcp.approx.ftz.f32 %0, %1;" : "=f"(i0) : "f"(rs[0]));
        asm volatile("rcp.approx.ftz.f32 %0, %1;" : "=f"(i1) : "f"(rs[1]));
        wg_wait<0>();
        pin<4>(ot[0]); pin<4>(ot[1]);
        uint32_t x[4];
#pragma unroll
        for (int j = 0; j < 4; j++) {
          x[j] = pack_bf16(ot[j >> 1][2 * (j & 1)] * i0, ot[j >> 1][2 * (j & 1) + 1] * i1);
          sts32v(sb + OM + rank * OMS + oa + (j >> 1) * 1024 + (j & 1) * 128, x[j]);
        }
        fence_proxy_async();
#pragma unroll
        for (int j = 0; j < 8; j++) {
          const int i = P_OS ? j >> 1 : j & 3;
          if (P_OS ? j & 1 : j >> 2) st_async32(r1 + OM + rank * OMS + oa + (i >> 1) * 1024 + (i & 1) * 128, x[i], r1 + B_OM);
          else st_async32(r2 + OM2 + rank * OM2S + oa + (i >> 1) * 1024 + (i & 1) * 128, x[i], r2 + B_OM);
        }
        e_arrive(sb + B_OM);
        if (P_G2 < 16 && P_G2L) nbar_arrive<NB_G2, 384>();
        PROFW(0, 4);
      }
#pragma unroll
      for (int i = 0; i < 10; i++) hold[i] = w ? sc[4 * (i >> 1) + (i & 1)] : sc[4 * (i >> 1) + 2 + (i & 1)];
    }
    if (more && s >= 0) {
      LANE_NOW;
      char* const pw = (char*)g_part + (uint32_t)((t0 * 16 + w * 4 + (lane >> 3)) * 4096 + h * 128 + ((lane ^ h) & 7) * 16);
      mbar_wait(sb + B_OM, sp, budget);
      if (w == 0) nbar_arrive<NB_G, 128>();
      PROFW(1, 5);
      if (!ATT) fence_proxy_async();
      float acc[3][8];
      auto store = [&](auto J) {
        constexpr int j = J;
        float* d = acc[j % 3];
        pin<8>(d);
        uint32_t x[4];
#pragma unroll
        for (int i = 0; i < 4; i++) { const uint32_t m = (h >> 3) == i; x[i] = (pack_bf16(d[2*i], d[2*i+1]) & ~m) | (m & ~sp); }
        stg_rlx128(pw + j * (48 * 4096), x[0], x[1], x[2], x[3]);
        if constexpr (ATT && j == JA) nbar_arrive<NB_TR, 160>();
        if constexpr (j == 2) PROFW(3, 26);
      };
      sfor<0, NT>([&](auto J) {
        constexpr int j = J;
        if constexpr (ATT && j == JA) { mbar_wait(sb + B_WA, sp, budget); PROFW(2, 0); }
        wg_fence();
        sfor<0, 8>([&](auto K) {
          constexpr int k = K;
          typedef Op<(ATT ? OM : OM2) + k * 256, 128, ATT ? OMS : OM2S, 0, 1> OB;
          if constexpr (j == 5 && k < 4) wg_rs16<k ? 1 : 2, OB>(acc[j % 3], wl + 4 * k, d0);
          else wg_ss16<k ? 1 : j < 3 ? 0 : 2, Op<(j == JA ? WA : j < 5 ? WO + (j - (j > JA)) * 16384 : WH - 8192) + k * 2048, 16, 1024, 1, 1>, OB>(acc[j % 3], d0, d0);
        });
        wg_commit();
        if constexpr (j == 0) { if (w == 3) e_expect_tx(sb + B_OM, ATT ? 2048 : 4096); }
        if constexpr (j == NT - 1 && !P_WOL) nbar_arrive<NB_WO, 384>();
        if constexpr (j > 0 && j != P_WB + 1) { wg_wait<1>(); store(IC<j - 1>{}); }
        if constexpr (j == P_WB || j == NT - 1) { wg_wait<0>(); store(IC<j>{}); }
        if constexpr (j == P_WB) {
          const uint32_t t = clock32();
          if (ATT) {
            if (w == 3 && lane < 14) sts128(sb + PM1 + lane * 16, (lane >> 1) == 3 ? 0x3F803F80u : 0);
            if (w == 3 || P_MB) fence_proxy_async();
            nbar_sync<NB_P, 128>();
          } else if (P_MB) fence_proxy_async();
          spin_until(t, TUN(8, 100));
        }
      });
      if (P_WOL) { spin_until(clock32(), TUN(9, 0)); nbar_arrive<NB_WO, 384>(); }
    } else if (more) nbar_arrive<NB_WO, 384>();
    PROFW(0, 6);
    asm volatile("" : "+r"(h), "+r"(rank), "+r"(w));
#pragma unroll 1
    for (int pass = 0; ATT && pass < 2; pass++)
    if (pass != rank) {
      LANE_NOW;
      const int lim = 8 * (g >> 1) + (g & 1) + 2 * w - 8 * c;
      uint32_t p[5];
#pragma unroll
      for (int i = 0; i < 8; i++) hold[2+i] = i <= lim ? hold[2+i] : -INFINITY;
      const float psum = softmax_row(hold, p);
#pragma unroll
      for (int i = 0; i < 5; i++) hold[i] = __uint_as_float(p[i]);
      hold[5] = psum;
    } else if (more) {
      LANE_NOW;
      const int blk = rank * 32 + h;
      char* const mw = (char*)g_mem + (uint32_t)(sp * 32768 + blk * 512 + w * 128 + lane * 4);
      uint32_t v0 = 0;
      if (s == -1 || (s == LAG - 1 && (w & 1))) {
        const unsigned short* q = (const unsigned short*)mem0 + c * 2 * DM + blk * 16 + (w >> 1) * 8 + g;
        v0 = q[0] | (uint32_t)q[DM] << 16;
        if (v0 == 0) v0 = 0x8000u;
      }
      keep(mw);
      if (s >= 0) {
        const uint32_t ca = sb + WA + lane * 128 + (((2 * w) ^ lane) & 7) * 16 + (lane >> 3) * 4;
        const uint32_t sa = sb + OM + (((g >> 1) & 1) * 2 + (g >> 2)) * 128 + (2 * c + (w >> 1)) * 16 + (w & 1) * 8 + (g & 1) * 2;
        const bool g4l = P_G4L == 1 || (P_G4L == 2 && single(s));
        for (bool first = true; ; first = false) {
          float r[4];
          mbar_wait(sb + B_PART, pph, budget);
          PROFW(0, 11);
          pph ^= 1;
          wg_fence();
          sfor<0, 8>([&](auto K) { constexpr int k = K; wg_ss8<k != 0, Op<WA + k * 2048, 16, 1024, 1, 1>, Op<PM1 + (6 - (k & 6)) * 16, 0, 128, 0, 0>>(r, d0, d0); });
          wg_commit();
          if (!g4l && first) nbar_arrive<NB_G4, 384>();
          const uint32_t x0 = lds32v(ca), x1 = lds32v(ca + 4096), x2 = lds32v(ca + 8192), x3 = lds32v(ca + 12288);
          bool bad = __any_sync(0xffffffffu, (sp ? x0 | x1 | x2 | x3 : ~(x0 & x1 & x2 & x3)) & 1) && budget > 0;
          wg_wait<0>();
          pin<4>(r);
          uint32_t y = pack_bf16(r[0], r[2]);
          y |= (y & 0xffffu) ? 0 : 0x8000u;
          y |= (y >> 16) ? 0 : 0x80000000u;
          if (bad) y = 0;
          sts16(sa, y); sts16(sa + 4, y >> 16);
          nbar_sync<NB_P, 128>();
          y = lds32v(sb + OM + w * 128 + lane * 4);
          const bool ok = !__any_sync(0xffffffffu, y == 0);
          if (ok) stg_rlx32(mw, v0 ? v0 : y);
          if (g4l && first) nbar_arrive<NB_G4, 384>();
          if (ok) break;
          nbar_sync<NB_P, 128>();
          budget--;
          if (w == 0) { e_expect_tx(sb + B_PART, 16384); e_bulk_g2s(sb + WA, (const char*)g_part + blk * 16384, 16384, sb + B_PART); }
          __syncwarp();
        }
        nbar_sync<NB_P, 128>();
        if (w < 2) e_arrive_cl(mapr(h, sb + B_BFREE, w));
      } else stg_rlx32(mw, v0);
      stg_rlx32(mw + (sp ? -32768 : 32768), 0);
      PROFW(1, 8);
    }
    if (ATT && s >= 0) {
      const int seg = s - (rank ? LAG : 0);
      const bool act = (unsigned)seg < NSEG;
      LANE_NOW;
      uint32_t a[12];
#pragma unroll
      for (int i = 0; i < 12; i++) a[i] = __float_as_uint(hold[i < 10 ? i >> 1 : 4]) + ((uint32_t)budget >> (31 - (i & 3)));
      float o[32], inv, psum = hold[5];
      char* const ob = (char*)g_o[rank] + ((size_t)(seg * 32 + 8 * (g >> 1) + (g & 1) + 2 * w) * (NH * DH) + h * DH + c * 8) * 2;
      sfor<0, 2>([&](auto HF) {
        constexpr int hf = HF;
        wg_fence();
        wg_rs64<hf * 2, Op<QB + 8 * RG + hf * 1024, 2 * RG, 128, 0, 0>>(o, a, d0);
        wg_rs64<1, Op<QB + 12 * RG + hf * 1024, RG, 128, 0, 0>>(o, a + 4, d0);
        wg_rs64<1, Op<QB + 14 * RG + hf * 1024, 0, 128, 0, 0>>(o, a + 8, d0);
        wg_commit();
        if constexpr (hf == 0) {
          psum += __shfl_xor_sync(0xffffffffu, psum, 1);
          psum += __shfl_xor_sync(0xffffffffu, psum, 2);
          asm("rcp.approx.ftz.f32 %0, %1;" : "=f"(inv) : "f"(psum));
        }
        wg_wait<0>();
        pin<32>(o);
        if constexpr (hf == 1) { if (w == 2 && more) e_arrive_cl(mapr(h, sb + B_BFREE, 2)); }
        if (act) {
#pragma unroll
          for (int i = 0; i < 2; i++)
            stg128(ob + (hf * 2 + i) * 64, pack_bf16(o[16*i] * inv, o[16*i+1] * inv), pack_bf16(o[16*i+4] * inv, o[16*i+5] * inv),
                   pack_bf16(o[16*i+8] * inv, o[16*i+9] * inv), pack_bf16(o[16*i+12] * inv, o[16*i+13] * inv));
        }
      });
      PROFW(0, 7);
      if (act && (seg & 3) == 3) {
        nbar_sync<NB_P, 128>();
        if (w == 0) e_flag_add(g_fl.dep + grp(0, rank, seg >> 2), 4);
      }
    } else if (!ATT && w == 3) {
      if (s + 4 < NSEG) e_prefetch(g_xn[0] + (size_t)((s + 4) * 32 + h) * DM, 2048);
    }
  }
  cluster_arrive(); cluster_wait();
  char* const pw = (char*)g_part + (size_t)((ATT ? rank + 1 : 0) * 16 + w * 4 + (lane0 >> 3)) * 4096 + h * 128 + (lane0 & 7) * 16;
#pragma unroll
  for (int j = 0; j < NT; j++) stg_rlx128(pw + j * (48 * 4096), 0, 0, 0, 0);
}

DEVI void rec_load(const uint32_t sb, const int h, const int rank, const int w, const CUtensorMap* mX, const CUtensorMap* mWo) {
  using namespace rec;
  static_assert(((NSTEP - 1) & 31) > 3, "stale time stamps of the previous launch never match");
  const int lane0 = lane_reg(), mq = (w + 3) & 3;
  int budget = SPIN_BUDGET;
  if (w == 0) { e_flag_add(g_fl.xn[0][0]); flag_wait(g_fl.xn[0][0], 96, budget); }
  bool late = false;
  cluster_arrive(); cluster_wait();
  if (w == 0) { if (lane0 < 4) mbar_arrive(sb + B_FULL + 8 * lane0); __syncwarp(); }
  uint32_t lph = 0;
#pragma unroll 1
  for (int s = -1; s < NSTEP - 1; s++) {
    if (w == 0) {
      if (late) flag_wait(g_fl.xn[1][(s + 1 - LAG) >> 2], 128, budget);
      if (single(s)) {
#pragma unroll 1
        for (int i = 0; i < 8; i++) {
          const int k = i < 5 ? (0x21430 >> (4 * i)) & 15 : i;
          const int sl = (SLOT1 >> (4 * k)) & 15;
          mbar_wait(sb + B_EMPTY + 8 * sl, (((USE1 >> (4 * k)) ^ (sl >> 1 == 1 ? flip(s) : 0)) & 1) ^ 1, budget);
          e_expect_tx(sb + B_FULL + 8 * sl, 8192);
          e_tma_3d(sb + RING + sl * 8192, mX + 1, 0, (s + 1 + (s < LAG ? 0 : NSTEP)) * 32, k * 2, sb + B_FULL + 8 * sl);
        }
      } else {
        int sl = 4, ph = 1;
#pragma unroll 1
        for (int i = 0; i < 16; i++) {
          mbar_wait(sb + B_EMPTY + 8 * sl, ph ^ (sl >> 1 & LAG & 1), budget);
          e_expect_tx(sb + B_FULL + 8 * sl, 8192);
          e_tma_3d(sb + RING + sl * 8192, mX, i * 64, (s + 1) * 32, 0, sb + B_FULL + 8 * sl);
          if (++sl == 5) { sl = 0; ph ^= 1; }
        }
      }
      nbar_arrive<NB_X, 128>();
      const int sn = s + 2 - LAG;
      late = (sn & 3) == 0 && (unsigned)sn < NSEG && ld_acquire(g_fl.xn[1][sn >> 2]) < 128;
      asm volatile("fence.proxy.async.global;" ::: "memory");
    }
    uint32_t t = gtime();
    if (s >= 0) {
      uint2 a;
      if (w == 2 && rank < 2) {
        nbar_sync<NB_S, 64>();
        e_expect_tx(sb + B_WA, 16384);
        e_tma_2d(sb + WA, mWo, (3 * JA + 1 + rank) * 64, h * DH, sb + B_WA);
        e_tma_2d(sb + WA + 8192, mWo, (3 * JA + 1 + rank) * 64, h * DH + 64, sb + B_WA);
        e_arrive_cl(mapr(h, sb + B_SDONE, rank ^ 1));
        stg_rlx32(&g_ann[s & 1][lane0][h * 2 + rank], (gtime() & ~31u) | ((s + 1) & 31));
        e_expect_tx(sb + B_QK, 10240);
        e_expect_tx(sb + B_V, 10240);
      }
      if (w) nbar_sync<NB_G, 128>();
      do { a = ldg_rlx64(&g_ann[s & 1][h][lane0 * 2]); } while (__any_sync(0xffffffffu, ((a.x ^ (s + 1)) | (a.y ^ (s + 1))) & 31) && --budget > 0);
      t += __reduce_max_sync(0xffffffffu, max((int)(a.x - t), (int)(a.y - t)));
      t &= ~31u;
      PROFW(1, 12);
      if (w == 1 && rank < 2) {
        nbar_sync<NB_TR, 160>();
        wait_time(t + (single(s) ? (rank ? TUN(11, 1650) : TUN(10, 1250)) : rank ? TUN(1, 1750) : TUN(0, 1350)), budget);
        e_expect_tx(sb + B_PART, 16384);
        e_bulk_g2s(sb + WA, (const char*)g_part + (rank * 32 + h) * 16384, 16384, sb + B_PART);
        PROFW(1, 21);
      }
      t += single(s) ? (mq == 0 ? TUN(12, 2200) : mq == 1 ? TUN(13, 2300) : mq == 2 ? TUN(14, 2700) : TUN(15, 2800))
                     : (mq == 0 ? TUN(2, 2350) : mq == 1 ? TUN(3, 2450) : mq == 2 ? TUN(4, 2850) : TUN(5, 2950));
    }
    if (w) nbar_sync<NB_X, 128>();
    mbar_wait(sb + B_EMPTY + 8 * mq, mq >= 2 ? flip(s + 1) ^ 1 : 1, budget);
    PROFW(1, 9);
    wait_time(t, budget);
    PROFW(1, 22); PROFW(3, 23);
    while (true) {
      e_expect_tx(sb + B_MLAND + 8 * mq, 8192);
      e_bulk_g2s(sb + RING + mq * 8192, (const char*)g_mem + (s & 1) * 32768 + mq * 8192, 8192, sb + B_MLAND + 8 * mq);
      const uint32_t a = sb + RING + mq * 8192 + lane0 * 32 + (lane0 >> 2) * 4;
      mbar_wait(sb + B_MLAND + 8 * mq, lph, budget);
      lph ^= 1;
      PROFW(1, 24);
      uint32_t mn = 0xffffffffu;
#pragma unroll
      for (int i = 0; i < 8; i++) mn = min(mn, lds32v(a + i * 1024));
      if (!__any_sync(0xffffffffu, mn == 0) || --budget <= 0) break;
    }
    e_arrive(sb + B_FULL + 8 * mq);
    PROFW(1, 10); PROFW(2, 13); PROFW(3, 14); PROFW(0, 15);
  }
}

DEVI void ln_row(const uint4* u, bf16* dst, int lane) {
  const uint32_t* x = (const uint32_t*)u;
  float mean = 0, q = 0;
#pragma unroll
  for (int i = 0; i < 16; i++) mean += bf_lo(x[i]) + bf_hi(x[i]);
  mean *= 1.f / 32;
#pragma unroll
  for (int i = 0; i < 16; i++) { const float a = bf_lo(x[i]) - mean, b = bf_hi(x[i]) - mean; q = fmaf(a, a, fmaf(b, b, q)); }
#pragma unroll
  for (int o = 1; o < 32; o *= 2) {
    const float m2 = __shfl_xor_sync(0xffffffffu, mean, o), q2 = __shfl_xor_sync(0xffffffffu, q, o), dl = m2 - mean;
    q = fmaf(dl * dl, 16.f * o, q + q2);
    mean = 0.5f * (mean + m2);
  }
  const float rs = rsqrtf(q * (1.f / DM) + 1e-5f), mr = -mean * rs;
#pragma unroll
  for (int i = 0; i < 4; i++) {
    uint32_t y[4];
#pragma unroll
    for (int k = 0; k < 4; k++) y[k] = pack_bf16(fmaf(bf_lo(x[4*i+k]), rs, mr), fmaf(bf_hi(x[4*i+k]), rs, mr));
    stg128((uint4*)dst + i * 32 + lane, y[0], y[1], y[2], y[3]);
  }
}

struct RecMaps { CUtensorMap w[3], wo, x[2]; };
__global__ void __cluster_dims__(R_CL, 1, 1) __launch_bounds__(512, 1)
rec_kernel(const __grid_constant__ RecMaps M, const bf16* __restrict__ Wo, const bf16* __restrict__ mem0, const bf16* __restrict__ x, uint32_t zero) {
  using namespace rec;
  extern __shared__ __align__(1024) uint8_t smem[];
  const uint32_t sb = smem_u32(smem);
  const int tid = threadIdx.x, warp = __shfl_sync(0xffffffffu, tid >> 5, 0), wg = warp >> 2, lane = tid & 31;
  const int h = blockIdx.x / 3, rank = blockIdx.x % 3;
  if (warp == 0) {
    if (lane < 20) mbar_init(sb + BARS + 8 * lane, (lane >= 5 && lane < 10) || lane == 19 ? 2 : lane == 14 ? 9 : lane == 16 && rank < 2 ? 5 : 1);
    else if (lane < 23) mbar_init(sb + B_W1 + 8 * (lane - 20), 1);
    else if (lane == 23) mbar_init(sb + B_PART, 1);
    fence_mbar_init();
    __syncwarp();
    if (lane == 0) { mbar_expect_tx(sb + B_W1, (NSS + R1) * 4096); mbar_expect_tx(sb + B_QK, 10240); mbar_expect_tx(sb + B_V, 10240); mbar_expect_tx(sb + B_OM, rank < 2 ? 2048 : 4096); }
    __syncwarp();
    for (int i = lane; i < 128; i += 32) {
      const int j = i >> 1, t = i & 1, r = reg_idx(j);
      if (is_ss(j)) tma_load_2d(sb + WS + (t * NSS + ss_before(j)) * 2048, &M.w[rank], h * DH + t * 64, j * 16, sb + B_W1);
      else if (r < R1) tma_load_2d(sb + WO + (t * R1 + r) * 2048, &M.w[rank], h * DH + t * 64, j * 16, sb + B_W1);
      else tma_prefetch_2d(&M.w[rank], h * DH + t * 64, j * 16);
    }
  } else if (warp == 1) {
    constexpr int N = (sizeof(Flags) - sizeof(g_fl.xn)) / 16;
    if (lane < 8 && blockIdx.x * 8 + lane < N) ((uint4*)g_fl.dep)[blockIdx.x * 8 + lane] = make_uint4(0, 0, 0, 0);
    static_assert(N <= 96 * 8, "flag reset");
    if (blockIdx.x < 64) ((uint4*)g_stat[4])[blockIdx.x * 64 + lane] = ((uint4*)g_stat[4])[blockIdx.x * 64 + 32 + lane] = make_uint4(0, 0, 0, 0);
    __threadfence();
    __syncwarp();
    asm volatile("griddepcontrol.launch_dependents;" ::: "memory");
  } else if (warp >= 5 && blockIdx.x * 11 + warp - 5 < SEQ / 2) {
    const size_t o = (size_t)(blockIdx.x * 11 + warp - 5) * (2 * DM);
    uint4 u[8];
#pragma unroll
    for (int i = 0; i < 8; i++) u[i] = __ldg((const uint4*)(x + o) + i * 32 + lane);
    ln_row(u, g_xn[0] + o, lane);
    ln_row(u + 4, g_xn[0] + o + DM, lane);
  }
  __syncthreads();
  if (wg == 3) {
    reg_dec<24>();
    rec_load(sb, h, rank, warp & 3, M.x, &M.wo);
    cluster_arrive(); cluster_wait();
  } else if (wg == 2) {
    reg_dec<72>();
    if (rank < 2) rec_attn<true>(sb, h, rank, warp & 3, Wo, mem0);
    else rec_attn<false>(sb, h, rank, warp & 3, Wo, mem0);
  } else {
    reg_inc<208>();
    rec_proj(sb, h, rank, warp, &M.w[rank], &M.wo, zero);
    cluster_arrive(); cluster_wait();
  }
}

namespace gm {
constexpr int STAGES = 6, STAGE_BYTES = 32768;
constexpr uint32_t SO = STAGES * STAGE_BYTES, B_FULL = SO + 32768, B_TRIG = B_FULL + 56, B_EMPTY = B_FULL + 64, B_JOB = B_FULL + 128,
                   B_MSG = B_FULL + 144, B_XF = B_FULL + 160, B_SF = B_FULL + 176, JOB = B_FULL + 192, MSG = JOB + 8, SMEM = B_FULL + 256;
constexpr int T_O = 0, T_GU = 1, T_D = 2, T_END = 3;
#define G_LOOK 8
#define G_FILL 7
#define G_SLEEP 100
#define G_SLEEP2 500
#define G_SLEEP3 100
#define G_DF 0
#define G_FL 10
#define G_DE 0
#define G_DS 16
DEVI bool is_split(int ty, int l, int cb) { return ty == T_O || (ty == T_D && (!l || cb >= G_DS)); }
struct Pipe { int s, ph; DEVI void next() { if (++s == STAGES) { s = 0; ph ^= 1; } } };
}
struct GemmMaps { CUtensorMap o, wo, x, x1, x1s, xm, xms, xn, wg, wu, h, hs, wd, x2, out, outs; };

DEVI float geglu(float g, float u) {
  const float z = g * (0.7978845608028654f + 0.035677408136300125f * g * g);
  float t; asm("tanh.approx.f32 %0, %1;" : "=f"(t) : "f"(z));
  const float hg = 0.5f * g;
  return fmaf(hg, t, hg) * u;
}
DEVI int h_ready(int v) { const int t = v ^ 0x10141014; return t & 0xff0000ff ? 0 : t & 0xff00 ? 20 : t ? 36 : 56; }
DEVI int a_ready(int ty, int l, int cb) {
  const int v = ld_acquire(g_fl.dep + grp(ty, l, cb));
  asm volatile("fence.proxy.async.global;" ::: "memory");
  return ty == gm::T_D ? h_ready(v) : v >= (ty == gm::T_O && l ? 256 : 128) ? 64 : 0;
}

__global__ void __cluster_dims__(2, 1, 1) __launch_bounds__(512, 1) gemm_kernel(const __grid_constant__ GemmMaps M) {
  using namespace gm;
  extern __shared__ __align__(1024) uint8_t smem[];
  const uint32_t sb = smem_u32(smem);
  const int tid = threadIdx.x, wid = __shfl_sync(0xffffffffu, tid >> 5, 0), wg = wid >> 2, warp = wid & 3;
  int budget = SPIN_BUDGET;
  const int rank = blockIdx.x & 1;
  const uint32_t peer = mapa(sb, rank ^ 1);
  if (tid < 24) mbar_init(sb + B_FULL + 8 * tid, tid >> 3 == 1 ? 2 : 1);
  fence_mbar_init();
  if (wid == 1 && rank == 0) sts32v(sb + JOB + 16, bcast(e_ticket(g_fl.ticket)));
  cluster_arrive(); cluster_wait();
  int pair;
  asm volatile("ld.shared::cluster.u32 %0, [%1];" : "=r"(pair) : "r"(mapa(sb + JOB + 16, 0)) : "memory");
  pair = __shfl_sync(0xffffffffu, pair, 0);
  const int cta = pair * 2 + rank, lane = lane_reg();
  if (wg >= 2) {
    reg_dec<72>();
    if (wid == 8 || wid == 10) {
      Pipe p; p.s = 0; p.ph = 1;
      for (int n = 0; ; n++) {
        if (wid == 8) e_expect_tx(sb + B_MSG + 8 * (n & 1), 4);
        mbar_wait(sb + B_MSG + 8 * (n & 1), (n >> 1) & 1, budget);
        const int msg = __shfl_sync(0xffffffffu, lds32v(sb + MSG + 4 * (n & 1)), 0);
        const int ty = (msg >> 11) & 3, l = (msg >> 10) & 1;
        const bool shb = ty == T_GU && l, spl = is_split(ty, l, (msg >> 6) & 15);
        const int cb = ((msg >> 6) & 15) + (shb ? rank : 0), j = (msg & 63) + (ty == T_END || shb ? 0 : rank);
        const int ke = ty == T_O ? 64 : ty == T_GU ? 16 : 56, k0 = spl ? rank : 0, dk = spl ? 2 : 1;
        const int c0 = ty == T_GU ? j * 64 : spl ? (j >> 1) * 128 : j * 128, c1 = ty == T_GU ? c0 : c0 + 64;
        mbar_wait(sb + B_EMPTY + 8 * p.s, p.ph, budget);
        trap_if_spent(budget);
        auto stages = [&](auto f) {
#pragma unroll 1
          for (int k = k0; k < ke; k += dk) {
            mbar_wait(sb + B_EMPTY + 8 * p.s, p.ph, budget);
            f(k, sb + p.s * STAGE_BYTES, sb + B_FULL + 8 * p.s);
            p.next();
          }
        };
        if (wid == 8) {
          const int job = ty << 11 | l << 10 | cb << 6 | j;
          sts32v(sb + JOB + 4 * (n & 1), job | p.s << 16 | (p.ph ^ 1) << 20);
          e_arrive(sb + B_JOB + 8 * (n & 1));
          if (ty == T_END) break;
          if (ty != T_GU) { e_expect_tx(sb + B_FULL + 8 * p.s, spl ? 16384 : STAGE_BYTES); p.next(); }
          const CUtensorMap* const m0 = ty == T_D ? &M.wd : shb && rank ? &M.wu : &M.wg, * const m1 = ty == T_D ? &M.wd : &M.wu;
          if (ty == T_O) stages([&](int k, uint32_t a, uint32_t fb) { e_expect_tx(fb, STAGE_BYTES); e_tma_5d(a + 16384, &M.wo, c0, k * 2, fb); e_tma_5d(a + 24576, &M.wo, c1, k * 2, fb); });
          else if (shb) stages([&](int k, uint32_t a, uint32_t fb) { e_expect_tx(fb, STAGE_BYTES); e_tma_2d_mc(a + 16384 + rank * 8192, m0, c0, k * 64, fb); });
          else stages([&](int k, uint32_t a, uint32_t fb) { e_expect_tx(fb, STAGE_BYTES); e_tma_2d(a + 16384, m0, c0, k * 64, fb); e_tma_2d(a + 24576, m1, c1, k * 64, fb); });
        } else {
          if (ty == T_END) break;
          const int row = l * SEQ + cb * 128, kt = ke + k0 - G_LOOK * dk;
          const uint64_t polA = ty != T_GU ? EVICT_FIRST : EVICT_NORMAL;
          int rdy = msg >> 16;
          auto need = [&](int k) {
            if (k == kt) e_arrive(sb + B_TRIG);
            while (k >= rdy && k >= (rdy = a_ready(ty, l, cb))) { __nanosleep(G_SLEEP); trap_if_spent(--budget); }
          };
          if (ty != T_GU) {
            need(0);
            const uint32_t a = sb + p.s * STAGE_BYTES, fb = sb + B_FULL + 8 * p.s;
            const CUtensorMap* const m = ty == T_D ? (spl ? &M.x1 : &M.x1s) : l ? &M.x2 : &M.x;
            const int r = (ty == T_D ? row : cb * 128) + (spl ? rank * 64 : 0);
            e_tma_2d(a, m, c0, r, fb, polA); e_tma_2d(a + 16384, m, c1, r, fb, polA);
            p.next();
          }
          if (shb || spl) {
            const CUtensorMap* const ma = ty == T_O ? &M.o : ty == T_GU ? &M.xms : &M.hs;
            stages([&](int k, uint32_t a, uint32_t fb) { need(k); e_tma_2d(a, ma, k * 64, row, fb, polA); });
          } else {
            const CUtensorMap* const ma = ty == T_GU ? &M.xm : &M.h;
            stages([&](int k, uint32_t a, uint32_t fb) { need(k); e_tma_2d_mc(a + rank * 8192, ma, k * 64, row + rank * 64, fb, polA); });
          }
        }
      }
    } else if (wid == 9 && rank == 0) {
      int k1 = pair < 18 ? 0 : 48;
      bool late = false;
      for (int n = 0, ty = 0; ty != T_END; n++) {
        mbar_wait(sb + B_TRIG, (n & 1) ^ 1, budget);
        int l, cb, j, rdy = 64;
        while (true) {
          const int ph = k1 % 3;
          const bool gap = pair < 8 ? ph == 1 : pair >= 16 && ph == 2;
          if (k1 < 48) {
            cb = k1++ / 3;
            if (gap && (late || !(G_FILL & (pair < 8 ? 1 : 2)))) continue;
            if (!gap) {
              l = 0;
              ty = pair < 8 ? (ph ? T_GU : T_O) : ph == 2 ? T_D : T_GU;
              j = 2 * (pair < 8 ? (ph ? pair + 10 : pair) : ph == 1 ? pair + 10 : pair - 8);
              rdy = a_ready(ty, 0, cb);
              if (ph == 0) late = rdy != 0;
              break;
            }
          }
          int d0 = ld_relaxed(g_fl.dep + lane), d1 = ld_relaxed(g_fl.dep + 32 + lane);
          const int t0 = ld_relaxed(g_fl.taken + lane), t1 = ld_relaxed(g_fl.taken + 32 + lane);
          const bool l0 = t0 < (lane < 16 ? 8 : lane & 1 ? 0 : 56), l1 = lane < 16 && t1 < (lane < G_DS ? 4 : 8);
          const uint32_t rd = __ballot_sync(0xffffffffu, d0 >= (lane < 16 ? 256 : 128));
          uint32_t ok0 = __ballot_sync(0xffffffffu, l0) & rd & (rd >> 1 | 0xffff), ok1 = __ballot_sync(0xffffffffu, l1 && h_ready(d1) > 0);
          if (gap) { ok1 = 0; if (pair < 16) ok0 &= G_FILL & 4 ? 0xffff0003u : 0xffff0000u; }
          ty = T_END; l = 1; cb = j = 0;
          if (!gap && !__any_sync(0xffffffffu, l0 || l1)) break;
          if (ok1 & ((1u << G_DS) - 1)) ok1 &= (1u << G_DS) - 1;
          const uint32_t dfirst = ok1 & __ballot_sync(0xffffffffu, lane < G_DF && d1 == 0x10141014);
          if (dfirst && !(ok0 & 0xffff)) { ok0 = 0; ok1 = dfirst; }
          else if (__any_sync(0xffffffffu, l0)) ok1 &= (1u << G_DE) - 1;
          uint32_t m = ok0 ? ok0 : ok1;
          if (!m && !gap) __nanosleep(100);
          while (m) {
            const int nth = ok0 ? 0 : pair % __popc(m);
            const int b = __ffs(__ballot_sync(0xffffffffu, __popc(m << (31 - lane)) > nth)) - 1, gn = b + (ok0 ? 0 : 32);
            const int t = bcast(e_ticket(g_fl.taken + gn));
            if (t < (gn < 16 ? 8 : gn < 32 ? 56 : gn < 32 + G_DS ? 4 : 8)) { ty = gn >> 4; cb = gn & 15; j = ty == T_GU ? t : 2 * t; break; }
            m &= ~(1u << b);
          }
          if (ty != T_END) {
            rdy = a_ready(ty, 1, cb);
            if (ty == T_GU) a_ready(ty, 1, cb + 1);
            break;
          }
          trap_if_spent(--budget);
        }
        const int msg = rdy << 16 | ty << 11 | l << 10 | cb << 6 | j;
        e_st_async32(peer + MSG + 4 * (n & 1), msg, peer + B_MSG + 8 * (n & 1));
        e_st_async32(sb + MSG + 4 * (n & 1), msg, sb + B_MSG + 8 * (n & 1));
      }
    } else if (wg == 3) {
      bool open = lane < G_FL && ld_relaxed(g_fl.rows + lane) < 128;
      while (__any_sync(0xffffffffu, open)) {
        int v = 0;
        if (open) asm volatile("ld.acquire.gpu.global.s32 %0, [%1];" : "=r"(v) : "l"(g_fl.part + lane) : "memory");
        const uint32_t ok = __ballot_sync(0xffffffffu, open && v >= 128);
        if (!ok) {
          if (--budget <= 0) break;
          __nanosleep(G_SLEEP2);
          continue;
        }
        const int cb = __ffs(__ballot_sync(0xffffffffu, __popc(ok << (31 - lane)) > (cta >> 5) % __popc(ok))) - 1;
        const int r = bcast(e_ticket(g_fl.rows + cb));
        if (r >= 128) { open = open && lane != cb; continue; }
        uint4 u[4];
#pragma unroll
        for (int i = 0; i < 4; i++) u[i] = ldg_rlx128((const uint4*)(g_x1[1] + (size_t)(cb * 128 + r) * DM) + i * 32 + lane);
        ln_row(u, g_xm[1] + (size_t)(cb * 128 + r) * DM, lane);
        __syncwarp();
        e_flag_add(g_fl.dep + grp(T_GU, 1, cb));
      }
      if (cta == 0 && wid == 12) {
        asm volatile("griddepcontrol.wait;" ::: "memory");
        g_fl.xn[lane >> 4][lane & 15][0] = 0;
        if (NSTEP & 1) for (int i = lane; i < 2048; i += 32) g_mem[1][i] = make_uint4(0, 0, 0, 0);
      }
    }
    cluster_arrive(); cluster_wait();
  } else {
    reg_inc<184>();
    const bool lead = warp == 0;
    const uint32_t eb = (warp == 1 ? peer : sb) + B_EMPTY;
    const int rl = warp < 2 ? 0 : -1;
    const uint32_t so = sb + SO + wg * 16384;
    const int r0 = warp * 16 + (lane & 7) + ((lane >> 3) & 1) * 8;
    const uint32_t sw = r0 * 128 + (((lane >> 4) ^ (r0 & 7)) << 4);
    int xph = 0;
    for (int n = wg; ; n += 2) {
      float d0[64], d1[64];
      mbar_wait(sb + B_JOB + 8 * wg, (n >> 1) & 1, budget);
      fault_if_spent(budget);
      const int job = __shfl_sync(0xffffffffu, lds32v(sb + JOB + 4 * wg), 0);
      const int ty = (job >> 11) & 3, l = (job >> 10) & 1, cb = (job >> 6) & 15, j = job & 63;
      if (ty == T_END) {
        if (n > 0) nbar_sync_r(1 + wg, 256);
        if (lead && !(job & 1)) { sts32v(sb + JOB + 4 * (wg ^ 1), job | 1); e_arrive(sb + B_JOB + 8 * (wg ^ 1)); }
        if (!(job & 1)) nbar_arrive_r(1 + (wg ^ 1), 256);
        break;
      }
      Pipe q; q.s = (job >> 16) & 15; q.ph = job >> 20;
      const bool spl = is_split(ty, l, cb);
      if (ty != T_GU) mbar_wait(sb + B_FULL + 8 * q.s, q.ph, budget);
#pragma unroll
      for (int m = 0; m < 2; m++) {
        float* d = m ? d1 : d0;
        if (ty != T_GU && !(m && spl)) {
#pragma unroll
          for (int c = 0; c < 8; c++) {
            uint32_t r[4];
            ldsm4(sb + q.s * STAGE_BYTES + (c >> 2) * 16384 + m * 8192 + (sw ^ ((c & 3) << 5)), r[0], r[1], r[2], r[3]);
#pragma unroll
            for (int i = 0; i < 4; i++) { d[8*c+2*i] = bf_lo(r[i]); d[8*c+2*i+1] = bf_hi(r[i]); }
          }
        } else {
#pragma unroll
          for (int i = 0; i < 64; i++) d[i] = 0.f;
        }
      }
      if (ty != T_GU) {
        fence_proxy_async();
        nbar_sync_r(3 + wg, 128);
        arrive_cl_if_eq(eb + 8 * q.s, lane, rl);
        q.next();
      }
      pin<64>(d0); pin<64>(d1);
      if (n > 0) nbar_sync_r(1 + wg, 256);
      const int nk = ty == T_O ? 32 : ty == T_GU ? 16 : spl ? 28 : 56;
      const uint32_t ro = spl ? rank * 512 : 0;
      int prev = 0;
      for (int i = 0; i < nk; i++) {
        mbar_wait(sb + B_FULL + 8 * q.s, q.ph, budget);
        const uint32_t da = desc_base(sb) + q.s * (STAGE_BYTES / 16);
        wg_fence();
        sfor<0, 4>([&](auto K) {
          constexpr int k = K;
          typedef Op<16384 + k * 2048, 8192, 1024, 1, 1> OB;
          wg_ss128<1, Op<k * 32, 16, 1024, 1, 0>, OB>(d0, da + ro, da);
          wg_ss128<1, Op<8192 + k * 32, 16, 1024, 1, 0>, OB>(d1, da - ro, da);
        });
        wg_commit();
        wg_wait<1>();
        arrive_cl_if_eq(eb + 8 * prev, lane, i ? rl : -1);
        prev = q.s;
        q.next();
      }
      nbar_arrive_r(1 + (wg ^ 1), 256);
      wg_wait<0>();
      pin<64>(d0); pin<64>(d1);
      arrive_cl_if_eq(eb + 8 * prev, lane, rl);
      if (spl) {
        const uint32_t xa = SO + wg * 16384 + warp * 512 + lane * 16;
        if (lead) e_expect_tx(sb + B_XF + 8 * wg, 16384);
        mbar_wait(sb + B_SF + 8 * wg, ((n >> 1) & 1) ^ 1, budget);
#pragma unroll
        for (int i = 0; i < 8; i++) {
          const float* d = d1 + 8 * i;
          st_async128(peer + xa + i * 2048, pack_bf16(d[0], d[1]), pack_bf16(d[2], d[3]), pack_bf16(d[4], d[5]), pack_bf16(d[6], d[7]), peer + B_XF + 8 * wg);
        }
        mbar_wait(sb + B_XF + 8 * wg, xph, budget);
        xph ^= 1;
        uint32_t y[32];
#pragma unroll
        for (int i = 0; i < 8; i++) {
          const float* d = d0 + 8 * i;
          const uint4 v = lds128(sb + xa + i * 2048);
          y[4*i] = pack_bf16(d[0] + bf_lo(v.x), d[1] + bf_hi(v.x)); y[4*i+1] = pack_bf16(d[2] + bf_lo(v.y), d[3] + bf_hi(v.y));
          y[4*i+2] = pack_bf16(d[4] + bf_lo(v.z), d[5] + bf_hi(v.z)); y[4*i+3] = pack_bf16(d[6] + bf_lo(v.w), d[7] + bf_hi(v.w));
        }
        const bool fuse = !l || (ty == T_O && cb >= G_FL);
        float2* const st = &g_stat[l ? 4 + (cb & 7) : ty + (cb & 1)][0][rank * 64 + warp * 16 + (lane >> 2) * 2];
        if (fuse) {
          float mn[2], sq[2];
#pragma unroll
          for (int z = 0; z < 2; z++) {
            float m = 0, s2 = 0;
#pragma unroll
            for (int i = 0; i < 16; i++) m += bf_lo(y[2*i+z]) + bf_hi(y[2*i+z]);
            m += __shfl_xor_sync(0xffffffffu, m, 1); m += __shfl_xor_sync(0xffffffffu, m, 2);
            m *= 1.f / 128;
#pragma unroll
            for (int i = 0; i < 16; i++) { const float a = bf_lo(y[2*i+z]) - m, b = bf_hi(y[2*i+z]) - m; s2 = fmaf(a, a, fmaf(b, b, s2)); }
            s2 += __shfl_xor_sync(0xffffffffu, s2, 1); s2 += __shfl_xor_sync(0xffffffffu, s2, 2);
            mn[z] = m; sq[z] = s2;
          }
          if ((lane & 3) == 0) stg_rlx128(st + (j >> 1) * 128, __float_as_uint(mn[0]), (__float_as_uint(sq[0]) & ~31u) | (cb + 1), __float_as_uint(mn[1]), __float_as_uint(sq[1]));
          __syncwarp();
        }
        const int row = (ty == T_O ? l * SEQ : 0) + cb * 128 + rank * 64;
        auto put = [&](const CUtensorMap* mo, auto f) {
          nbar_sync_r(3 + wg, 128);
#pragma unroll
          for (int c = 0; c < 8; c++) stsm4(so + (c >> 2) * 8192 + (sw ^ ((c & 3) << 5)), f(4*c), f(4*c+1), f(4*c+2), f(4*c+3));
          fence_proxy_async();
          nbar_sync_r(3 + wg, 128);
          if (lead) { e_tma_store_2d(mo, so, (j >> 1) * 128, row); e_tma_store_2d(mo, so + 8192, (j >> 1) * 128 + 64, row); bulk_commit(); }
        };
        if (fuse) {
          uint4 u[2];
          while (true) {
            __nanosleep(G_SLEEP3);
            u[0] = ldg_rlx128(st + (lane & 3) * 256); u[1] = ldg_rlx128(st + (lane & 3) * 256 + 128);
            if (!__any_sync(0xffffffffu, ((u[0].y ^ (cb + 1)) | (u[1].y ^ (cb + 1))) & 31) || --budget <= 0) break;
          }
          float rs[2], mr[2];
#pragma unroll
          for (int z = 0; z < 2; z++) {
            const float ma = __uint_as_float(z ? u[0].z : u[0].x), mb = __uint_as_float(z ? u[1].z : u[1].x);
            float m = ma + mb;
            m += __shfl_xor_sync(0xffffffffu, m, 1); m += __shfl_xor_sync(0xffffffffu, m, 2);
            m *= 0.125f;
            float s2 = __uint_as_float(z ? u[0].w : u[0].y & ~31u) + __uint_as_float(z ? u[1].w : u[1].y & ~31u) + 128.f * ((ma - m) * (ma - m) + (mb - m) * (mb - m));
            s2 += __shfl_xor_sync(0xffffffffu, s2, 1); s2 += __shfl_xor_sync(0xffffffffu, s2, 2);
            rs[z] = rsqrtf(s2 * (1.f / DM) + 1e-5f); mr[z] = -m * rs[z];
          }
          put(ty == T_O ? &M.xm : &M.xn, [&](int i) { return pack_bf16(fmaf(bf_lo(y[i]), rs[i & 1], mr[i & 1]), fmaf(bf_hi(y[i]), rs[i & 1], mr[i & 1])); });
          if (lead) {
            bulk_wait<0>();
            e_flag_add_bulk(ty == T_D ? g_fl.xn[1][cb] : g_fl.dep + grp(T_GU, l, cb), 8);
          }
        }
        put(ty == T_O ? &M.x1 : l ? &M.out : &M.x2, [&](int i) { return y[i]; });
      } else {
        if (ty == T_GU) {
#pragma unroll
          for (int i = 0; i < 32; i++) { d0[i] = geglu(d0[i], d0[32 + i]); d1[i] = geglu(d1[i], d1[32 + i]); }
        }
#pragma unroll
        for (int hf = 0; hf < 2; hf++) {
          if (hf) {
            if (ty == T_GU) break;
            if (lead) bulk_wait_read<0>();
            nbar_sync_r(3 + wg, 128);
          }
#pragma unroll
          for (int m = 0; m < 2; m++)
#pragma unroll
            for (int c = 0; c < 4; c++) {
              const float* d = (m ? d1 : d0) + 32 * hf + 8 * c;
              stsm4(so + m * 8192 + (sw ^ (c << 5)), pack_bf16(d[0], d[1]), pack_bf16(d[2], d[3]), pack_bf16(d[4], d[5]), pack_bf16(d[6], d[7]));
            }
          fence_proxy_async();
          nbar_sync_r(3 + wg, 128);
          if (lead) {
            if (ty == T_GU) e_tma_store_2d(&M.hs, so, j * 64, l * SEQ + cb * 128); else e_tma_store_2d(&M.outs, so, j * 128 + hf * 64, cb * 128);
            bulk_commit();
          }
        }
      }
      if (lead) {
        bulk_wait<0>();
        e_arrive_cl(peer + B_SF + 8 * wg);
        if (ty == T_GU) e_flag_add_bulk(g_fl.dep + grp(T_D, l, cb), j < 20 ? 1 : j < 36 ? 1 << 8 : 1 << 16);
        else if (ty == T_O) { e_flag_add_bulk(g_fl.dep + grp(T_D, l, cb), 1 << 24); if (l && cb < G_FL) e_flag_add_bulk(g_fl.part + cb, 8); }
        else if (!l) e_flag_add_bulk(g_fl.dep + grp(T_O, 1, cb), 8);
      }
    }
    cluster_arrive(); cluster_wait();
  }
}

typedef CUresult (*PFN_encodeTiled)(CUtensorMap*, CUtensorMapDataType, cuuint32_t, void*, const cuuint64_t*, const cuuint64_t*,
                                    const cuuint32_t*, const cuuint32_t*, CUtensorMapInterleave, CUtensorMapSwizzle,
                                    CUtensorMapL2promotion, CUtensorMapFloatOOBfill);
static PFN_encodeTiled g_encode = nullptr;
static int g_sms = 0;
static CUtensorMap encode(const void* ptr, int rank, const cuuint64_t* dims, const cuuint64_t* strides, const cuuint32_t* box) {
  CUtensorMap m;
  const cuuint32_t es[5] = {1, 1, 1, 1, 1};
  g_encode(&m, CU_TENSOR_MAP_DATA_TYPE_BFLOAT16, rank, (void*)ptr, dims, strides, box, es, CU_TENSOR_MAP_INTERLEAVE_NONE,
           CU_TENSOR_MAP_SWIZZLE_128B, CU_TENSOR_MAP_L2_PROMOTION_L2_256B, CU_TENSOR_MAP_FLOAT_OOB_FILL_NONE);
  return m;
}
static CUtensorMap make_map(const void* ptr, uint64_t rows, uint64_t cols, uint32_t box_rows) {
  const cuuint64_t dims[2] = {cols, rows}, strides[1] = {cols * 2};
  const cuuint32_t box[2] = {64, box_rows};
  return encode(ptr, 2, dims, strides, box);
}
static CUtensorMap make_map_x(const void* ptr) {
  const cuuint64_t dims[3] = {DM, NSTEP * 32, 2}, strides[2] = {DM * 2, (cuuint64_t)NSTEP * 32 * DM * 2};
  const cuuint32_t box[3] = {64, 32, 2};
  return encode(ptr, 3, dims, strides, box);
}
static CUtensorMap make_map_x1(const void* ptr) {
  const cuuint64_t dims[3] = {64, 2 * NSTEP * 32, DM / 64}, strides[2] = {DM * 2, 128};
  const cuuint32_t box[3] = {64, 32, 2};
  return encode(ptr, 3, dims, strides, box);
}
static CUtensorMap make_map_wo(const void* ptr) {
  const cuuint64_t dims[5] = {DM, 2, 4, 4, NH * DH / 32}, strides[4] = {DM * 2, 8 * DM * 2, 2 * DM * 2, 32 * DM * 2};
  const cuuint32_t box[5] = {64, 2, 4, 4, 2};
  return encode(ptr, 5, dims, strides, box);
}

extern "C" void kernel_launch(void* const* d_in, const int* in_sizes, int n_in, void* d_out, int out_size) {
  const bf16 *x = (const bf16*)d_in[0], *mem0 = (const bf16*)d_in[1], *Wo = (const bf16*)d_in[5];
  if (!g_encode) {
    void* p = nullptr; cudaDriverEntryPointQueryResult q;
    cudaGetDriverEntryPoint("cuTensorMapEncodeTiled", &p, cudaEnableDefault, &q);
    g_encode = (PFN_encodeTiled)p;
    int dev = 0;
    cudaGetDevice(&dev);
    cudaDeviceGetAttribute(&g_sms, cudaDevAttrMultiProcessorCount, dev);
    cudaFuncSetAttribute(rec_kernel, cudaFuncAttributeMaxDynamicSharedMemorySize, rec::SMEM);
    cudaFuncSetAttribute(gemm_kernel, cudaFuncAttributeMaxDynamicSharedMemorySize, gm::SMEM);
  }
  void *xn, *o, *x1, *xm, *x2, *hh;
  cudaGetSymbolAddress(&xn, g_xn); cudaGetSymbolAddress(&o, g_o); cudaGetSymbolAddress(&x1, g_x1);
  cudaGetSymbolAddress(&xm, g_xm); cudaGetSymbolAddress(&x2, g_x2); cudaGetSymbolAddress(&hh, g_h);
  RecMaps R;
  for (int i = 0; i < 3; i++) R.w[i] = make_map(d_in[2 + i], DM, NH * DH, 16);
  R.wo = make_map(Wo, NH * DH, DM, 64); R.x[0] = make_map_x(xn); R.x[1] = make_map_x1(xn);
  rec_kernel<<<96, 512, rec::SMEM>>>(R, Wo, mem0, x, 0);
  GemmMaps G;
  G.o = make_map(o, 2 * SEQ, NH * DH, 128); G.wo = make_map_wo(Wo);
  G.x1 = make_map(x1, 2 * SEQ, DM, 64); G.x1s = make_map(x1, 2 * SEQ, DM, 128);
  G.xn = make_map((bf16*)xn + (NSTEP + LAG) * 32 * DM, SEQ, DM, 64);
  G.xm = make_map(xm, 2 * SEQ, DM, 64); G.xms = make_map(xm, 2 * SEQ, DM, 128);
  G.wg = make_map(d_in[8], DM, DF, 64); G.wu = make_map(d_in[9], DM, DF, 64); G.wd = make_map(d_in[10], DF, DM, 64);
  G.h = make_map(hh, 2 * SEQ, DF, 64); G.hs = make_map(hh, 2 * SEQ, DF, 128);
  G.x = make_map(x, SEQ, DM, 64); G.x2 = make_map(x2, SEQ, DM, 64); G.out = make_map(d_out, SEQ, DM, 64); G.outs = make_map(d_out, SEQ, DM, 128);
  cudaLaunchConfig_t cfg = {};
  cfg.gridDim = dim3(g_sms & ~1); cfg.blockDim = dim3(512); cfg.dynamicSmemBytes = gm::SMEM; cfg.stream = cudaStreamPerThread;
  cudaLaunchAttribute at;
  at.id = cudaLaunchAttributeProgrammaticStreamSerialization; at.val.programmaticStreamSerializationAllowed = 1;
  cfg.attrs = &at; cfg.numAttrs = 1;
  cudaLaunchKernelEx(&cfg, gemm_kernel, G);
}
```

```cpp
#include <cuda_runtime.h>
#include <cuda_bf16.h>
#include <cuda.h>
#include <stdint.h>

#define DEVI __device__ __forceinline__
typedef __nv_bfloat16 bf16;

#define LAG 14
constexpr int SEQ = 2048, DM = 1024, NH = 32, DH = 128, DF = 3584, NSEG = 64, NSTEP = NSEG + LAG;

__device__ __align__(1024) bf16 g_xn[2][NSTEP * 32 * DM];
__device__ __align__(1024) bf16 g_o[2][SEQ * NH * DH];
__device__ __align__(1024) bf16 g_x1[2][SEQ * DM];
__device__ __align__(1024) bf16 g_xm[2][SEQ * DM];
__device__ __align__(1024) bf16 g_x2[SEQ * DM];
__device__ __align__(1024) bf16 g_h[2][SEQ * DF];
__device__ __align__(1024) uint4 g_part[256 * 32 * 8];
__device__ __align__(1024) uint32_t g_ann[2][32][64];
__device__ __align__(1024) uint4 g_mem[2][2048];
__device__ __align__(128) float2 g_stat[12][8][128];
__host__ __device__ constexpr int grp(int type, int layer, int blk) { return layer ? 16 * type + blk : 64 + (16 * type + blk) * 32; }
struct Flags {
  int xn[2][16][32];
  int dep[64 + 48 * 32];
  int taken[64];
  int rows[32];
  int part[32];
  int ticket[32];
};
__device__ __align__(128) Flags g_fl;

DEVI uint32_t smem_u32(const void* p) { return (uint32_t)__cvta_generic_to_shared(p); }
DEVI void mbar_init(uint32_t bar, uint32_t cnt) { asm volatile("mbarrier.init.shared::cta.b64 [%0], %1;" :: "r"(bar), "r"(cnt) : "memory"); }
DEVI void mbar_expect_tx(uint32_t bar, uint32_t bytes) { asm volatile("mbarrier.arrive.expect_tx.shared::cta.b64 _, [%0], %1;" :: "r"(bar), "r"(bytes) : "memory"); }
DEVI void mbar_arrive(uint32_t bar) { asm volatile("mbarrier.arrive.shared::cta.b64 _, [%0];" :: "r"(bar) : "memory"); }
DEVI bool mbar_try(uint32_t bar, uint32_t parity) {
  uint32_t p;
  asm volatile("{.reg .pred p; mbarrier.try_wait.parity.shared::cta.b64 p, [%1], %2; selp.u32 %0, 1, 0, p;}" : "=r"(p) : "r"(bar), "r"(parity) : "memory");
  return p;
}
DEVI bool mbar_test(uint32_t bar, uint32_t parity) {
  uint32_t p;
  asm volatile("{.reg .pred p; mbarrier.test_wait.parity.shared::cta.b64 p, [%1], %2; selp.u32 %0, 1, 0, p;}" : "=r"(p) : "r"(bar), "r"(parity) : "memory");
  return p;
}
constexpr int SPIN_BUDGET = 1 << 20;
DEVI void mbar_wait(uint32_t bar, uint32_t parity, int& budget) {
  while (!mbar_try(bar, parity)) { if (--budget < 0) break; }
}
DEVI void trap_if_spent(int budget) { asm volatile("{.reg .pred p; setp.le.s32 p, %0, 0; @p trap;}" :: "r"(budget) : "memory"); }
DEVI void fault_if_spent(int budget) { asm volatile("{.reg .pred p; setp.le.s32 p, %0, 0; @p st.global.u32 [%1], 0;}" :: "r"(budget), "l"(0ull) : "memory"); }
DEVI uint32_t mapa(uint32_t addr, uint32_t rank) { uint32_t r; asm("mapa.shared::cluster.u32 %0, %1, %2;" : "=r"(r) : "r"(addr), "r"(rank)); return r; }
DEVI void cluster_arrive() { asm volatile("barrier.cluster.arrive.release.aligned;" ::: "memory"); }
DEVI void cluster_wait() { asm volatile("barrier.cluster.wait.acquire.aligned;" ::: "memory"); }
DEVI void fence_mbar_init() { asm volatile("fence.mbarrier_init.release.cluster;" ::: "memory"); }
DEVI void fence_proxy_async() { asm volatile("fence.proxy.async.shared::cta;" ::: "memory"); }
DEVI void tma_load_2d(uint32_t dst, const CUtensorMap* m, int c0, int c1, uint32_t bar) {
  asm volatile("cp.async.bulk.tensor.2d.shared::cluster.global.mbarrier::complete_tx::bytes [%0], [%1, {%3, %4}], [%2];"
    :: "r"(dst), "l"(m), "r"(bar), "r"(c0), "r"(c1) : "memory");
}
DEVI void tma_load_5d(uint32_t dst, const CUtensorMap* m, int c0, int c4, uint32_t bar) {
  asm volatile("cp.async.bulk.tensor.5d.shared::cluster.global.mbarrier::complete_tx::bytes [%0], [%1, {%3, %5, %5, %5, %4}], [%2];"
    :: "r"(dst), "l"(m), "r"(bar), "r"(c0), "r"(c4), "r"(0) : "memory");
}
DEVI void tma_prefetch_2d(const CUtensorMap* m, int c0, int c1) {
  asm volatile("cp.async.bulk.prefetch.tensor.2d.L2.global [%0, {%1, %2}];" :: "l"(m), "r"(c0), "r"(c1) : "memory");
}
DEVI void tma_prefetch_5d(const CUtensorMap* m, int c0, int c4) {
  asm volatile("cp.async.bulk.prefetch.tensor.5d.L2.global [%0, {%1, %3, %3, %3, %2}];" :: "l"(m), "r"(c0), "r"(c4), "r"(0) : "memory");
}
#define ELECT "{.reg .pred p; elect.sync _|p, 0xffffffff;\n @p "
DEVI void e_expect_tx(uint32_t bar, uint32_t bytes) { asm volatile(ELECT "mbarrier.arrive.expect_tx.shared::cta.b64 _, [%0], %1;}" :: "r"(bar), "r"(bytes) : "memory"); }
DEVI void e_arrive(uint32_t bar) { asm volatile(ELECT "mbarrier.arrive.shared::cta.b64 _, [%0];}" :: "r"(bar) : "memory"); }
DEVI void e_arrive_cl(uint32_t bar) { asm volatile(ELECT "mbarrier.arrive.shared::cluster.b64 _, [%0];}" :: "r"(bar) : "memory"); }
constexpr uint64_t EVICT_NORMAL = 0x1000000000000000ull, EVICT_FIRST = 0x12F0000000000000ull;
DEVI void e_tma_2d(uint32_t dst, const CUtensorMap* m, int c0, int c1, uint32_t bar, uint64_t pol = EVICT_NORMAL) {
  asm volatile(ELECT "cp.async.bulk.tensor.2d.shared::cluster.global.mbarrier::complete_tx::bytes.L2::cache_hint [%0], [%1, {%3, %4}], [%2], %5;}"
    :: "r"(dst), "l"(m), "r"(bar), "r"(c0), "r"(c1), "l"(pol) : "memory");
}
DEVI void e_tma_2d_mc(uint32_t dst, const CUtensorMap* m, int c0, int c1, uint32_t bar, uint64_t pol = EVICT_NORMAL) {
  asm volatile(ELECT "cp.async.bulk.tensor.2d.shared::cluster.global.mbarrier::complete_tx::bytes.multicast::cluster.L2::cache_hint [%0], [%1, {%3, %4}], [%2], %5, %6;}"
    :: "r"(dst), "l"(m), "r"(bar), "r"(c0), "r"(c1), "h"((unsigned short)3), "l"(pol) : "memory");
}
DEVI void e_st_async32(uint32_t a, uint32_t x, uint32_t bar) {
  asm volatile(ELECT "st.async.weak.shared::cluster.mbarrier::complete_tx::bytes.b32 [%0], %1, [%2];}" :: "r"(a), "r"(x), "r"(bar) : "memory");
}
DEVI void e_tma_store_2d(const CUtensorMap* m, uint32_t src, int c0, int c1) {
  asm volatile(ELECT "cp.async.bulk.tensor.2d.global.shared::cta.bulk_group [%0, {%2, %3}], [%1];}" :: "l"(m), "r"(src), "r"(c0), "r"(c1) : "memory");
}
DEVI void e_flag_add(int* p, int v = 1) {
  asm volatile("{.reg .pred p; elect.sync _|p, 0xffffffff;\n fence.proxy.async.global; @p red.release.gpu.global.add.s32 [%0], %1;}" :: "l"(p), "r"(v) : "memory");
}
DEVI void e_flag_add_bulk(int* p, int v) {
  asm volatile(ELECT "red.relaxed.gpu.global.add.s32 [%0], %1;}" :: "l"(p), "r"(v) : "memory");
}
DEVI int e_ticket(int* p, int n = 1) { int v = 0; asm volatile(ELECT "atom.relaxed.gpu.global.add.s32 %0, [%1], %2;}" : "+r"(v) : "l"(p), "r"(n) : "memory"); __syncwarp(); return v; }
DEVI int bcast(int v) { return __reduce_max_sync(0xffffffffu, v); }
DEVI int ld_relaxed(const int* p) { int v; asm volatile("ld.relaxed.gpu.global.s32 %0, [%1];" : "=r"(v) : "l"(p) : "memory"); return v; }
DEVI int ld_acquire(const int* p) { int v; asm volatile("ld.acquire.gpu.global.s32 %0, [%1];" : "=r"(v) : "l"(p) : "memory"); return __shfl_sync(0xffffffffu, v, 0); }
DEVI void e_tma_3d(uint32_t dst, const CUtensorMap* m, int c0, int c1, int c2, uint32_t bar) {
  asm volatile(ELECT "cp.async.bulk.tensor.3d.shared::cluster.global.mbarrier::complete_tx::bytes [%0], [%1, {%3, %4, %5}], [%2];}"
    :: "r"(dst), "l"(m), "r"(bar), "r"(c0), "r"(c1), "r"(c2) : "memory");
}
DEVI void e_tma_5d(uint32_t dst, const CUtensorMap* m, int c0, int c4, uint32_t bar) {
  asm volatile(ELECT "cp.async.bulk.tensor.5d.shared::cluster.global.mbarrier::complete_tx::bytes [%0], [%1, {%3, %5, %5, %5, %4}], [%2];}"
    :: "r"(dst), "l"(m), "r"(bar), "r"(c0), "r"(c4), "r"(0) : "memory");
}
DEVI void e_bulk_g2s(uint32_t dst, const void* src, uint32_t bytes, uint32_t bar) {
  asm volatile(ELECT "cp.async.bulk.shared::cluster.global.mbarrier::complete_tx::bytes [%0], [%1], %2, [%3];}" :: "r"(dst), "l"(src), "r"(bytes), "r"(bar) : "memory");
}
DEVI void e_prefetch(const void* src, uint32_t bytes) {
  asm volatile(ELECT "cp.async.bulk.prefetch.L2.global [%0], %1;}" :: "l"(src), "r"(bytes) : "memory");
}
DEVI void bulk_commit() { asm volatile("cp.async.bulk.commit_group;" ::: "memory"); }
template<int N> DEVI void bulk_wait_read() { asm volatile("cp.async.bulk.wait_group.read %0;" :: "n"(N) : "memory"); }
template<int N> DEVI void bulk_wait() { asm volatile("cp.async.bulk.wait_group %0;" :: "n"(N) : "memory"); }
template<int ID, int N> DEVI void nbar_sync() { asm volatile("bar.sync %0, %1;" :: "n"(ID), "n"(N) : "memory"); }
template<int ID, int N> DEVI void nbar_arrive() { asm volatile("bar.arrive %0, %1;" :: "n"(ID), "n"(N) : "memory"); }
DEVI void nbar_sync_r(int id, int n) { asm volatile("bar.sync %0, %1;" :: "r"(id), "r"(n) : "memory"); }
DEVI void nbar_arrive_r(int id, int n) { asm volatile("bar.arrive %0, %1;" :: "r"(id), "r"(n) : "memory"); }
template<int R> DEVI void reg_inc() { asm volatile("setmaxnreg.inc.sync.aligned.u32 %0;" :: "n"(R)); }
template<int R> DEVI void reg_dec() { asm volatile("setmaxnreg.dec.sync.aligned.u32 %0;" :: "n"(R)); }
DEVI void wg_fence() { asm volatile("wgmma.fence.sync.aligned;" ::: "memory"); }
DEVI void wg_commit() { asm volatile("wgmma.commit_group.sync.aligned;" ::: "memory"); }
template<int N> DEVI void wg_wait() { asm volatile("wgmma.wait_group.sync.aligned %0;" :: "n"(N) : "memory"); }
DEVI uint32_t pack_bf16(float lo, float hi) { uint32_t r; asm("cvt.rn.bf16x2.f32 %0, %1, %2;" : "=r"(r) : "f"(hi), "f"(lo)); return r; }
DEVI float bf_lo(uint32_t v) { return __uint_as_float(v << 16); }
DEVI float bf_hi(uint32_t v) { return __uint_as_float(v & 0xffff0000u); }
DEVI uint32_t movmat(uint32_t a) { uint32_t r; asm volatile("movmatrix.sync.aligned.m8n8.trans.b16 %0, %1;" : "=r"(r) : "r"(a)); return r; }
DEVI void ldsm4(uint32_t addr, uint32_t& r0, uint32_t& r1, uint32_t& r2, uint32_t& r3) {
  asm volatile("ldmatrix.sync.aligned.m8n8.x4.shared.b16 {%0,%1,%2,%3}, [%4];" : "=r"(r0), "=r"(r1), "=r"(r2), "=r"(r3) : "r"(addr) : "memory");
}
DEVI void ldsm4t(uint32_t addr, uint32_t& r0, uint32_t& r1, uint32_t& r2, uint32_t& r3) {
  asm volatile("ldmatrix.sync.aligned.m8n8.x4.trans.shared.b16 {%0,%1,%2,%3}, [%4];" : "=r"(r0), "=r"(r1), "=r"(r2), "=r"(r3) : "r"(addr) : "memory");
}
DEVI void stsm4(uint32_t addr, uint32_t r0, uint32_t r1, uint32_t r2, uint32_t r3) {
  asm volatile("stmatrix.sync.aligned.m8n8.x4.shared.b16 [%0], {%1,%2,%3,%4};" :: "r"(addr), "r"(r0), "r"(r1), "r"(r2), "r"(r3) : "memory");
}
DEVI uint4 lds128(uint32_t a) { uint4 v; asm volatile("ld.shared.v4.u32 {%0,%1,%2,%3}, [%4];" : "=r"(v.x), "=r"(v.y), "=r"(v.z), "=r"(v.w) : "r"(a) : "memory"); return v; }
DEVI uint32_t lds32v(uint32_t a) { uint32_t v; asm volatile("ld.volatile.shared.u32 %0, [%1];" : "=r"(v) : "r"(a) : "memory"); return v; }
DEVI void sts32v(uint32_t a, uint32_t v) { asm volatile("st.volatile.shared.u32 [%0], %1;" :: "r"(a), "r"(v) : "memory"); }
DEVI void st_async128(uint32_t a, uint32_t x, uint32_t y, uint32_t z, uint32_t w, uint32_t bar) {
  asm volatile("st.async.weak.shared::cluster.mbarrier::complete_tx::bytes.v4.b32 [%0], {%1,%2,%3,%4}, [%5];" :: "r"(a), "r"(x), "r"(y), "r"(z), "r"(w), "r"(bar) : "memory");
}
DEVI void st_async32(uint32_t a, uint32_t x, uint32_t bar) {
  asm volatile("st.async.weak.shared::cluster.mbarrier::complete_tx::bytes.b32 [%0], %1, [%2];" :: "r"(a), "r"(x), "r"(bar) : "memory");
}
DEVI void st_cl128(bool own, uint32_t a, uint32_t x, uint32_t y, uint32_t z, uint32_t w, uint32_t bar) {
  asm volatile("{.reg .pred p; setp.ne.u32 p, %6, 0; @p st.shared.v4.b32 [%0], {%1,%2,%3,%4};\n"
               "@!p st.async.weak.shared::cluster.mbarrier::complete_tx::bytes.v4.b32 [%0], {%1,%2,%3,%4}, [%5];}"
               :: "r"(a), "r"(x), "r"(y), "r"(z), "r"(w), "r"(bar), "r"((uint32_t)own) : "memory");
}
DEVI void st_cl32(bool own, uint32_t a, uint32_t x, uint32_t bar) {
  asm volatile("{.reg .pred p; setp.ne.u32 p, %3, 0; @p st.shared.b32 [%0], %1;\n"
               "@!p st.async.weak.shared::cluster.mbarrier::complete_tx::bytes.b32 [%0], %1, [%2];}" :: "r"(a), "r"(x), "r"(bar), "r"((uint32_t)own) : "memory");
}
DEVI uint4 ldg_rlx128(const void* p) {
  uint4 v;
  asm volatile("ld.relaxed.gpu.global.v4.b32 {%0,%1,%2,%3}, [%4];" : "=r"(v.x), "=r"(v.y), "=r"(v.z), "=r"(v.w) : "l"(p) : "memory");
  return v;
}
DEVI void stg_rlx128(void* p, uint32_t x, uint32_t y, uint32_t z, uint32_t w) {
  asm volatile("st.relaxed.gpu.global.v4.b32 [%0], {%1,%2,%3,%4};" :: "l"(p), "r"(x), "r"(y), "r"(z), "r"(w) : "memory");
}
DEVI void stg128(void* p, uint32_t x, uint32_t y, uint32_t z, uint32_t w) {
  asm volatile("st.global.v4.b32 [%0], {%1,%2,%3,%4};" :: "l"(p), "r"(x), "r"(y), "r"(z), "r"(w) : "memory");
}
DEVI void stg_rlx64(void* p, uint32_t x, uint32_t y) { asm volatile("st.relaxed.gpu.global.v2.b32 [%0], {%1,%2};" :: "l"(p), "r"(x), "r"(y) : "memory"); }
DEVI void stg_rlx32(void* p, uint32_t x) { asm volatile("st.relaxed.gpu.global.b32 [%0], %1;" :: "l"(p), "r"(x) : "memory"); }
DEVI uint32_t clock32() { uint32_t c; asm volatile("mov.u32 %0, %%clock;" : "=r"(c) :: "memory"); return c; }
DEVI uint32_t gtime() { uint32_t c; asm volatile("mov.u32 %0, %%globaltimer_lo;" : "=r"(c) :: "memory"); return c; }
DEVI void wait_time(uint32_t t, int& budget) { while ((int)(gtime() - t) < 0 && --budget > 0) {} }
DEVI uint2 ldg_rlx64(const void* p) { uint2 v; asm volatile("ld.relaxed.gpu.global.v2.b32 {%0,%1}, [%2];" : "=r"(v.x), "=r"(v.y) : "l"(p) : "memory"); return v; }
DEVI void sts16(uint32_t a, uint32_t x) { asm volatile("st.shared.b16 [%0], %1;" :: "r"(a), "h"((unsigned short)x) : "memory"); }
DEVI void sts128(uint32_t a, uint32_t x) { asm volatile("st.shared.v4.b32 [%0], {%1,%1,%1,%1};" :: "r"(a), "r"(x) : "memory"); }
DEVI void arrive_if_eq(uint32_t bar, int a, int b) { asm volatile("{.reg .pred p; setp.eq.s32 p, %1, %2; @p mbarrier.arrive.shared::cta.b64 _, [%0];}" :: "r"(bar), "r"(a), "r"(b) : "memory"); }
DEVI void arrive_cl_if_eq(uint32_t bar, int a, int b) { asm volatile("{.reg .pred p; setp.eq.s32 p, %1, %2; @p mbarrier.arrive.shared::cluster.b64 _, [%0];}" :: "r"(bar), "r"(a), "r"(b) : "memory"); }
template<int ID, int N> DEVI bool nbar_or(bool x) {
  uint32_t r;
  asm volatile("{.reg .pred p, q; setp.ne.u32 p, %1, 0; bar.red.or.pred q, %2, %3, p; selp.u32 %0, 1, 0, q;}" : "=r"(r) : "r"((uint32_t)x), "n"(ID), "n"(N) : "memory");
  return __any_sync(0xffffffffu, r);
}
DEVI void spin_until(uint32_t t0, int d) { while ((int)(clock32() - t0) < d) {} }
DEVI void flag_wait(const int* p, int n, int& budget) {
  while (ld_acquire(p) < n && --budget > 0) __nanosleep(128);
  asm volatile("fence.proxy.async.global;" ::: "memory");
}

#define F4(C, o)  C(d[o+0]), C(d[o+1]), C(d[o+2]), C(d[o+3])
#define F8(C, o)  F4(C, o), F4(C, o+4)
#define F32(C, o) F8(C, o), F8(C, o+8), F8(C, o+16), F8(C, o+24)
#define R4  "{%0,%1,%2,%3}"
#define R8  "{%0,%1,%2,%3,%4,%5,%6,%7}"
#define R16 "{%0,%1,%2,%3,%4,%5,%6,%7,%8,%9,%10,%11,%12,%13,%14,%15}"
#define R20 "{%0,%1,%2,%3,%4,%5,%6,%7,%8,%9,%10,%11,%12,%13,%14,%15,%16,%17,%18,%19}"
#define R32 "{%0,%1,%2,%3,%4,%5,%6,%7,%8,%9,%10,%11,%12,%13,%14,%15,%16,%17,%18,%19,%20,%21,%22,%23,%24,%25,%26,%27,%28,%29,%30,%31}"
#define R64 "{%0,%1,%2,%3,%4,%5,%6,%7,%8,%9,%10,%11,%12,%13,%14,%15,%16,%17,%18,%19,%20,%21,%22,%23,%24,%25,%26,%27,%28,%29,%30,%31," \
  "%32,%33,%34,%35,%36,%37,%38,%39,%40,%41,%42,%43,%44,%45,%46,%47,%48,%49,%50,%51,%52,%53,%54,%55,%56,%57,%58,%59,%60,%61,%62,%63}"
template<uint32_t OFF, uint32_t LBO, uint32_t SBO, uint32_t SW, int T> struct Op {
  static constexpr uint32_t lo = (OFF >> 4) | ((LBO >> 4) << 16), hi = (SBO >> 4) | (SW << 30);
  static constexpr int t = T;
};
DEVI uint32_t desc_base(uint32_t addr) { return (addr & 0x3FFFF) >> 4; }
#define RS_ASM(SHAPE, REGS, A0, A1, A2, A3, B, LO, HI, T, SD) \
  "{.reg .b64 tb; .reg .b32 lb; add.u32 lb, " B ", " LO "; mov.b64 tb, {lb, " HI "};\n" \
  "wgmma.mma_async.sync.aligned." SHAPE ".f32.bf16.bf16 " REGS ", {" A0 "," A1 "," A2 "," A3 "}, tb, " SD ", 1, 1, " T ";}"
#define WG_RS(NAME, SHAPE, REGS, LIST, ...) \
  template<int ACC, class OB> DEVI void NAME(float* d, const uint32_t* a, uint32_t b) { \
    if (ACC) asm volatile(RS_ASM(SHAPE, REGS, __VA_ARGS__) \
      : LIST("+f") : "r"(a[0]), "r"(a[1]), "r"(a[2]), "r"(a[3]), "r"(b), "n"(OB::lo), "n"(OB::hi), "n"(OB::t), "n"(ACC & 1)); \
    else asm volatile(RS_ASM(SHAPE, REGS, __VA_ARGS__) \
      : LIST("=f") : "r"(a[0]), "r"(a[1]), "r"(a[2]), "r"(a[3]), "r"(b), "n"(OB::lo), "n"(OB::hi), "n"(OB::t), "n"(0)); \
  }
#define SS_ASM(SHAPE, REGS, A, B, LA, HA, TA, LB, HB, TB, SD) \
  "{.reg .b64 ta, tb; .reg .b32 la, lb; add.u32 la, " A ", " LA "; mov.b64 ta, {la, " HA "}; add.u32 lb, " B ", " LB "; mov.b64 tb, {lb, " HB "};\n" \
  "wgmma.mma_async.sync.aligned." SHAPE ".f32.bf16.bf16 " REGS ", ta, tb, " SD ", 1, 1, " TA ", " TB ";}"
#define WG_SS(NAME, SHAPE, REGS, LIST, ...) \
  template<int ACC, class OA, class OB> DEVI void NAME(float* d, uint32_t a, uint32_t b) { \
    if (ACC) asm volatile(SS_ASM(SHAPE, REGS, __VA_ARGS__) \
      : LIST("+f") : "r"(a), "r"(b), "n"(OA::lo), "n"(OA::hi), "n"(OA::t), "n"(OB::lo), "n"(OB::hi), "n"(OB::t), "n"(ACC & 1)); \
    else asm volatile(SS_ASM(SHAPE, REGS, __VA_ARGS__) \
      : LIST("=f") : "r"(a), "r"(b), "n"(OA::lo), "n"(OA::hi), "n"(OA::t), "n"(OB::lo), "n"(OB::hi), "n"(OB::t), "n"(0)); \
  }
#define L4(C)  F4(C, 0)
#define L8(C)  F8(C, 0)
#define L16(C) F8(C, 0), F8(C, 8)
#define L20(C) F8(C, 0), F8(C, 8), F4(C, 16)
#define L32(C) F32(C, 0)
WG_RS(wg_rs8, "m64n8k16", R4, L4, "%4", "%5", "%6", "%7", "%8", "%9", "%10", "%11", "%12")
WG_RS(wg_rs16, "m64n16k16", R8, L8, "%8", "%9", "%10", "%11", "%12", "%13", "%14", "%15", "%16")
WG_RS(wg_rs32, "m64n32k16", R16, L16, "%16", "%17", "%18", "%19", "%20", "%21", "%22", "%23", "%24")
WG_SS(wg_ss32, "m64n32k16", R16, L16, "%16", "%17", "%18", "%19", "%20", "%21", "%22", "%23", "%24")
WG_RS(wg_rs64, "m64n64k16", R32, L32, "%32", "%33", "%34", "%35", "%36", "%37", "%38", "%39", "%40")
WG_SS(wg_ss8, "m64n8k16", R4, L4, "%4", "%5", "%6", "%7", "%8", "%9", "%10", "%11", "%12")
WG_SS(wg_ss16, "m64n16k16", R8, L8, "%8", "%9", "%10", "%11", "%12", "%13", "%14", "%15", "%16")
WG_SS(wg_ss40, "m64n40k16", R20, L20, "%20", "%21", "%22", "%23", "%24", "%25", "%26", "%27", "%28")
WG_SS(wg_ss64, "m64n64k16", R32, L32, "%32", "%33", "%34", "%35", "%36", "%37", "%38", "%39", "%40")
#define L64(C) F32(C, 0), F32(C, 32)
WG_SS(wg_ss128, "m64n128k16", R64, L64, "%64", "%65", "%66", "%67", "%68", "%69", "%70", "%71", "%72")
template<int I> struct IC { __host__ __device__ constexpr operator int() const { return I; } };
template<int I, int N, class F> DEVI void sfor(F&& f) {
  if constexpr (I < N) { f(IC<I>{}); sfor<I + 1, N>(f); }
}

#define R_CL 6
namespace rec {
constexpr int NHI = 36, NLO = 5, NRS = NHI + NLO, NSS = 64 - NRS;
constexpr uint32_t WS = 0;
constexpr uint32_t WO = 2 * NSS * 2048;
constexpr uint32_t RING = WO + 65536;
constexpr uint32_t QB = RING + 40960, RG = 2080, POSQ = 0x64210, POSK = 0xB9753, POSV = 0xEDCA8;
#define JA 2
constexpr uint32_t WA = QB;
constexpr uint32_t OM = QB + 9 * RG, OMS = 2 * RG;
constexpr uint32_t OM2 = QB + 16384, OM2S = 2048;
constexpr uint32_t WH = QB + 20480;
constexpr uint32_t B_PART = QB + 15 * RG - 32;
constexpr uint32_t PM0 = QB + 16384, PM1 = QB + 15 * RG, PM2 = PM1 + 256;
constexpr uint32_t BARS = PM2 + 128;
constexpr uint32_t B_FULL = BARS, B_EMPTY = BARS + 40, B_MLAND = BARS + 80, B_QK = BARS + 112, B_V = BARS + 120, B_OM = BARS + 128,
                   B_WA = BARS + 136, B_SDONE = BARS + 144, B_BFREE = BARS + 152, B_W1 = PM1, B_W2 = PM1 + 8, B_WO = PM1 + 16;
constexpr uint32_t SMEM = BARS + 160;
static_assert(SMEM <= 232448 && QB % 1024 == 0, "smem map");
constexpr int R1 = (PM1 - WO) / 4096;
constexpr int NB_WO = 1, NB_ST = 2, NB_P = 3, NB_TR = 4, NB_X = 5, NB_G = 6, NB_G1 = 7, NB_G2 = 8, NB_G4 = 9, NB_S = 10;
__host__ __device__ constexpr bool is_lo(int j) { return j % 12 == 8; }
__host__ __device__ constexpr int lo_before(int j) { return (j + 3) / 12; }
__host__ __device__ constexpr int ss_before(int j) { return (j - lo_before(j)) * NSS / (64 - NLO); }
__host__ __device__ constexpr bool is_ss(int j) { return ss_before(j + 1) != ss_before(j); }
__host__ __device__ constexpr int reg_idx(int j) { return is_lo(j) ? NHI + lo_before(j) : j - ss_before(j) - lo_before(j); }
#define LOQ(i) ((0x12010 >> (4 * (i))) & 3)
template<int j> using OpW = Op<WS + ss_before(j) * 2048, 16, 1024, 1, 1>;
#define P_G1 1
#define P_G2 3
#define P_G2L 0
#define P_OS 1
#define P_NA 6
#define P_G4 10
#define P_G5 12
#define P_FW 0
#define P_SEND 0xff3f2f10u
#define P_WB 2
#define P_WOL 0
#define P_G4L 0
#define P_S1 1
#define P_S2 2
#define P_S0 3
#define P_MB 0
#define P_S4 5
#define P_S5 6
constexpr uint32_t SLOT1 = 0x32410324, USE1 = 0x22111110;
DEVI bool single(int s) { return s < LAG - 1 || s >= NSEG - 1; }
DEVI uint32_t flip(int s) { return (s < LAG - 1 ? s + 1 : s < NSEG - 1 ? LAG : LAG + s + 1) & 1; }
#define TUN(i, v) (v)
}
#define PROFW(wq, i)
DEVI uint32_t mapr(int h, uint32_t addr, int rank) { return mapa(addr, rank + (R_CL == 6 ? (h & 1) * 3 : 0)); }
template<int N> DEVI void pin(float* d) {
#pragma unroll
  for (int i = 0; i < N; i++) asm volatile("" : "+f"(d[i]) :: "memory");
}
DEVI void keep(const void* a) { asm volatile("{.reg .pred p; setp.eq.u64 p, %0, 0; vote.sync.any.pred p, p, 0xffffffff; @p exit;}" :: "l"(a) : "memory"); }
DEVI int lane_reg() { return __shfl_sync(0xffffffffu, threadIdx.x & 31, threadIdx.x & 31); }
#define LANE_NOW [[maybe_unused]] const int lane = lane0 + ((uint32_t)budget >> 30), g = lane >> 2, c = lane & 3

DEVI void rec_proj(const uint32_t sb, const int h, const int rank, const int w, const CUtensorMap* mW, const CUtensorMap* mWo, const uint32_t zero) {
  using namespace rec;
  const int lane0 = lane_reg(), wg = w >> 2, ww = w & 3;
  int budget = SPIN_BUDGET;
  uint32_t wr[NRS * 4];
  {
    LANE_NOW;
    const uint32_t wsw = ((lane & 7) + (lane >> 4) * 8) * 128 + (((ww * 2 + ((lane >> 3) & 1)) ^ (lane & 7)) << 4);
    mbar_wait(sb + B_W1, 0, budget);
#pragma unroll
    for (int r = 0; r < R1; r++) ldsm4t(sb + WO + (wg * R1 + r) * 2048 + wsw, wr[4*r], wr[4*r+1], wr[4*r+2], wr[4*r+3]);
    fence_proxy_async();
    nbar_sync<NB_ST, 256>();
    if (w == 0) {
      if (lane == 0) { mbar_expect_tx(sb + B_W2, (NRS - R1) * 4096); mbar_expect_tx(sb + B_WO, rank == 2 ? 65536 + 16384 + 8192 : 65536); }
      __syncwarp();
      for (int i = lane; i < 128; i += 32) {
        const int j = i & 63, t = i >> 6, r = reg_idx(j);
        if (!is_ss(j) && r >= R1) tma_load_2d(sb + RING + (t * (NRS - R1) + r - R1) * 2048, mW, h * DH + t * 64, j * 16, sb + B_W2);
      }
      const int t0 = (rank + 1) % 3;
      if (lane < 8) tma_load_2d(sb + WO + lane * 8192, mWo, (3 * ((lane >> 1) + (lane >> 1 >= JA)) + t0) * 64, h * DH + (lane & 1) * 64, sb + B_WO);
      else if (rank < 2 && lane < 10) tma_prefetch_2d(mWo, (3 * JA + t0) * 64, h * DH + (lane & 1) * 64);
      else if (rank == 2 && lane < 11) tma_load_2d(lane < 10 ? sb + WA + (lane - 8) * 8192 : sb + WH, mWo, lane < 10 ? 3 * JA * 64 : 15 * 64, h * DH + (lane > 8) * 64, sb + B_WO);
    }
    mbar_wait(sb + B_W2, 0, budget);
#pragma unroll
    for (int r = R1; r < NRS; r++) ldsm4t(sb + RING + (wg * (NRS - R1) + r - R1) * 2048 + wsw, wr[4*r], wr[4*r+1], wr[4*r+2], wr[4*r+3]);
    fence_proxy_async();
    cluster_arrive(); cluster_wait();
  }
  const uint32_t d0 = desc_base(sb), da = d0 + wg * (NSS * 128);
  const uint32_t pos = rank == 0 ? POSQ : rank == 1 ? POSK : POSV, bar = rank == 2 ? B_V : B_QK;
  uint32_t stg[3][4] = {}, pk[16] = {};
  auto stage = [&](uint32_t* t, int r) {
#pragma unroll
    for (int i = 0; i < 4; i++) asm volatile("xor.b32 %0, %1, %2;" : "+r"(t[i]) : "r"(wr[4 * r + i]), "r"(zero));
  };
#pragma unroll 1
  for (int s = -1; s < NSTEP; s++) {
    const uint32_t fl = flip(s);
    if (s >= 0) {
      float d[8];
      stage(stg[0], NHI);
      mbar_wait(sb + B_FULL, 0, budget);
      PROFW(0, 16);
      sfor<0, 8>([&](auto E) {
        constexpr int e = E, q = e >> 1;
        wg_fence();
        sfor<8 * e, 8 * e + 8>([&](auto J) {
          constexpr int j = J;
          typedef Op<RING + j * 512, 256, 128, 0, 1> OB;
          if constexpr (is_ss(j)) wg_ss16<j != 0, OpW<j>, OB>(d, da, d0);
          else wg_rs16<j != 0, OB>(d, is_lo(j) ? stg[LOQ(lo_before(j))] : wr + 4 * reg_idx(j), d0);
        });
        wg_commit();
        if constexpr (e == 0) { if (s > 0) mbar_wait(sb + B_BFREE, (s & 1) ^ 1, budget); }
        if constexpr (e > 0 && !(e & 1)) {
          wg_wait<1>();
          arrive_if_eq(sb + B_EMPTY + 8 * (q - 1), lane0, ww * 32);
        }
        if constexpr (e < 6 && !(e & 1)) sfor<lo_before(16 * q + 16), lo_before(16 * q + 32)>([&](auto I) { constexpr int i = I; stage(stg[LOQ(i)], NHI + i); });
        if constexpr (e < 6 && (e & 1) == P_FW) mbar_wait(sb + B_FULL + 8 * (q + 1), q ? fl : 0, budget);
        if constexpr (((P_SEND >> (4 * e)) & 15) < 4) {
          constexpr int n = (P_SEND >> (4 * e)) & 15;
          LANE_NOW;
          const uint32_t r = mapr(h, sb, n >> 1);
          uint32_t t[4];
#pragma unroll
          for (int i = 0; i < 4; i++) { if (n == 0) t[i] = pk[i]; else asm volatile("xor.b32 %0, %1, %2;" : "=r"(t[i]) : "r"(pk[4*n+i]), "r"(zero)); }
          st_cl128(rank == n >> 1, r + QB + ((pos >> (4 + 4 * c)) & 15) * RG + w * 256 + (n & 1) * 128 + g * 16, t[0], t[1], t[2], t[3], r + bar);
        }
      });
      LANE_NOW;
      const uint32_t dst = QB + (pos & 15) * RG + w * 256 + lane * 4;
      wg_wait<0>();
      pin<8>(d);
      {
        const uint32_t x0 = pack_bf16(d[0], d[1]), x1 = pack_bf16(d[2], d[3]), y0 = pack_bf16(d[4], d[5]), y1 = pack_bf16(d[6], d[7]);
        const uint32_t r = mapr(h, sb, rank == 0);
        if (rank < 2) { sts32v(sb + dst, rank ? y0 : x0); sts32v(sb + dst + 128, rank ? y1 : x1); fence_proxy_async(); }
        st_async32(r + dst, rank ? x0 : y0, r + bar); st_async32(r + dst + 128, rank ? x1 : y1, r + bar);
        if (rank < 2) e_arrive(sb + B_QK);
        else { const uint32_t r1 = mapr(h, sb, 1); st_async32(r1 + dst, y0, r1 + bar); st_async32(r1 + dst + 128, y1, r1 + bar); }
      }
      PROFW(0, 17);
      if (s == NSTEP - 1) break;
      arrive_if_eq(sb + B_EMPTY + 24, lane0, ww * 32);
    } else e_arrive(sb + B_EMPTY + 8 * ww);
    const bool gate = rank < 2 && s >= 0;
    if (single(s)) {
      float d[16];
      sfor<0, 8>([&](auto C) {
        constexpr int cc = C, sl = (SLOT1 >> (4 * cc)) & 15;
        if constexpr (cc == 0) mbar_wait(sb + B_FULL + 8 * sl, 0, budget);
        if constexpr (cc == P_S1) { if (gate) nbar_sync<NB_G1, 384>(); }
        if constexpr (cc == P_S2) { if (gate) nbar_sync<NB_G2, 384>(); }
        if constexpr (cc == P_S0) nbar_sync<NB_WO, 384>();
        if constexpr (cc == P_S4 || cc == P_S5) { if (gate && cc == (rank ? P_S5 : P_S4)) nbar_sync<NB_G4, 384>(); }
        if constexpr (lo_before(cc * 8 + 8) != lo_before(cc * 8)) stage(stg[0], NHI + lo_before(cc * 8));
        wg_fence();
        sfor<0, 8>([&](auto I) {
          constexpr int i = I, j = cc * 8 + i;
          typedef Op<RING + sl * 8192 + (i >> 2) * 4096 + (i & 3) * 32, 16, 1024, 1, 0> OB;
          if constexpr (is_ss(j)) wg_ss32<j != 0, OpW<j>, OB>(d, da, d0);
          else wg_rs32<j != 0, OB>(d, is_lo(j) ? stg[0] : wr + 4 * reg_idx(j), d0);
        });
        wg_commit();
        if constexpr (cc < 7) {
          constexpr int sn = (SLOT1 >> (4 * cc + 4)) & 15;
          mbar_wait(sb + B_FULL + 8 * sn, ((USE1 >> (4 * cc + 4)) & 1) ^ (sn >> 1 == 1 ? fl : 0), budget);
        }
        wg_wait<0>();
        arrive_if_eq(sb + B_EMPTY + 8 * sl, lane0, ww * 32);
      });
      pin<16>(d);
      PROFW(0, 20);
#pragma unroll
      for (int i = 0; i < 8; i++) pk[i] = pk[8 + i] = pack_bf16(d[4 * (i & 3) + ((i >> 1) & 2)], d[4 * (i & 3) + ((i >> 1) & 2) + 1]);
      continue;
    }
    float d[32];
    sfor<0, 16>([&](auto C) {
      constexpr int cc = C, sl = (cc + 4) % 5;
      if constexpr (cc == 0) mbar_wait(sb + B_FULL + 8 * sl, 0, budget);
      if constexpr (cc == P_G1) { if (gate) nbar_sync<NB_G1, 384>(); }
      if constexpr (cc == P_G2) { if (gate) nbar_sync<NB_G2, 384>(); }
      if constexpr (cc == P_NA) {
        PROFW(0, 18);
        nbar_sync<NB_WO, 384>();
      }
      if constexpr (cc == P_G4 || cc == P_G5) { if (gate && cc == (rank ? P_G5 : P_G4)) nbar_sync<NB_G4, 384>(); }
      wg_fence();
      sfor<0, 4>([&](auto I) {
        constexpr int i = I, j = cc * 4 + i;
        typedef Op<RING + sl * 8192 + i * 32, 16, 1024, 1, 0> OB;
        if constexpr (is_ss(j)) wg_ss64<j != 0, OpW<j>, OB>(d, da, d0);
        else wg_rs64<j != 0, OB>(d, is_lo(j) ? stg[0] : wr + 4 * reg_idx(j), d0);
      });
      wg_commit();
      if constexpr (cc == P_NA) PROFW(0, 19);
      if constexpr (cc < 15) {
        if constexpr (is_lo(cc * 4 + 4)) stage(stg[0], reg_idx(cc * 4 + 4));
        mbar_wait(sb + B_FULL + 8 * ((sl + 1) % 5), ((cc + 5) / 5 + (sl == 1 || sl == 2 ? LAG : 0)) & 1, budget);
      }
      wg_wait<0>();
      arrive_if_eq(sb + B_EMPTY + 8 * sl, lane0, ww * 32);
    });
    pin<32>(d);
    PROFW(0, 20);
#pragma unroll
    for (int i = 0; i < 16; i++) pk[i] = pack_bf16(d[16 * (i >> 3) + 4 * (i & 3) + ((i >> 1) & 2)], d[16 * (i >> 3) + 4 * (i & 3) + ((i >> 1) & 2) + 1]);
  }
}

DEVI float softmax_row(float* v, uint32_t* p) {
  constexpr float SC = 0.08838834764831845f * 1.4426950408889634f;
  float m = fmaxf(fmaxf(fmaxf(fmaxf(v[0], v[1]), fmaxf(v[2], v[3])), fmaxf(fmaxf(v[4], v[5]), fmaxf(v[6], v[7]))), fmaxf(v[8], v[9]));
  m = fmaxf(m, __shfl_xor_sync(0xffffffffu, m, 1));
  m = fmaxf(m, __shfl_xor_sync(0xffffffffu, m, 2));
  const float ms = -m * SC, mh = fmaf(m, -SC, -1.f);
#pragma unroll
  for (int i = 0; i < 10; i++) asm("ex2.approx.ftz.f32 %0, %1;" : "=f"(v[i]) : "f"(fmaf(v[i], SC, i < 8 ? ms : mh)));
#pragma unroll
  for (int n = 0; n < 5; n++) p[n] = pack_bf16(v[2*n], v[2*n+1]);
  return fmaf(v[8] + v[9], 2.f, ((v[0] + v[1]) + (v[2] + v[3])) + ((v[4] + v[5]) + (v[6] + v[7])));
}

template<bool ATT>
DEVI void rec_attn(const uint32_t sb, int h, int rank, int w, const bf16* __restrict__ Wo, const bf16* __restrict__ mem0) {
  using namespace rec;
  const int lane0 = lane_reg();
  int budget = SPIN_BUDGET;
  constexpr int NT = ATT ? 5 : 6;
  uint32_t wl[16];
  if (!ATT) {
    LANE_NOW;
#pragma unroll
    for (int i = 0; i < 16; i++) {
      const int dh = 8 * (i >> 1) + 2 * c;
      const unsigned short* p = (const unsigned short*)Wo + (size_t)(h * DH + dh) * DM + 15 * 64 + 16 * w + 8 * (i & 1) + g;
      wl[i] = p[0] | (uint32_t)p[DM] << 16;
    }
  }
  cluster_arrive(); cluster_wait();
  const uint32_t d0 = desc_base(sb);
  uint32_t pph = 0;
#pragma unroll 1
  for (int s = -1; s < NSTEP; s++) {
    asm volatile("" : "+r"(h), "+r"(rank), "+r"(w));
    const uint32_t sp = s & 1;
    const int t0 = ATT ? rank + 1 : 0;
    const bool more = s + 1 < NSTEP;
    if (s == 0) mbar_wait(sb + B_WO, 0, budget);
    float hold[10] = {0, 0, 0, 0, 0, 0, 0, 0, 0, 0};
    if (ATT && s >= 0) {
      float sc[20];
      LANE_NOW;
      mbar_wait(sb + B_QK, sp, budget);
      PROFW(0, 1);
      fence_proxy_async();
      wg_fence();
      sfor<0, 8>([&](auto K) { constexpr int k = K; wg_ss40<k != 0, Op<QB + k * 256, 128, RG, 0, 1>, Op<QB + 3 * RG + k * 256, 128, 2 * RG, 0, 1>>(sc, d0, d0); });
      wg_commit();
      if (P_G1 < 16 && more) nbar_arrive<NB_G1, 384>();
      mbar_wait(sb + B_V, sp, budget);
      wg_wait<0>();
      pin<20>(sc);
      if (w == 3 && more) nbar_arrive<NB_S, 64>();
      PROFW(1, 2);
      if (w == 0) {
        uint32_t p[5];
        float v[10];
#pragma unroll
        for (int i = 0; i < 10; i++) v[i] = sc[4 * (i >> 1) + (i & 1)];
        softmax_row(v, p);
        const uint32_t a = sb + lane * 4;
        sts32v(a + PM0, p[0]); sts32v(a + PM0 + 128, p[1]); sts32v(a + PM1, p[2]); sts32v(a + PM1 + 128, p[3]); sts32v(a + PM2, p[4]);
      }
      if (more) {
        float rs[4], ot[2][4];
        uint32_t one[4];
#pragma unroll
        for (int i = 0; i < 4; i++) one[i] = 0x3F803F80u + ((uint32_t)budget >> (31 - i));
        typedef Op<PM0, 128, 128, 0, 0> P0; typedef Op<PM1, 128, 128, 0, 0> P1; typedef Op<PM2, 0, 128, 0, 0> P2;
        fence_proxy_async();
        nbar_sync<NB_P, 128>();
        PROFW(0, 3);
        wg_fence();
        wg_rs8<0, P0>(rs, one, d0); wg_rs8<1, P1>(rs, one, d0); wg_rs8<1, P2>(rs, one, d0);
        wg_commit();
        sfor<0, 2>([&](auto T) {
          constexpr int t = T;
          wg_ss8<0, Op<QB + 8 * RG + t * 1024, 2 * RG, 128, 0, 0>, P0>(ot[t], d0, d0);
          wg_ss8<1, Op<QB + 12 * RG + t * 1024, RG, 128, 0, 0>, P1>(ot[t], d0, d0);
          wg_ss8<1, Op<QB + 14 * RG + t * 1024, 0, 128, 0, 0>, P2>(ot[t], d0, d0);
        });
        wg_commit();
        if (P_G2 < 16 && !P_G2L) nbar_arrive<NB_G2, 384>();
        const uint32_t oa = w * 256 + lane * 4, r1 = mapr(h, sb, rank ^ 1), r2 = mapr(h, sb, 2);
        mbar_wait(sb + B_SDONE, sp, budget);
        wg_wait<1>();
        pin<4>(rs);
        float i0, i1;
        asm volatile("rcp.approx.ftz.f32 %0, %1;" : "=f"(i0) : "f"(rs[0]));
        asm volatile("rcp.approx.ftz.f32 %0, %1;" : "=f"(i1) : "f"(rs[1]));
        wg_wait<0>();
        pin<4>(ot[0]); pin<4>(ot[1]);
        uint32_t x[4];
#pragma unroll
        for (int j = 0; j < 4; j++) {
          x[j] = pack_bf16(ot[j >> 1][2 * (j & 1)] * i0, ot[j >> 1][2 * (j & 1) + 1] * i1);
          sts32v(sb + OM + rank * OMS + oa + (j >> 1) * 1024 + (j & 1) * 128, x[j]);
        }
        fence_proxy_async();
#pragma unroll
        for (int j = 0; j < 8; j++) {
          const int i = P_OS ? j >> 1 : j & 3;
          if (P_OS ? j & 1 : j >> 2) st_async32(r1 + OM + rank * OMS + oa + (i >> 1) * 1024 + (i & 1) * 128, x[i], r1 + B_OM);
          else st_async32(r2 + OM2 + rank * OM2S + oa + (i >> 1) * 1024 + (i & 1) * 128, x[i], r2 + B_OM);
        }
        e_arrive(sb + B_OM);
        if (P_G2 < 16 && P_G2L) nbar_arrive<NB_G2, 384>();
        PROFW(0, 4);
      }
#pragma unroll
      for (int i = 0; i < 10; i++) hold[i] = w ? sc[4 * (i >> 1) + (i & 1)] : sc[4 * (i >> 1) + 2 + (i & 1)];
    }
    if (more && s >= 0) {
      LANE_NOW;
      char* const pw = (char*)g_part + (uint32_t)((t0 * 16 + w * 4 + (lane >> 3)) * 4096 + h * 128 + ((lane ^ h) & 7) * 16);
      mbar_wait(sb + B_OM, sp, budget);
      if (w == 0) nbar_arrive<NB_G, 128>();
      PROFW(1, 5);
      if (!ATT) fence_proxy_async();
      float acc[3][8];
      auto store = [&](auto J) {
        constexpr int j = J;
        float* d = acc[j % 3];
        pin<8>(d);
        uint32_t x[4];
#pragma unroll
        for (int i = 0; i < 4; i++) { const uint32_t m = (h >> 3) == i; x[i] = (pack_bf16(d[2*i], d[2*i+1]) & ~m) | (m & ~sp); }
        stg_rlx128(pw + j * (48 * 4096), x[0], x[1], x[2], x[3]);
        if constexpr (ATT && j == JA) nbar_arrive<NB_TR, 160>();
        if constexpr (j == 2) PROFW(3, 26);
      };
      sfor<0, NT>([&](auto J) {
        constexpr int j = J;
        if constexpr (ATT && j == JA) { mbar_wait(sb + B_WA, sp, budget); PROFW(2, 0); }
        wg_fence();
        sfor<0, 8>([&](auto K) {
          constexpr int k = K;
          typedef Op<(ATT ? OM : OM2) + k * 256, 128, ATT ? OMS : OM2S, 0, 1> OB;
          if constexpr (j == 5 && k < 4) wg_rs16<k ? 1 : 2, OB>(acc[j % 3], wl + 4 * k, d0);
          else wg_ss16<k ? 1 : j < 3 ? 0 : 2, Op<(j == JA ? WA : j < 5 ? WO + (j - (j > JA)) * 16384 : WH - 8192) + k * 2048, 16, 1024, 1, 1>, OB>(acc[j % 3], d0, d0);
        });
        wg_commit();
        if constexpr (j == 0) { if (w == 3) e_expect_tx(sb + B_OM, ATT ? 2048 : 4096); }
        if constexpr (j == NT - 1 && !P_WOL) nbar_arrive<NB_WO, 384>();
        if constexpr (j > 0 && j != P_WB + 1) { wg_wait<1>(); store(IC<j - 1>{}); }
        if constexpr (j == P_WB || j == NT - 1) { wg_wait<0>(); store(IC<j>{}); }
        if constexpr (j == P_WB) {
          const uint32_t t = clock32();
          if (ATT) {
            if (w == 3 && lane < 14) sts128(sb + PM1 + lane * 16, (lane >> 1) == 3 ? 0x3F803F80u : 0);
            if (w == 3 || P_MB) fence_proxy_async();
            nbar_sync<NB_P, 128>();
          } else if (P_MB) fence_proxy_async();
          spin_until(t, TUN(8, 100));
        }
      });
      if (P_WOL) { spin_until(clock32(), TUN(9, 0)); nbar_arrive<NB_WO, 384>(); }
    } else if (more) nbar_arrive<NB_WO, 384>();
    PROFW(0, 6);
    asm volatile("" : "+r"(h), "+r"(rank), "+r"(w));
#pragma unroll 1
    for (int pass = 0; ATT && pass < 2; pass++)
    if (pass != rank) {
      LANE_NOW;
      const int lim = 8 * (g >> 1) + (g & 1) + 2 * w - 8 * c;
      uint32_t p[5];
#pragma unroll
      for (int i = 0; i < 8; i++) hold[2+i] = i <= lim ? hold[2+i] : -INFINITY;
      const float psum = softmax_row(hold, p);
#pragma unroll
      for (int i = 0; i < 5; i++) hold[i] = __uint_as_float(p[i]);
      hold[5] = psum;
    } else if (more) {
      LANE_NOW;
      const int blk = rank * 32 + h;
      char* const mw = (char*)g_mem + (uint32_t)(sp * 32768 + blk * 512 + w * 128 + lane * 4);
      uint32_t v0 = 0;
      if (s == -1 || (s == LAG - 1 && (w & 1))) {
        const unsigned short* q = (const unsigned short*)mem0 + c * 2 * DM + blk * 16 + (w >> 1) * 8 + g;
        v0 = q[0] | (uint32_t)q[DM] << 16;
        if (v0 == 0) v0 = 0x8000u;
      }
      keep(mw);
      if (s >= 0) {
        const uint32_t ca = sb + WA + lane * 128 + (((2 * w) ^ lane) & 7) * 16 + (lane >> 3) * 4;
        const uint32_t sa = sb + OM + (((g >> 1) & 1) * 2 + (g >> 2)) * 128 + (2 * c + (w >> 1)) * 16 + (w & 1) * 8 + (g & 1) * 2;
        const bool g4l = P_G4L == 1 || (P_G4L == 2 && single(s));
        for (bool first = true; ; first = false) {
          float r[4];
          mbar_wait(sb + B_PART, pph, budget);
          PROFW(0, 11);
          pph ^= 1;
          wg_fence();
          sfor<0, 8>([&](auto K) { constexpr int k = K; wg_ss8<k != 0, Op<WA + k * 2048, 16, 1024, 1, 1>, Op<PM1 + (6 - (k & 6)) * 16, 0, 128, 0, 0>>(r, d0, d0); });
          wg_commit();
          if (!g4l && first) nbar_arrive<NB_G4, 384>();
          const uint32_t x0 = lds32v(ca), x1 = lds32v(ca + 4096), x2 = lds32v(ca + 8192), x3 = lds32v(ca + 12288);
          bool bad = __any_sync(0xffffffffu, (sp ? x0 | x1 | x2 | x3 : ~(x0 & x1 & x2 & x3)) & 1) && budget > 0;
          wg_wait<0>();
          pin<4>(r);
          uint32_t y = pack_bf16(r[0], r[2]);
          y |= (y & 0xffffu) ? 0 : 0x8000u;
          y |= (y >> 16) ? 0 : 0x80000000u;
          if (bad) y = 0;
          sts16(sa, y); sts16(sa + 4, y >> 16);
          nbar_sync<NB_P, 128>();
          y = lds32v(sb + OM + w * 128 + lane * 4);
          const bool ok = !__any_sync(0xffffffffu, y == 0);
          if (ok) stg_rlx32(mw, v0 ? v0 : y);
          if (g4l && first) nbar_arrive<NB_G4, 384>();
          if (ok) break;
          nbar_sync<NB_P, 128>();
          budget--;
          if (w == 0) { e_expect_tx(sb + B_PART, 16384); e_bulk_g2s(sb + WA, (const char*)g_part + blk * 16384, 16384, sb + B_PART); }
          __syncwarp();
        }
        nbar_sync<NB_P, 128>();
        if (w < 2) e_arrive_cl(mapr(h, sb + B_BFREE, w));
      } else stg_rlx32(mw, v0);
      stg_rlx32(mw + (sp ? -32768 : 32768), 0);
      PROFW(1, 8);
    }
    if (ATT && s >= 0) {
      const int seg = s - (rank ? LAG : 0);
      const bool act = (unsigned)seg < NSEG;
      LANE_NOW;
      uint32_t a[12];
#pragma unroll
      for (int i = 0; i < 12; i++) a[i] = __float_as_uint(hold[i < 10 ? i >> 1 : 4]) + ((uint32_t)budget >> (31 - (i & 3)));
      float o[32], inv, psum = hold[5];
      char* const ob = (char*)g_o[rank] + ((size_t)(seg * 32 + 8 * (g >> 1) + (g & 1) + 2 * w) * (NH * DH) + h * DH + c * 8) * 2;
      sfor<0, 2>([&](auto HF) {
        constexpr int hf = HF;
        wg_fence();
        wg_rs64<hf * 2, Op<QB + 8 * RG + hf * 1024, 2 * RG, 128, 0, 0>>(o, a, d0);
        wg_rs64<1, Op<QB + 12 * RG + hf * 1024, RG, 128, 0, 0>>(o, a + 4, d0);
        wg_rs64<1, Op<QB + 14 * RG + hf * 1024, 0, 128, 0, 0>>(o, a + 8, d0);
        wg_commit();
        if constexpr (hf == 0) {
          psum += __shfl_xor_sync(0xffffffffu, psum, 1);
          psum += __shfl_xor_sync(0xffffffffu, psum, 2);
          asm("rcp.approx.ftz.f32 %0, %1;" : "=f"(inv) : "f"(psum));
        }
        wg_wait<0>();
        pin<32>(o);
        if constexpr (hf == 1) { if (w == 2 && more) e_arrive_cl(mapr(h, sb + B_BFREE, 2)); }
        if (act) {
#pragma unroll
          for (int i = 0; i < 2; i++)
            stg128(ob + (hf * 2 + i) * 64, pack_bf16(o[16*i] * inv, o[16*i+1] * inv), pack_bf16(o[16*i+4] * inv, o[16*i+5] * inv),
                   pack_bf16(o[16*i+8] * inv, o[16*i+9] * inv), pack_bf16(o[16*i+12] * inv, o[16*i+13] * inv));
        }
      });
      PROFW(0, 7);
      if (act && (seg & 3) == 3) {
        nbar_sync<NB_P, 128>();
        if (w == 0) e_flag_add(g_fl.dep + grp(0, rank, seg >> 2), 4);
      }
    } else if (!ATT && w == 3) {
      if (s + 4 < NSEG) e_prefetch(g_xn[0] + (size_t)((s + 4) * 32 + h) * DM, 2048);
    }
  }
  cluster_arrive(); cluster_wait();
  char* const pw = (char*)g_part + (size_t)((ATT ? rank + 1 : 0) * 16 + w * 4 + (lane0 >> 3)) * 4096 + h * 128 + (lane0 & 7) * 16;
#pragma unroll
  for (int j = 0; j < NT; j++) stg_rlx128(pw + j * (48 * 4096), 0, 0, 0, 0);
}

DEVI void rec_load(const uint32_t sb, const int h, const int rank, const int w, const CUtensorMap* mX, const CUtensorMap* mWo) {
  using namespace rec;
  static_assert(((NSTEP - 1) & 31) > 3, "stale time stamps of the previous launch never match");
  const int lane0 = lane_reg(), mq = (w + 3) & 3;
  int budget = SPIN_BUDGET;
  if (w == 0) { e_flag_add(g_fl.xn[0][0]); flag_wait(g_fl.xn[0][0], 96, budget); }
  bool late = false;
  cluster_arrive(); cluster_wait();
  if (w == 0) { if (lane0 < 4) mbar_arrive(sb + B_FULL + 8 * lane0); __syncwarp(); }
  uint32_t lph = 0;
#pragma unroll 1
  for (int s = -1; s < NSTEP - 1; s++) {
    if (w == 0) {
      if (late) flag_wait(g_fl.xn[1][(s + 1 - LAG) >> 2], 128, budget);
      if (single(s)) {
#pragma unroll 1
        for (int i = 0; i < 8; i++) {
          const int k = i < 5 ? (0x21430 >> (4 * i)) & 15 : i;
          const int sl = (SLOT1 >> (4 * k)) & 15;
          mbar_wait(sb + B_EMPTY + 8 * sl, (((USE1 >> (4 * k)) ^ (sl >> 1 == 1 ? flip(s) : 0)) & 1) ^ 1, budget);
          e_expect_tx(sb + B_FULL + 8 * sl, 8192);
          e_tma_3d(sb + RING + sl * 8192, mX + 1, 0, (s + 1 + (s < LAG ? 0 : NSTEP)) * 32, k * 2, sb + B_FULL + 8 * sl);
        }
      } else {
        int sl = 4, ph = 1;
#pragma unroll 1
        for (int i = 0; i < 16; i++) {
          mbar_wait(sb + B_EMPTY + 8 * sl, ph ^ (sl >> 1 & LAG & 1), budget);
          e_expect_tx(sb + B_FULL + 8 * sl, 8192);
          e_tma_3d(sb + RING + sl * 8192, mX, i * 64, (s + 1) * 32, 0, sb + B_FULL + 8 * sl);
          if (++sl == 5) { sl = 0; ph ^= 1; }
        }
      }
      nbar_arrive<NB_X, 128>();
      const int sn = s + 2 - LAG;
      late = (sn & 3) == 0 && (unsigned)sn < NSEG && ld_acquire(g_fl.xn[1][sn >> 2]) < 128;
      asm volatile("fence.proxy.async.global;" ::: "memory");
    }
    uint32_t t = gtime();
    if (s >= 0) {
      uint2 a;
      if (w == 2 && rank < 2) {
        nbar_sync<NB_S, 64>();
        e_expect_tx(sb + B_WA, 16384);
        e_tma_2d(sb + WA, mWo, (3 * JA + 1 + rank) * 64, h * DH, sb + B_WA);
        e_tma_2d(sb + WA + 8192, mWo, (3 * JA + 1 + rank) * 64, h * DH + 64, sb + B_WA);
        e_arrive_cl(mapr(h, sb + B_SDONE, rank ^ 1));
        stg_rlx32(&g_ann[s & 1][lane0][h * 2 + rank], (gtime() & ~31u) | ((s + 1) & 31));
        e_expect_tx(sb + B_QK, 10240);
        e_expect_tx(sb + B_V, 10240);
      }
      if (w) nbar_sync<NB_G, 128>();
      do { a = ldg_rlx64(&g_ann[s & 1][h][lane0 * 2]); } while (__any_sync(0xffffffffu, ((a.x ^ (s + 1)) | (a.y ^ (s + 1))) & 31) && --budget > 0);
      t += __reduce_max_sync(0xffffffffu, max((int)(a.x - t), (int)(a.y - t)));
      t &= ~31u;
      PROFW(1, 12);
      if (w == 1 && rank < 2) {
        nbar_sync<NB_TR, 160>();
        wait_time(t + (single(s) ? (rank ? TUN(11, 1650) : TUN(10, 1250)) : rank ? TUN(1, 1750) : TUN(0, 1350)), budget);
        e_expect_tx(sb + B_PART, 16384);
        e_bulk_g2s(sb + WA, (const char*)g_part + (rank * 32 + h) * 16384, 16384, sb + B_PART);
        PROFW(1, 21);
      }
      t += single(s) ? (mq == 0 ? TUN(12, 2200) : mq == 1 ? TUN(13, 2300) : mq == 2 ? TUN(14, 2700) : TUN(15, 2800))
                     : (mq == 0 ? TUN(2, 2350) : mq == 1 ? TUN(3, 2450) : mq == 2 ? TUN(4, 2850) : TUN(5, 2950));
    }
    if (w) nbar_sync<NB_X, 128>();
    mbar_wait(sb + B_EMPTY + 8 * mq, mq >= 2 ? flip(s + 1) ^ 1 : 1, budget);
    PROFW(1, 9);
    wait_time(t, budget);
    PROFW(1, 22); PROFW(3, 23);
    while (true) {
      e_expect_tx(sb + B_MLAND + 8 * mq, 8192);
      e_bulk_g2s(sb + RING + mq * 8192, (const char*)g_mem + (s & 1) * 32768 + mq * 8192, 8192, sb + B_MLAND + 8 * mq);
      const uint32_t a = sb + RING + mq * 8192 + lane0 * 32 + (lane0 >> 2) * 4;
      mbar_wait(sb + B_MLAND + 8 * mq, lph, budget);
      lph ^= 1;
      PROFW(1, 24);
      uint32_t mn = 0xffffffffu;
#pragma unroll
      for (int i = 0; i < 8; i++) mn = min(mn, lds32v(a + i * 1024));
      if (!__any_sync(0xffffffffu, mn == 0) || --budget <= 0) break;
    }
    e_arrive(sb + B_FULL + 8 * mq);
    PROFW(1, 10); PROFW(2, 13); PROFW(3, 14); PROFW(0, 15);
  }
}

DEVI void ln_row(const uint4* u, bf16* dst, int lane) {
  const uint32_t* x = (const uint32_t*)u;
  float mean = 0, q = 0;
#pragma unroll
  for (int i = 0; i < 16; i++) mean += bf_lo(x[i]) + bf_hi(x[i]);
  mean *= 1.f / 32;
#pragma unroll
  for (int i = 0; i < 16; i++) { const float a = bf_lo(x[i]) - mean, b = bf_hi(x[i]) - mean; q = fmaf(a, a, fmaf(b, b, q)); }
#pragma unroll
  for (int o = 1; o < 32; o *= 2) {
    const float m2 = __shfl_xor_sync(0xffffffffu, mean, o), q2 = __shfl_xor_sync(0xffffffffu, q, o), dl = m2 - mean;
    q = fmaf(dl * dl, 16.f * o, q + q2);
    mean = 0.5f * (mean + m2);
  }
  const float rs = rsqrtf(q * (1.f / DM) + 1e-5f), mr = -mean * rs;
#pragma unroll
  for (int i = 0; i < 4; i++) {
    uint32_t y[4];
#pragma unroll
    for (int k = 0; k < 4; k++) y[k] = pack_bf16(fmaf(bf_lo(x[4*i+k]), rs, mr), fmaf(bf_hi(x[4*i+k]), rs, mr));
    stg128((uint4*)dst + i * 32 + lane, y[0], y[1], y[2], y[3]);
  }
}

struct RecMaps { CUtensorMap w[3], wo, x[2]; };
__global__ void __cluster_dims__(R_CL, 1, 1) __launch_bounds__(512, 1)
rec_kernel(const __grid_constant__ RecMaps M, const bf16* __restrict__ Wo, const bf16* __restrict__ mem0, const bf16* __restrict__ x, uint32_t zero) {
  using namespace rec;
  extern __shared__ __align__(1024) uint8_t smem[];
  const uint32_t sb = smem_u32(smem);
  const int tid = threadIdx.x, warp = __shfl_sync(0xffffffffu, tid >> 5, 0), wg = warp >> 2, lane = tid & 31;
  const int h = blockIdx.x / 3, rank = blockIdx.x % 3;
  if (warp == 0) {
    if (lane < 20) mbar_init(sb + BARS + 8 * lane, (lane >= 5 && lane < 10) || lane == 19 ? 2 : lane == 14 ? 9 : lane == 16 && rank < 2 ? 5 : 1);
    else if (lane < 23) mbar_init(sb + B_W1 + 8 * (lane - 20), 1);
    else if (lane == 23) mbar_init(sb + B_PART, 1);
    fence_mbar_init();
    __syncwarp();
    if (lane == 0) { mbar_expect_tx(sb + B_W1, (NSS + R1) * 4096); mbar_expect_tx(sb + B_QK, 10240); mbar_expect_tx(sb + B_V, 10240); mbar_expect_tx(sb + B_OM, rank < 2 ? 2048 : 4096); }
    __syncwarp();
    for (int i = lane; i < 128; i += 32) {
      const int j = i >> 1, t = i & 1, r = reg_idx(j);
      if (is_ss(j)) tma_load_2d(sb + WS + (t * NSS + ss_before(j)) * 2048, &M.w[rank], h * DH + t * 64, j * 16, sb + B_W1);
      else if (r < R1) tma_load_2d(sb + WO + (t * R1 + r) * 2048, &M.w[rank], h * DH + t * 64, j * 16, sb + B_W1);
      else tma_prefetch_2d(&M.w[rank], h * DH + t * 64, j * 16);
    }
  } else if (warp == 1) {
    constexpr int N = (sizeof(Flags) - sizeof(g_fl.xn)) / 16;
    if (lane < 8 && blockIdx.x * 8 + lane < N) ((uint4*)g_fl.dep)[blockIdx.x * 8 + lane] = make_uint4(0, 0, 0, 0);
    static_assert(N <= 96 * 8, "flag reset");
    if (blockIdx.x < 64) ((uint4*)g_stat[4])[blockIdx.x * 64 + lane] = ((uint4*)g_stat[4])[blockIdx.x * 64 + 32 + lane] = make_uint4(0, 0, 0, 0);
    __threadfence();
    __syncwarp();
    asm volatile("griddepcontrol.launch_dependents;" ::: "memory");
  } else if (warp >= 5 && blockIdx.x * 11 + warp - 5 < SEQ / 2) {
    const size_t o = (size_t)(blockIdx.x * 11 + warp - 5) * (2 * DM);
    uint4 u[8];
#pragma unroll
    for (int i = 0; i < 8; i++) u[i] = __ldg((const uint4*)(x + o) + i * 32 + lane);
    ln_row(u, g_xn[0] + o, lane);
    ln_row(u + 4, g_xn[0] + o + DM, lane);
  }
  __syncthreads();
  if (wg == 3) {
    reg_dec<24>();
    rec_load(sb, h, rank, warp & 3, M.x, &M.wo);
    cluster_arrive(); cluster_wait();
  } else if (wg == 2) {
    reg_dec<72>();
    if (rank < 2) rec_attn<true>(sb, h, rank, warp & 3, Wo, mem0);
    else rec_attn<false>(sb, h, rank, warp & 3, Wo, mem0);
  } else {
    reg_inc<208>();
    rec_proj(sb, h, rank, warp, &M.w[rank], &M.wo, zero);
    cluster_arrive(); cluster_wait();
  }
}

namespace gm {
constexpr int STAGES = 6, STAGE_BYTES = 32768;
constexpr uint32_t SO = STAGES * STAGE_BYTES, B_FULL = SO + 32768, B_TRIG = B_FULL + 56, B_EMPTY = B_FULL + 64, B_JOB = B_FULL + 128,
                   B_MSG = B_FULL + 144, B_XF = B_FULL + 160, B_SF = B_FULL + 176, JOB = B_FULL + 192, MSG = JOB + 8, SMEM = B_FULL + 256;
constexpr int T_O = 0, T_GU = 1, T_D = 2, T_END = 3;
#define G_LOOK 8
#define G_FILL 7
#define G_SLEEP 100
#define G_SLEEP2 500
#define G_SLEEP3 100
#define G_DF 0
#define G_FL 10
#define G_DE 0
#define G_DS 16
DEVI bool is_split(int ty, int l, int cb) { return ty == T_O || (ty == T_D && (!l || cb >= G_DS)); }
#define G_ROLES 16, 17, 8, 9, 10, 0, 1, 2, 3, 4, 5, 6, 7, 11, 12, 13, 14, 15
#define G_CR 2
constexpr uint64_t pack_roles(int i0, int i1) { constexpr int r[18] = {G_ROLES}; uint64_t v = 0; for (int i = i0; i < i1; i++) v |= (uint64_t)r[i] << (5 * (i - i0)); return v; }
constexpr uint64_t ROLE0 = pack_roles(0, 12), ROLE1 = pack_roles(12, 18);
struct Pipe { int s, ph; DEVI void next() { if (++s == STAGES) { s = 0; ph ^= 1; } } };
}
struct GemmMaps { CUtensorMap o, wo, x, x1, x1s, xm, xms, xn, wg, wu, h, hs, wd, x2, out, outs; };

DEVI float geglu(float g, float u) {
  const float z = g * (0.7978845608028654f + 0.035677408136300125f * g * g);
  float t; asm("tanh.approx.f32 %0, %1;" : "=f"(t) : "f"(z));
  const float hg = 0.5f * g;
  return fmaf(hg, t, hg) * u;
}
DEVI int h_ready(int v) { const int t = v ^ 0x10141014; return t & 0xff0000ff ? 0 : t & 0xff00 ? 20 : t ? 36 : 56; }
DEVI int a_ready(int ty, int l, int cb) {
  const int v = ld_acquire(g_fl.dep + grp(ty, l, cb));
  asm volatile("fence.proxy.async.global;" ::: "memory");
  return ty == gm::T_D ? h_ready(v) : v >= (ty == gm::T_O && l ? 256 : 128) ? 64 : 0;
}

__global__ void __cluster_dims__(2, 1, 1) __launch_bounds__(512, 1) gemm_kernel(const __grid_constant__ GemmMaps M) {
  using namespace gm;
  extern __shared__ __align__(1024) uint8_t smem[];
  const uint32_t sb = smem_u32(smem);
  const int tid = threadIdx.x, wid = __shfl_sync(0xffffffffu, tid >> 5, 0), wg = wid >> 2, warp = wid & 3;
  int budget = SPIN_BUDGET;
  const int rank = blockIdx.x & 1;
  const uint32_t peer = mapa(sb, rank ^ 1);
  if (tid < 24) mbar_init(sb + B_FULL + 8 * tid, tid >> 3 == 1 ? 2 : 1);
  fence_mbar_init();
  if (wid == 1 && rank == 0) {
    uint32_t sm; asm volatile("mov.u32 %0, %%smid;" : "=r"(sm));
    const bool crowd = sm >= 124 || sm < 50;
    const int t = bcast(e_ticket(g_fl.ticket, crowd ? 1 : 256)), a = t & 255, b = t >> 8, i = crowd ? a : 17 - b;
    sts32v(sb + JOB + 16, a + b >= 18 ? a + b : (int)((i < 12 ? ROLE0 >> (5 * i) : ROLE1 >> (5 * i - 60)) & 31) | crowd << 8);
  }
  cluster_arrive(); cluster_wait();
  int pair;
  asm volatile("ld.shared::cluster.u32 %0, [%1];" : "=r"(pair) : "r"(mapa(sb + JOB + 16, 0)) : "memory");
  const bool crowd = __shfl_sync(0xffffffffu, pair, 0) >> 8;
  pair = __shfl_sync(0xffffffffu, pair, 0) & 255;
  const int cta = pair * 2 + rank, lane = lane_reg();
  if (wg >= 2) {
    reg_dec<72>();
    if (wid == 8 || wid == 10) {
      Pipe p; p.s = 0; p.ph = 1;
      for (int n = 0; ; n++) {
        if (wid == 8) e_expect_tx(sb + B_MSG + 8 * (n & 1), 4);
        mbar_wait(sb + B_MSG + 8 * (n & 1), (n >> 1) & 1, budget);
        const int msg = __shfl_sync(0xffffffffu, lds32v(sb + MSG + 4 * (n & 1)), 0);
        const int ty = (msg >> 11) & 3, l = (msg >> 10) & 1;
        const bool shb = ty == T_GU && l, spl = is_split(ty, l, (msg >> 6) & 15);
        const int cb = ((msg >> 6) & 15) + (shb ? rank : 0), j = (msg & 63) + (ty == T_END || shb ? 0 : rank);
        const int ke = ty == T_O ? 64 : ty == T_GU ? 16 : 56, k0 = spl ? rank : 0, dk = spl ? 2 : 1;
        const int c0 = ty == T_GU ? j * 64 : spl ? (j >> 1) * 128 : j * 128, c1 = ty == T_GU ? c0 : c0 + 64;
        mbar_wait(sb + B_EMPTY + 8 * p.s, p.ph, budget);
        trap_if_spent(budget);
        auto stages = [&](auto f) {
#pragma unroll 1
          for (int k = k0; k < ke; k += dk) {
            mbar_wait(sb + B_EMPTY + 8 * p.s, p.ph, budget);
            f(k, sb + p.s * STAGE_BYTES, sb + B_FULL + 8 * p.s);
            p.next();
          }
        };
        if (wid == 8) {
          const int job = ty << 11 | l << 10 | cb << 6 | j;
          sts32v(sb + JOB + 4 * (n & 1), job | p.s << 16 | (p.ph ^ 1) << 20);
          e_arrive(sb + B_JOB + 8 * (n & 1));
          if (ty == T_END) break;
          if (ty != T_GU) { e_expect_tx(sb + B_FULL + 8 * p.s, spl ? 16384 : STAGE_BYTES); p.next(); }
          const CUtensorMap* const m0 = ty == T_D ? &M.wd : shb && rank ? &M.wu : &M.wg, * const m1 = ty == T_D ? &M.wd : &M.wu;
          if (ty == T_O) stages([&](int k, uint32_t a, uint32_t fb) { e_expect_tx(fb, STAGE_BYTES); e_tma_5d(a + 16384, &M.wo, c0, k * 2, fb); e_tma_5d(a + 24576, &M.wo, c1, k * 2, fb); });
          else if (shb) stages([&](int k, uint32_t a, uint32_t fb) { e_expect_tx(fb, STAGE_BYTES); e_tma_2d_mc(a + 16384 + rank * 8192, m0, c0, k * 64, fb); });
          else stages([&](int k, uint32_t a, uint32_t fb) { e_expect_tx(fb, STAGE_BYTES); e_tma_2d(a + 16384, m0, c0, k * 64, fb); e_tma_2d(a + 24576, m1, c1, k * 64, fb); });
        } else {
          if (ty == T_END) break;
          const int row = l * SEQ + cb * 128, kt = ke + k0 - G_LOOK * dk;
          const uint64_t polA = ty != T_GU ? EVICT_FIRST : EVICT_NORMAL;
          int rdy = msg >> 16;
          auto need = [&](int k) {
            if (k == kt) e_arrive(sb + B_TRIG);
            while (k >= rdy && k >= (rdy = a_ready(ty, l, cb))) { __nanosleep(G_SLEEP); trap_if_spent(--budget); }
          };
          if (ty != T_GU) {
            need(0);
            const uint32_t a = sb + p.s * STAGE_BYTES, fb = sb + B_FULL + 8 * p.s;
            const CUtensorMap* const m = ty == T_D ? (spl ? &M.x1 : &M.x1s) : l ? &M.x2 : &M.x;
            const int r = (ty == T_D ? row : cb * 128) + (spl ? rank * 64 : 0);
            e_tma_2d(a, m, c0, r, fb, polA); e_tma_2d(a + 16384, m, c1, r, fb, polA);
            p.next();
          }
          if (shb || spl) {
            const CUtensorMap* const ma = ty == T_O ? &M.o : ty == T_GU ? &M.xms : &M.hs;
            stages([&](int k, uint32_t a, uint32_t fb) { need(k); e_tma_2d(a, ma, k * 64, row, fb, polA); });
          } else {
            const CUtensorMap* const ma = ty == T_GU ? &M.xm : &M.h;
            stages([&](int k, uint32_t a, uint32_t fb) { need(k); e_tma_2d_mc(a + rank * 8192, ma, k * 64, row + rank * 64, fb, polA); });
          }
        }
      }
    } else if (wid == 9 && rank == 0) {
      int k1 = pair < 18 ? 0 : 48;
      bool late = false;
      for (int n = 0, ty = 0; ty != T_END; n++) {
        mbar_wait(sb + B_TRIG, (n & 1) ^ 1, budget);
        int l, cb, j, rdy = 64;
        while (true) {
          const int ph = k1 % 3;
          const bool gap = pair < 8 ? ph == 1 : pair >= 16 && ph == 2;
          if (k1 < 48) {
            cb = k1++ / 3;
            if (gap && (late || (crowd && (G_CR & 1)) || !(G_FILL & (pair < 8 ? 1 : 2)))) continue;
            if (!gap) {
              l = 0;
              ty = pair < 8 ? (ph ? T_GU : T_O) : ph == 2 ? T_D : T_GU;
              j = 2 * (pair < 8 ? (ph ? pair + 10 : pair) : ph == 1 ? pair + 10 : pair - 8);
              rdy = a_ready(ty, 0, cb);
              if (ph == 0) late = rdy != 0;
              break;
            }
          }
          int d0 = ld_relaxed(g_fl.dep + lane), d1 = ld_relaxed(g_fl.dep + 32 + lane);
          const int t0 = ld_relaxed(g_fl.taken + lane), t1 = ld_relaxed(g_fl.taken + 32 + lane);
          const bool l0 = t0 < (lane < 16 ? 8 : lane & 1 ? 0 : 56), l1 = lane < 16 && t1 < (lane < G_DS ? 4 : 8);
          const uint32_t rd = __ballot_sync(0xffffffffu, d0 >= (lane < 16 ? 256 : 128));
          uint32_t ok0 = __ballot_sync(0xffffffffu, l0) & rd & (rd >> 1 | 0xffff), ok1 = __ballot_sync(0xffffffffu, l1 && h_ready(d1) > 0);
          if (gap) { ok1 = 0; if (pair < 16) ok0 &= G_FILL & 4 ? 0xffff0003u : 0xffff0000u; }
          if (crowd && (G_CR & 2) && ok0 >> 16) ok0 &= 0xffff0000u;
          ty = T_END; l = 1; cb = j = 0;
          if (!gap && !__any_sync(0xffffffffu, l0 || l1)) break;
          if (ok1 & ((1u << G_DS) - 1)) ok1 &= (1u << G_DS) - 1;
          const uint32_t dfirst = ok1 & __ballot_sync(0xffffffffu, lane < G_DF && d1 == 0x10141014);
          if (dfirst && !(ok0 & 0xffff)) { ok0 = 0; ok1 = dfirst; }
          else if (__any_sync(0xffffffffu, l0)) ok1 &= (1u << G_DE) - 1;
          uint32_t m = ok0 ? ok0 : ok1;
          if (!m && !gap) __nanosleep(100);
          while (m) {
            const int nth = ok0 ? 0 : pair % __popc(m);
            const int b = __ffs(__ballot_sync(0xffffffffu, __popc(m << (31 - lane)) > nth)) - 1, gn = b + (ok0 ? 0 : 32);
            const int t = bcast(e_ticket(g_fl.taken + gn));
            if (t < (gn < 16 ? 8 : gn < 32 ? 56 : gn < 32 + G_DS ? 4 : 8)) { ty = gn >> 4; cb = gn & 15; j = ty == T_GU ? t : 2 * t; break; }
            m &= ~(1u << b);
          }
          if (ty != T_END) {
            rdy = a_ready(ty, 1, cb);
            if (ty == T_GU) a_ready(ty, 1, cb + 1);
            break;
          }
          trap_if_spent(--budget);
        }
        const int msg = rdy << 16 | ty << 11 | l << 10 | cb << 6 | j;
        e_st_async32(peer + MSG + 4 * (n & 1), msg, peer + B_MSG + 8 * (n & 1));
        e_st_async32(sb + MSG + 4 * (n & 1), msg, sb + B_MSG + 8 * (n & 1));
      }
    } else if (wg == 3) {
      bool open = lane < G_FL && ld_relaxed(g_fl.rows + lane) < 128;
      while (__any_sync(0xffffffffu, open)) {
        int v = 0;
        if (open) asm volatile("ld.acquire.gpu.global.s32 %0, [%1];" : "=r"(v) : "l"(g_fl.part + lane) : "memory");
        const uint32_t ok = __ballot_sync(0xffffffffu, open && v >= 128);
        if (!ok) {
          if (--budget <= 0) break;
          __nanosleep(G_SLEEP2);
          continue;
        }
        const int cb = __ffs(__ballot_sync(0xffffffffu, __popc(ok << (31 - lane)) > (cta >> 5) % __popc(ok))) - 1;
        const int r = bcast(e_ticket(g_fl.rows + cb));
        if (r >= 128) { open = open && lane != cb; continue; }
        uint4 u[4];
#pragma unroll
        for (int i = 0; i < 4; i++) u[i] = ldg_rlx128((const uint4*)(g_x1[1] + (size_t)(cb * 128 + r) * DM) + i * 32 + lane);
        ln_row(u, g_xm[1] + (size_t)(cb * 128 + r) * DM, lane);
        __syncwarp();
        e_flag_add(g_fl.dep + grp(T_GU, 1, cb));
      }
      if (cta == 0 && wid == 12) {
        asm volatile("griddepcontrol.wait;" ::: "memory");
        g_fl.xn[lane >> 4][lane & 15][0] = 0;
        if (NSTEP & 1) for (int i = lane; i < 2048; i += 32) g_mem[1][i] = make_uint4(0, 0, 0, 0);
      }
    }
    cluster_arrive(); cluster_wait();
  } else {
    reg_inc<184>();
    const bool lead = warp == 0;
    const uint32_t eb = (warp == 1 ? peer : sb) + B_EMPTY;
    const int rl = warp < 2 ? 0 : -1;
    const uint32_t so = sb + SO + wg * 16384;
    const int r0 = warp * 16 + (lane & 7) + ((lane >> 3) & 1) * 8;
    const uint32_t sw = r0 * 128 + (((lane >> 4) ^ (r0 & 7)) << 4);
    int xph = 0;
    for (int n = wg; ; n += 2) {
      float d0[64], d1[64];
      mbar_wait(sb + B_JOB + 8 * wg, (n >> 1) & 1, budget);
      fault_if_spent(budget);
      const int job = __shfl_sync(0xffffffffu, lds32v(sb + JOB + 4 * wg), 0);
      const int ty = (job >> 11) & 3, l = (job >> 10) & 1, cb = (job >> 6) & 15, j = job & 63;
      if (ty == T_END) {
        if (n > 0) nbar_sync_r(1 + wg, 256);
        if (lead && !(job & 1)) { sts32v(sb + JOB + 4 * (wg ^ 1), job | 1); e_arrive(sb + B_JOB + 8 * (wg ^ 1)); }
        if (!(job & 1)) nbar_arrive_r(1 + (wg ^ 1), 256);
        break;
      }
      Pipe q; q.s = (job >> 16) & 15; q.ph = job >> 20;
      const bool spl = is_split(ty, l, cb);
      if (ty != T_GU) mbar_wait(sb + B_FULL + 8 * q.s, q.ph, budget);
#pragma unroll
      for (int m = 0; m < 2; m++) {
        float* d = m ? d1 : d0;
        if (ty != T_GU && !(m && spl)) {
#pragma unroll
          for (int c = 0; c < 8; c++) {
            uint32_t r[4];
            ldsm4(sb + q.s * STAGE_BYTES + (c >> 2) * 16384 + m * 8192 + (sw ^ ((c & 3) << 5)), r[0], r[1], r[2], r[3]);
#pragma unroll
            for (int i = 0; i < 4; i++) { d[8*c+2*i] = bf_lo(r[i]); d[8*c+2*i+1] = bf_hi(r[i]); }
          }
        } else {
#pragma unroll
          for (int i = 0; i < 64; i++) d[i] = 0.f;
        }
      }
      if (ty != T_GU) {
        fence_proxy_async();
        nbar_sync_r(3 + wg, 128);
        arrive_cl_if_eq(eb + 8 * q.s, lane, rl);
        q.next();
      }
      pin<64>(d0); pin<64>(d1);
      if (n > 0) nbar_sync_r(1 + wg, 256);
      const int nk = ty == T_O ? 32 : ty == T_GU ? 16 : spl ? 28 : 56;
      const uint32_t ro = spl ? rank * 512 : 0;
      int prev = 0;
      for (int i = 0; i < nk; i++) {
        mbar_wait(sb + B_FULL + 8 * q.s, q.ph, budget);
        const uint32_t da = desc_base(sb) + q.s * (STAGE_BYTES / 16);
        wg_fence();
        sfor<0, 4>([&](auto K) {
          constexpr int k = K;
          typedef Op<16384 + k * 2048, 8192, 1024, 1, 1> OB;
          wg_ss128<1, Op<k * 32, 16, 1024, 1, 0>, OB>(d0, da + ro, da);
          wg_ss128<1, Op<8192 + k * 32, 16, 1024, 1, 0>, OB>(d1, da - ro, da);
        });
        wg_commit();
        wg_wait<1>();
        arrive_cl_if_eq(eb + 8 * prev, lane, i ? rl : -1);
        prev = q.s;
        q.next();
      }
      nbar_arrive_r(1 + (wg ^ 1), 256);
      wg_wait<0>();
      pin<64>(d0); pin<64>(d1);
      arrive_cl_if_eq(eb + 8 * prev, lane, rl);
      if (spl) {
        const uint32_t xa = SO + wg * 16384 + warp * 512 + lane * 16;
        if (lead) e_expect_tx(sb + B_XF + 8 * wg, 16384);
        mbar_wait(sb + B_SF + 8 * wg, ((n >> 1) & 1) ^ 1, budget);
#pragma unroll
        for (int i = 0; i < 8; i++) {
          const float* d = d1 + 8 * i;
          st_async128(peer + xa + i * 2048, pack_bf16(d[0], d[1]), pack_bf16(d[2], d[3]), pack_bf16(d[4], d[5]), pack_bf16(d[6], d[7]), peer + B_XF + 8 * wg);
        }
        mbar_wait(sb + B_XF + 8 * wg, xph, budget);
        xph ^= 1;
        uint32_t y[32];
#pragma unroll
        for (int i = 0; i < 8; i++) {
          const float* d = d0 + 8 * i;
          const uint4 v = lds128(sb + xa + i * 2048);
          y[4*i] = pack_bf16(d[0] + bf_lo(v.x), d[1] + bf_hi(v.x)); y[4*i+1] = pack_bf16(d[2] + bf_lo(v.y), d[3] + bf_hi(v.y));
          y[4*i+2] = pack_bf16(d[4] + bf_lo(v.z), d[5] + bf_hi(v.z)); y[4*i+3] = pack_bf16(d[6] + bf_lo(v.w), d[7] + bf_hi(v.w));
        }
        const bool fuse = !l || (ty == T_O && cb >= G_FL);
        float2* const st = &g_stat[l ? 4 + (cb & 7) : ty + (cb & 1)][0][rank * 64 + warp * 16 + (lane >> 2) * 2];
        if (fuse) {
          float mn[2], sq[2];
#pragma unroll
          for (int z = 0; z < 2; z++) {
            float m = 0, s2 = 0;
#pragma unroll
            for (int i = 0; i < 16; i++) m += bf_lo(y[2*i+z]) + bf_hi(y[2*i+z]);
            m += __shfl_xor_sync(0xffffffffu, m, 1); m += __shfl_xor_sync(0xffffffffu, m, 2);
            m *= 1.f / 128;
#pragma unroll
            for (int i = 0; i < 16; i++) { const float a = bf_lo(y[2*i+z]) - m, b = bf_hi(y[2*i+z]) - m; s2 = fmaf(a, a, fmaf(b, b, s2)); }
            s2 += __shfl_xor_sync(0xffffffffu, s2, 1); s2 += __shfl_xor_sync(0xffffffffu, s2, 2);
            mn[z] = m; sq[z] = s2;
          }
          if ((lane & 3) == 0) stg_rlx128(st + (j >> 1) * 128, __float_as_uint(mn[0]), (__float_as_uint(sq[0]) & ~31u) | (cb + 1), __float_as_uint(mn[1]), __float_as_uint(sq[1]));
          __syncwarp();
        }
        const int row = (ty == T_O ? l * SEQ : 0) + cb * 128 + rank * 64;
        auto put = [&](const CUtensorMap* mo, auto f) {
          nbar_sync_r(3 + wg, 128);
#pragma unroll
          for (int c = 0; c < 8; c++) stsm4(so + (c >> 2) * 8192 + (sw ^ ((c & 3) << 5)), f(4*c), f(4*c+1), f(4*c+2), f(4*c+3));
          fence_proxy_async();
          nbar_sync_r(3 + wg, 128);
          if (lead) { e_tma_store_2d(mo, so, (j >> 1) * 128, row); e_tma_store_2d(mo, so + 8192, (j >> 1) * 128 + 64, row); bulk_commit(); }
        };
        if (fuse) {
          uint4 u[2];
          while (true) {
            __nanosleep(G_SLEEP3);
            u[0] = ldg_rlx128(st + (lane & 3) * 256); u[1] = ldg_rlx128(st + (lane & 3) * 256 + 128);
            if (!__any_sync(0xffffffffu, ((u[0].y ^ (cb + 1)) | (u[1].y ^ (cb + 1))) & 31) || --budget <= 0) break;
          }
          float rs[2], mr[2];
#pragma unroll
          for (int z = 0; z < 2; z++) {
            const float ma = __uint_as_float(z ? u[0].z : u[0].x), mb = __uint_as_float(z ? u[1].z : u[1].x);
            float m = ma + mb;
            m += __shfl_xor_sync(0xffffffffu, m, 1); m += __shfl_xor_sync(0xffffffffu, m, 2);
            m *= 0.125f;
            float s2 = __uint_as_float(z ? u[0].w : u[0].y & ~31u) + __uint_as_float(z ? u[1].w : u[1].y & ~31u) + 128.f * ((ma - m) * (ma - m) + (mb - m) * (mb - m));
            s2 += __shfl_xor_sync(0xffffffffu, s2, 1); s2 += __shfl_xor_sync(0xffffffffu, s2, 2);
            rs[z] = rsqrtf(s2 * (1.f / DM) + 1e-5f); mr[z] = -m * rs[z];
          }
          put(ty == T_O ? &M.xm : &M.xn, [&](int i) { return pack_bf16(fmaf(bf_lo(y[i]), rs[i & 1], mr[i & 1]), fmaf(bf_hi(y[i]), rs[i & 1], mr[i & 1])); });
          if (lead) {
            bulk_wait<0>();
            e_flag_add_bulk(ty == T_D ? g_fl.xn[1][cb] : g_fl.dep + grp(T_GU, l, cb), 8);
          }
        }
        put(ty == T_O ? &M.x1 : l ? &M.out : &M.x2, [&](int i) { return y[i]; });
      } else {
        if (ty == T_GU) {
#pragma unroll
          for (int i = 0; i < 32; i++) { d0[i] = geglu(d0[i], d0[32 + i]); d1[i] = geglu(d1[i], d1[32 + i]); }
        }
#pragma unroll
        for (int hf = 0; hf < 2; hf++) {
          if (hf) {
            if (ty == T_GU) break;
            if (lead) bulk_wait_read<0>();
            nbar_sync_r(3 + wg, 128);
          }
#pragma unroll
          for (int m = 0; m < 2; m++)
#pragma unroll
            for (int c = 0; c < 4; c++) {
              const float* d = (m ? d1 : d0) + 32 * hf + 8 * c;
              stsm4(so + m * 8192 + (sw ^ (c << 5)), pack_bf16(d[0], d[1]), pack_bf16(d[2], d[3]), pack_bf16(d[4], d[5]), pack_bf16(d[6], d[7]));
            }
          fence_proxy_async();
          nbar_sync_r(3 + wg, 128);
          if (lead) {
            if (ty == T_GU) e_tma_store_2d(&M.hs, so, j * 64, l * SEQ + cb * 128); else e_tma_store_2d(&M.outs, so, j * 128 + hf * 64, cb * 128);
            bulk_commit();
          }
        }
      }
      if (lead) {
        bulk_wait<0>();
        e_arrive_cl(peer + B_SF + 8 * wg);
        if (ty == T_GU) e_flag_add_bulk(g_fl.dep + grp(T_D, l, cb), j < 20 ? 1 : j < 36 ? 1 << 8 : 1 << 16);
        else if (ty == T_O) { e_flag_add_bulk(g_fl.dep + grp(T_D, l, cb), 1 << 24); if (l && cb < G_FL) e_flag_add_bulk(g_fl.part + cb, 8); }
        else if (!l) e_flag_add_bulk(g_fl.dep + grp(T_O, 1, cb), 8);
      }
    }
    cluster_arrive(); cluster_wait();
  }
}

typedef CUresult (*PFN_encodeTiled)(CUtensorMap*, CUtensorMapDataType, cuuint32_t, void*, const cuuint64_t*, const cuuint64_t*,
                                    const cuuint32_t*, const cuuint32_t*, CUtensorMapInterleave, CUtensorMapSwizzle,
                                    CUtensorMapL2promotion, CUtensorMapFloatOOBfill);
static PFN_encodeTiled g_encode = nullptr;
static int g_sms = 0;
static CUtensorMap encode(const void* ptr, int rank, const cuuint64_t* dims, const cuuint64_t* strides, const cuuint32_t* box) {
  CUtensorMap m;
  const cuuint32_t es[5] = {1, 1, 1, 1, 1};
  g_encode(&m, CU_TENSOR_MAP_DATA_TYPE_BFLOAT16, rank, (void*)ptr, dims, strides, box, es, CU_TENSOR_MAP_INTERLEAVE_NONE,
           CU_TENSOR_MAP_SWIZZLE_128B, CU_TENSOR_MAP_L2_PROMOTION_L2_256B, CU_TENSOR_MAP_FLOAT_OOB_FILL_NONE);
  return m;
}
static CUtensorMap make_map(const void* ptr, uint64_t rows, uint64_t cols, uint32_t box_rows) {
  const cuuint64_t dims[2] = {cols, rows}, strides[1] = {cols * 2};
  const cuuint32_t box[2] = {64, box_rows};
  return encode(ptr, 2, dims, strides, box);
}
static CUtensorMap make_map_x(const void* ptr) {
  const cuuint64_t dims[3] = {DM, NSTEP * 32, 2}, strides[2] = {DM * 2, (cuuint64_t)NSTEP * 32 * DM * 2};
  const cuuint32_t box[3] = {64, 32, 2};
  return encode(ptr, 3, dims, strides, box);
}
static CUtensorMap make_map_x1(const void* ptr) {
  const cuuint64_t dims[3] = {64, 2 * NSTEP * 32, DM / 64}, strides[2] = {DM * 2, 128};
  const cuuint32_t box[3] = {64, 32, 2};
  return encode(ptr, 3, dims, strides, box);
}
static CUtensorMap make_map_wo(const void* ptr) {
  const cuuint64_t dims[5] = {DM, 2, 4, 4, NH * DH / 32}, strides[4] = {DM * 2, 8 * DM * 2, 2 * DM * 2, 32 * DM * 2};
  const cuuint32_t box[5] = {64, 2, 4, 4, 2};
  return encode(ptr, 5, dims, strides, box);
}

extern "C" void kernel_launch(void* const* d_in, const int* in_sizes, int n_in, void* d_out, int out_size) {
  const bf16 *x = (const bf16*)d_in[0], *mem0 = (const bf16*)d_in[1], *Wo = (const bf16*)d_in[5];
  if (!g_encode) {
    void* p = nullptr; cudaDriverEntryPointQueryResult q;
    cudaGetDriverEntryPoint("cuTensorMapEncodeTiled", &p, cudaEnableDefault, &q);
    g_encode = (PFN_encodeTiled)p;
    int dev = 0;
    cudaGetDevice(&dev);
    cudaDeviceGetAttribute(&g_sms, cudaDevAttrMultiProcessorCount, dev);
    cudaFuncSetAttribute(rec_kernel, cudaFuncAttributeMaxDynamicSharedMemorySize, rec::SMEM);
    cudaFuncSetAttribute(gemm_kernel, cudaFuncAttributeMaxDynamicSharedMemorySize, gm::SMEM);
  }
  void *xn, *o, *x1, *xm, *x2, *hh;
  cudaGetSymbolAddress(&xn, g_xn); cudaGetSymbolAddress(&o, g_o); cudaGetSymbolAddress(&x1, g_x1);
  cudaGetSymbolAddress(&xm, g_xm); cudaGetSymbolAddress(&x2, g_x2); cudaGetSymbolAddress(&hh, g_h);
  RecMaps R;
  for (int i = 0; i < 3; i++) R.w[i] = make_map(d_in[2 + i], DM, NH * DH, 16);
  R.wo = make_map(Wo, NH * DH, DM, 64); R.x[0] = make_map_x(xn); R.x[1] = make_map_x1(xn);
  rec_kernel<<<96, 512, rec::SMEM>>>(R, Wo, mem0, x, 0);
  GemmMaps G;
  G.o = make_map(o, 2 * SEQ, NH * DH, 128); G.wo = make_map_wo(Wo);
  G.x1 = make_map(x1, 2 * SEQ, DM, 64); G.x1s = make_map(x1, 2 * SEQ, DM, 128);
  G.xn = make_map((bf16*)xn + (NSTEP + LAG) * 32 * DM, SEQ, DM, 64);
  G.xm = make_map(xm, 2 * SEQ, DM, 64); G.xms = make_map(xm, 2 * SEQ, DM, 128);
  G.wg = make_map(d_in[8], DM, DF, 64); G.wu = make_map(d_in[9], DM, DF, 64); G.wd = make_map(d_in[10], DF, DM, 64);
  G.h = make_map(hh, 2 * SEQ, DF, 64); G.hs = make_map(hh, 2 * SEQ, DF, 128);
  G.x = make_map(x, SEQ, DM, 64); G.x2 = make_map(x2, SEQ, DM, 64); G.out = make_map(d_out, SEQ, DM, 64); G.outs = make_map(d_out, SEQ, DM, 128);
  cudaLaunchConfig_t cfg = {};
  cfg.gridDim = dim3(g_sms & ~1); cfg.blockDim = dim3(512); cfg.dynamicSmemBytes = gm::SMEM; cfg.stream = cudaStreamPerThread;
  cudaLaunchAttribute at;
  at.id = cudaLaunchAttributeProgrammaticStreamSerialization; at.val.programmaticStreamSerializationAllowed = 1;
  cfg.attrs = &at; cfg.numAttrs = 1;
  cudaLaunchKernelEx(&cfg, gemm_kernel, G);
}
```

```cpp
#include <cuda_runtime.h>
#include <cuda_bf16.h>
#include <cuda.h>
#include <stdint.h>

#define DEVI __device__ __forceinline__
typedef __nv_bfloat16 bf16;

#define LAG 14
constexpr int SEQ = 2048, DM = 1024, NH = 32, DH = 128, DF = 3584, NSEG = 64, NSTEP = NSEG + LAG;

__device__ __align__(1024) bf16 g_xn[2][NSTEP * 32 * DM];
__device__ __align__(1024) bf16 g_o[2][SEQ * NH * DH];
__device__ __align__(1024) bf16 g_x1[2][SEQ * DM];
__device__ __align__(1024) bf16 g_xm[2][SEQ * DM];
__device__ __align__(1024) bf16 g_x2[SEQ * DM];
__device__ __align__(1024) bf16 g_h[2][SEQ * DF];
__device__ __align__(1024) uint4 g_part[256 * 32 * 8];
__device__ __align__(1024) uint32_t g_ann[2][32][64];
__device__ __align__(1024) uint4 g_mem[2][2048];
__device__ __align__(128) float2 g_stat[12][8][128];
__host__ __device__ constexpr int grp(int type, int layer, int blk) { return layer ? 16 * type + blk : 64 + (16 * type + blk) * 32; }
struct Flags {
  int xn[2][16][32];
  int dep[64 + 48 * 32];
  int taken[64];
  int rows[32];
  int part[32];
  int ticket[32];
};
__device__ __align__(128) Flags g_fl;

DEVI uint32_t smem_u32(const void* p) { return (uint32_t)__cvta_generic_to_shared(p); }
DEVI void mbar_init(uint32_t bar, uint32_t cnt) { asm volatile("mbarrier.init.shared::cta.b64 [%0], %1;" :: "r"(bar), "r"(cnt) : "memory"); }
DEVI void mbar_expect_tx(uint32_t bar, uint32_t bytes) { asm volatile("mbarrier.arrive.expect_tx.shared::cta.b64 _, [%0], %1;" :: "r"(bar), "r"(bytes) : "memory"); }
DEVI void mbar_arrive(uint32_t bar) { asm volatile("mbarrier.arrive.shared::cta.b64 _, [%0];" :: "r"(bar) : "memory"); }
DEVI bool mbar_try(uint32_t bar, uint32_t parity) {
  uint32_t p;
  asm volatile("{.reg .pred p; mbarrier.try_wait.parity.shared::cta.b64 p, [%1], %2; selp.u32 %0, 1, 0, p;}" : "=r"(p) : "r"(bar), "r"(parity) : "memory");
  return p;
}
DEVI bool mbar_test(uint32_t bar, uint32_t parity) {
  uint32_t p;
  asm volatile("{.reg .pred p; mbarrier.test_wait.parity.shared::cta.b64 p, [%1], %2; selp.u32 %0, 1, 0, p;}" : "=r"(p) : "r"(bar), "r"(parity) : "memory");
  return p;
}
constexpr int SPIN_BUDGET = 1 << 20;
DEVI void mbar_wait(uint32_t bar, uint32_t parity, int& budget) {
  while (!mbar_try(bar, parity)) { if (--budget < 0) break; }
}
DEVI void trap_if_spent(int budget) { asm volatile("{.reg .pred p; setp.le.s32 p, %0, 0; @p trap;}" :: "r"(budget) : "memory"); }
DEVI void fault_if_spent(int budget) { asm volatile("{.reg .pred p; setp.le.s32 p, %0, 0; @p st.global.u32 [%1], 0;}" :: "r"(budget), "l"(0ull) : "memory"); }
DEVI uint32_t mapa(uint32_t addr, uint32_t rank) { uint32_t r; asm("mapa.shared::cluster.u32 %0, %1, %2;" : "=r"(r) : "r"(addr), "r"(rank)); return r; }
DEVI void cluster_arrive() { asm volatile("barrier.cluster.arrive.release.aligned;" ::: "memory"); }
DEVI void cluster_wait() { asm volatile("barrier.cluster.wait.acquire.aligned;" ::: "memory"); }
DEVI void fence_mbar_init() { asm volatile("fence.mbarrier_init.release.cluster;" ::: "memory"); }
DEVI void fence_proxy_async() { asm volatile("fence.proxy.async.shared::cta;" ::: "memory"); }
DEVI void tma_load_2d(uint32_t dst, const CUtensorMap* m, int c0, int c1, uint32_t bar) {
  asm volatile("cp.async.bulk.tensor.2d.shared::cluster.global.mbarrier::complete_tx::bytes [%0], [%1, {%3, %4}], [%2];"
    :: "r"(dst), "l"(m), "r"(bar), "r"(c0), "r"(c1) : "memory");
}
DEVI void tma_load_5d(uint32_t dst, const CUtensorMap* m, int c0, int c4, uint32_t bar) {
  asm volatile("cp.async.bulk.tensor.5d.shared::cluster.global.mbarrier::complete_tx::bytes [%0], [%1, {%3, %5, %5, %5, %4}], [%2];"
    :: "r"(dst), "l"(m), "r"(bar), "r"(c0), "r"(c4), "r"(0) : "memory");
}
DEVI void tma_prefetch_2d(const CUtensorMap* m, int c0, int c1) {
  asm volatile("cp.async.bulk.prefetch.tensor.2d.L2.global [%0, {%1, %2}];" :: "l"(m), "r"(c0), "r"(c1) : "memory");
}
DEVI void tma_prefetch_5d(const CUtensorMap* m, int c0, int c4) {
  asm volatile("cp.async.bulk.prefetch.tensor.5d.L2.global [%0, {%1, %3, %3, %3, %2}];" :: "l"(m), "r"(c0), "r"(c4), "r"(0) : "memory");
}
#define ELECT "{.reg .pred p; elect.sync _|p, 0xffffffff;\n @p "
DEVI void e_expect_tx(uint32_t bar, uint32_t bytes) { asm volatile(ELECT "mbarrier.arrive.expect_tx.shared::cta.b64 _, [%0], %1;}" :: "r"(bar), "r"(bytes) : "memory"); }
DEVI void e_arrive(uint32_t bar) { asm volatile(ELECT "mbarrier.arrive.shared::cta.b64 _, [%0];}" :: "r"(bar) : "memory"); }
DEVI void e_arrive_cl(uint32_t bar) { asm volatile(ELECT "mbarrier.arrive.shared::cluster.b64 _, [%0];}" :: "r"(bar) : "memory"); }
constexpr uint64_t EVICT_NORMAL = 0x1000000000000000ull, EVICT_FIRST = 0x12F0000000000000ull;
DEVI void e_tma_2d(uint32_t dst, const CUtensorMap* m, int c0, int c1, uint32_t bar, uint64_t pol = EVICT_NORMAL) {
  asm volatile(ELECT "cp.async.bulk.tensor.2d.shared::cluster.global.mbarrier::complete_tx::bytes.L2::cache_hint [%0], [%1, {%3, %4}], [%2], %5;}"
    :: "r"(dst), "l"(m), "r"(bar), "r"(c0), "r"(c1), "l"(pol) : "memory");
}
DEVI void e_tma_2d_mc(uint32_t dst, const CUtensorMap* m, int c0, int c1, uint32_t bar, uint64_t pol = EVICT_NORMAL) {
  asm volatile(ELECT "cp.async.bulk.tensor.2d.shared::cluster.global.mbarrier::complete_tx::bytes.multicast::cluster.L2::cache_hint [%0], [%1, {%3, %4}], [%2], %5, %6;}"
    :: "r"(dst), "l"(m), "r"(bar), "r"(c0), "r"(c1), "h"((unsigned short)3), "l"(pol) : "memory");
}
DEVI void e_st_async32(uint32_t a, uint32_t x, uint32_t bar) {
  asm volatile(ELECT "st.async.weak.shared::cluster.mbarrier::complete_tx::bytes.b32 [%0], %1, [%2];}" :: "r"(a), "r"(x), "r"(bar) : "memory");
}
DEVI void e_tma_store_2d(const CUtensorMap* m, uint32_t src, int c0, int c1) {
  asm volatile(ELECT "cp.async.bulk.tensor.2d.global.shared::cta.bulk_group [%0, {%2, %3}], [%1];}" :: "l"(m), "r"(src), "r"(c0), "r"(c1) : "memory");
}
DEVI void e_flag_add(int* p, int v = 1) {
  asm volatile("{.reg .pred p; elect.sync _|p, 0xffffffff;\n fence.proxy.async.global; @p red.release.gpu.global.add.s32 [%0], %1;}" :: "l"(p), "r"(v) : "memory");
}
DEVI void e_flag_add_bulk(int* p, int v) {
  asm volatile(ELECT "red.relaxed.gpu.global.add.s32 [%0], %1;}" :: "l"(p), "r"(v) : "memory");
}
DEVI int e_ticket(int* p, int n = 1) { int v = 0; asm volatile(ELECT "atom.relaxed.gpu.global.add.s32 %0, [%1], %2;}" : "+r"(v) : "l"(p), "r"(n) : "memory"); __syncwarp(); return v; }
DEVI int bcast(int v) { return __reduce_max_sync(0xffffffffu, v); }
DEVI int ld_relaxed(const int* p) { int v; asm volatile("ld.relaxed.gpu.global.s32 %0, [%1];" : "=r"(v) : "l"(p) : "memory"); return v; }
DEVI int ld_acquire(const int* p) { int v; asm volatile("ld.acquire.gpu.global.s32 %0, [%1];" : "=r"(v) : "l"(p) : "memory"); return __shfl_sync(0xffffffffu, v, 0); }
DEVI void e_tma_3d(uint32_t dst, const CUtensorMap* m, int c0, int c1, int c2, uint32_t bar) {
  asm volatile(ELECT "cp.async.bulk.tensor.3d.shared::cluster.global.mbarrier::complete_tx::bytes [%0], [%1, {%3, %4, %5}], [%2];}"
    :: "r"(dst), "l"(m), "r"(bar), "r"(c0), "r"(c1), "r"(c2) : "memory");
}
DEVI void e_tma_5d(uint32_t dst, const CUtensorMap* m, int c0, int c4, uint32_t bar) {
  asm volatile(ELECT "cp.async.bulk.tensor.5d.shared::cluster.global.mbarrier::complete_tx::bytes [%0], [%1, {%3, %5, %5, %5, %4}], [%2];}"
    :: "r"(dst), "l"(m), "r"(bar), "r"(c0), "r"(c4), "r"(0) : "memory");
}
DEVI void e_bulk_g2s(uint32_t dst, const void* src, uint32_t bytes, uint32_t bar) {
  asm volatile(ELECT "cp.async.bulk.shared::cluster.global.mbarrier::complete_tx::bytes [%0], [%1], %2, [%3];}" :: "r"(dst), "l"(src), "r"(bytes), "r"(bar) : "memory");
}
DEVI void e_prefetch(const void* src, uint32_t bytes) {
  asm volatile(ELECT "cp.async.bulk.prefetch.L2.global [%0], %1;}" :: "l"(src), "r"(bytes) : "memory");
}
DEVI void bulk_commit() { asm volatile("cp.async.bulk.commit_group;" ::: "memory"); }
template<int N> DEVI void bulk_wait_read() { asm volatile("cp.async.bulk.wait_group.read %0;" :: "n"(N) : "memory"); }
template<int N> DEVI void bulk_wait() { asm volatile("cp.async.bulk.wait_group %0;" :: "n"(N) : "memory"); }
template<int ID, int N> DEVI void nbar_sync() { asm volatile("bar.sync %0, %1;" :: "n"(ID), "n"(N) : "memory"); }
template<int ID, int N> DEVI void nbar_arrive() { asm volatile("bar.arrive %0, %1;" :: "n"(ID), "n"(N) : "memory"); }
DEVI void nbar_sync_r(int id, int n) { asm volatile("bar.sync %0, %1;" :: "r"(id), "r"(n) : "memory"); }
DEVI void nbar_arrive_r(int id, int n) { asm volatile("bar.arrive %0, %1;" :: "r"(id), "r"(n) : "memory"); }
template<int R> DEVI void reg_inc() { asm volatile("setmaxnreg.inc.sync.aligned.u32 %0;" :: "n"(R)); }
template<int R> DEVI void reg_dec() { asm volatile("setmaxnreg.dec.sync.aligned.u32 %0;" :: "n"(R)); }
DEVI void wg_fence() { asm volatile("wgmma.fence.sync.aligned;" ::: "memory"); }
DEVI void wg_commit() { asm volatile("wgmma.commit_group.sync.aligned;" ::: "memory"); }
template<int N> DEVI void wg_wait() { asm volatile("wgmma.wait_group.sync.aligned %0;" :: "n"(N) : "memory"); }
DEVI uint32_t pack_bf16(float lo, float hi) { uint32_t r; asm("cvt.rn.bf16x2.f32 %0, %1, %2;" : "=r"(r) : "f"(hi), "f"(lo)); return r; }
DEVI float bf_lo(uint32_t v) { return __uint_as_float(v << 16); }
DEVI float bf_hi(uint32_t v) { return __uint_as_float(v & 0xffff0000u); }
DEVI uint32_t movmat(uint32_t a) { uint32_t r; asm volatile("movmatrix.sync.aligned.m8n8.trans.b16 %0, %1;" : "=r"(r) : "r"(a)); return r; }
DEVI void ldsm4(uint32_t addr, uint32_t& r0, uint32_t& r1, uint32_t& r2, uint32_t& r3) {
  asm volatile("ldmatrix.sync.aligned.m8n8.x4.shared.b16 {%0,%1,%2,%3}, [%4];" : "=r"(r0), "=r"(r1), "=r"(r2), "=r"(r3) : "r"(addr) : "memory");
}
DEVI void ldsm4t(uint32_t addr, uint32_t& r0, uint32_t& r1, uint32_t& r2, uint32_t& r3) {
  asm volatile("ldmatrix.sync.aligned.m8n8.x4.trans.shared.b16 {%0,%1,%2,%3}, [%4];" : "=r"(r0), "=r"(r1), "=r"(r2), "=r"(r3) : "r"(addr) : "memory");
}
DEVI void stsm4(uint32_t addr, uint32_t r0, uint32_t r1, uint32_t r2, uint32_t r3) {
  asm volatile("stmatrix.sync.aligned.m8n8.x4.shared.b16 [%0], {%1,%2,%3,%4};" :: "r"(addr), "r"(r0), "r"(r1), "r"(r2), "r"(r3) : "memory");
}
DEVI uint4 lds128(uint32_t a) { uint4 v; asm volatile("ld.shared.v4.u32 {%0,%1,%2,%3}, [%4];" : "=r"(v.x), "=r"(v.y), "=r"(v.z), "=r"(v.w) : "r"(a) : "memory"); return v; }
DEVI uint32_t lds32v(uint32_t a) { uint32_t v; asm volatile("ld.volatile.shared.u32 %0, [%1];" : "=r"(v) : "r"(a) : "memory"); return v; }
DEVI void sts32v(uint32_t a, uint32_t v) { asm volatile("st.volatile.shared.u32 [%0], %1;" :: "r"(a), "r"(v) : "memory"); }
DEVI void st_async128(uint32_t a, uint32_t x, uint32_t y, uint32_t z, uint32_t w, uint32_t bar) {
  asm volatile("st.async.weak.shared::cluster.mbarrier::complete_tx::bytes.v4.b32 [%0], {%1,%2,%3,%4}, [%5];" :: "r"(a), "r"(x), "r"(y), "r"(z), "r"(w), "r"(bar) : "memory");
}
DEVI void st_async32(uint32_t a, uint32_t x, uint32_t bar) {
  asm volatile("st.async.weak.shared::cluster.mbarrier::complete_tx::bytes.b32 [%0], %1, [%2];" :: "r"(a), "r"(x), "r"(bar) : "memory");
}
DEVI void st_cl128(bool own, uint32_t a, uint32_t x, uint32_t y, uint32_t z, uint32_t w, uint32_t bar) {
  asm volatile("{.reg .pred p; setp.ne.u32 p, %6, 0; @p st.shared.v4.b32 [%0], {%1,%2,%3,%4};\n"
               "@!p st.async.weak.shared::cluster.mbarrier::complete_tx::bytes.v4.b32 [%0], {%1,%2,%3,%4}, [%5];}"
               :: "r"(a), "r"(x), "r"(y), "r"(z), "r"(w), "r"(bar), "r"((uint32_t)own) : "memory");
}
DEVI void st_cl32(bool own, uint32_t a, uint32_t x, uint32_t bar) {
  asm volatile("{.reg .pred p; setp.ne.u32 p, %3, 0; @p st.shared.b32 [%0], %1;\n"
               "@!p st.async.weak.shared::cluster.mbarrier::complete_tx::bytes.b32 [%0], %1, [%2];}" :: "r"(a), "r"(x), "r"(bar), "r"((uint32_t)own) : "memory");
}
DEVI uint4 ldg_rlx128(const void* p) {
  uint4 v;
  asm volatile("ld.relaxed.gpu.global.v4.b32 {%0,%1,%2,%3}, [%4];" : "=r"(v.x), "=r"(v.y), "=r"(v.z), "=r"(v.w) : "l"(p) : "memory");
  return v;
}
DEVI void stg_rlx128(void* p, uint32_t x, uint32_t y, uint32_t z, uint32_t w) {
  asm volatile("st.relaxed.gpu.global.v4.b32 [%0], {%1,%2,%3,%4};" :: "l"(p), "r"(x), "r"(y), "r"(z), "r"(w) : "memory");
}
DEVI void stg128(void* p, uint32_t x, uint32_t y, uint32_t z, uint32_t w) {
  asm volatile("st.global.v4.b32 [%0], {%1,%2,%3,%4};" :: "l"(p), "r"(x), "r"(y), "r"(z), "r"(w) : "memory");
}
DEVI void stg_rlx64(void* p, uint32_t x, uint32_t y) { asm volatile("st.relaxed.gpu.global.v2.b32 [%0], {%1,%2};" :: "l"(p), "r"(x), "r"(y) : "memory"); }
DEVI void stg_rlx32(void* p, uint32_t x) { asm volatile("st.relaxed.gpu.global.b32 [%0], %1;" :: "l"(p), "r"(x) : "memory"); }
DEVI uint32_t clock32() { uint32_t c; asm volatile("mov.u32 %0, %%clock;" : "=r"(c) :: "memory"); return c; }
DEVI uint32_t gtime() { uint32_t c; asm volatile("mov.u32 %0, %%globaltimer_lo;" : "=r"(c) :: "memory"); return c; }
DEVI void wait_time(uint32_t t, int& budget) { while ((int)(gtime() - t) < 0 && --budget > 0) {} }
DEVI uint2 ldg_rlx64(const void* p) { uint2 v; asm volatile("ld.relaxed.gpu.global.v2.b32 {%0,%1}, [%2];" : "=r"(v.x), "=r"(v.y) : "l"(p) : "memory"); return v; }
DEVI void sts16(uint32_t a, uint32_t x) { asm volatile("st.shared.b16 [%0], %1;" :: "r"(a), "h"((unsigned short)x) : "memory"); }
DEVI void sts128(uint32_t a, uint32_t x) { asm volatile("st.shared.v4.b32 [%0], {%1,%1,%1,%1};" :: "r"(a), "r"(x) : "memory"); }
DEVI void arrive_if_eq(uint32_t bar, int a, int b) { asm volatile("{.reg .pred p; setp.eq.s32 p, %1, %2; @p mbarrier.arrive.shared::cta.b64 _, [%0];}" :: "r"(bar), "r"(a), "r"(b) : "memory"); }
DEVI void arrive_cl_if_eq(uint32_t bar, int a, int b) { asm volatile("{.reg .pred p; setp.eq.s32 p, %1, %2; @p mbarrier.arrive.shared::cluster.b64 _, [%0];}" :: "r"(bar), "r"(a), "r"(b) : "memory"); }
template<int ID, int N> DEVI bool nbar_or(bool x) {
  uint32_t r;
  asm volatile("{.reg .pred p, q; setp.ne.u32 p, %1, 0; bar.red.or.pred q, %2, %3, p; selp.u32 %0, 1, 0, q;}" : "=r"(r) : "r"((uint32_t)x), "n"(ID), "n"(N) : "memory");
  return __any_sync(0xffffffffu, r);
}
DEVI void spin_until(uint32_t t0, int d) { while ((int)(clock32() - t0) < d) {} }
DEVI void flag_wait(const int* p, int n, int& budget) {
  while (ld_acquire(p) < n && --budget > 0) __nanosleep(128);
  asm volatile("fence.proxy.async.global;" ::: "memory");
}

#define F4(C, o)  C(d[o+0]), C(d[o+1]), C(d[o+2]), C(d[o+3])
#define F8(C, o)  F4(C, o), F4(C, o+4)
#define F32(C, o) F8(C, o), F8(C, o+8), F8(C, o+16), F8(C, o+24)
#define R4  "{%0,%1,%2,%3}"
#define R8  "{%0,%1,%2,%3,%4,%5,%6,%7}"
#define R16 "{%0,%1,%2,%3,%4,%5,%6,%7,%8,%9,%10,%11,%12,%13,%14,%15}"
#define R20 "{%0,%1,%2,%3,%4,%5,%6,%7,%8,%9,%10,%11,%12,%13,%14,%15,%16,%17,%18,%19}"
#define R32 "{%0,%1,%2,%3,%4,%5,%6,%7,%8,%9,%10,%11,%12,%13,%14,%15,%16,%17,%18,%19,%20,%21,%22,%23,%24,%25,%26,%27,%28,%29,%30,%31}"
#define R64 "{%0,%1,%2,%3,%4,%5,%6,%7,%8,%9,%10,%11,%12,%13,%14,%15,%16,%17,%18,%19,%20,%21,%22,%23,%24,%25,%26,%27,%28,%29,%30,%31," \
  "%32,%33,%34,%35,%36,%37,%38,%39,%40,%41,%42,%43,%44,%45,%46,%47,%48,%49,%50,%51,%52,%53,%54,%55,%56,%57,%58,%59,%60,%61,%62,%63}"
template<uint32_t OFF, uint32_t LBO, uint32_t SBO, uint32_t SW, int T> struct Op {
  static constexpr uint32_t lo = (OFF >> 4) | ((LBO >> 4) << 16), hi = (SBO >> 4) | (SW << 30);
  static constexpr int t = T;
};
DEVI uint32_t desc_base(uint32_t addr) { return (addr & 0x3FFFF) >> 4; }
#define RS_ASM(SHAPE, REGS, A0, A1, A2, A3, B, LO, HI, T, SD) \
  "{.reg .b64 tb; .reg .b32 lb; add.u32 lb, " B ", " LO "; mov.b64 tb, {lb, " HI "};\n" \
  "wgmma.mma_async.sync.aligned." SHAPE ".f32.bf16.bf16 " REGS ", {" A0 "," A1 "," A2 "," A3 "}, tb, " SD ", 1, 1, " T ";}"
#define WG_RS(NAME, SHAPE, REGS, LIST, ...) \
  template<int ACC, class OB> DEVI void NAME(float* d, const uint32_t* a, uint32_t b) { \
    if (ACC) asm volatile(RS_ASM(SHAPE, REGS, __VA_ARGS__) \
      : LIST("+f") : "r"(a[0]), "r"(a[1]), "r"(a[2]), "r"(a[3]), "r"(b), "n"(OB::lo), "n"(OB::hi), "n"(OB::t), "n"(ACC & 1)); \
    else asm volatile(RS_ASM(SHAPE, REGS, __VA_ARGS__) \
      : LIST("=f") : "r"(a[0]), "r"(a[1]), "r"(a[2]), "r"(a[3]), "r"(b), "n"(OB::lo), "n"(OB::hi), "n"(OB::t), "n"(0)); \
  }
#define SS_ASM(SHAPE, REGS, A, B, LA, HA, TA, LB, HB, TB, SD) \
  "{.reg .b64 ta, tb; .reg .b32 la, lb; add.u32 la, " A ", " LA "; mov.b64 ta, {la, " HA "}; add.u32 lb, " B ", " LB "; mov.b64 tb, {lb, " HB "};\n" \
  "wgmma.mma_async.sync.aligned." SHAPE ".f32.bf16.bf16 " REGS ", ta, tb, " SD ", 1, 1, " TA ", " TB ";}"
#define WG_SS(NAME, SHAPE, REGS, LIST, ...) \
  template<int ACC, class OA, class OB> DEVI void NAME(float* d, uint32_t a, uint32_t b) { \
    if (ACC) asm volatile(SS_ASM(SHAPE, REGS, __VA_ARGS__) \
      : LIST("+f") : "r"(a), "r"(b), "n"(OA::lo), "n"(OA::hi), "n"(OA::t), "n"(OB::lo), "n"(OB::hi), "n"(OB::t), "n"(ACC & 1)); \
    else asm volatile(SS_ASM(SHAPE, REGS, __VA_ARGS__) \
      : LIST("=f") : "r"(a), "r"(b), "n"(OA::lo), "n"(OA::hi), "n"(OA::t), "n"(OB::lo), "n"(OB::hi), "n"(OB::t), "n"(0)); \
  }
#define L4(C)  F4(C, 0)
#define L8(C)  F8(C, 0)
#define L16(C) F8(C, 0), F8(C, 8)
#define L20(C) F8(C, 0), F8(C, 8), F4(C, 16)
#define L32(C) F32(C, 0)
WG_RS(wg_rs8, "m64n8k16", R4, L4, "%4", "%5", "%6", "%7", "%8", "%9", "%10", "%11", "%12")
WG_RS(wg_rs16, "m64n16k16", R8, L8, "%8", "%9", "%10", "%11", "%12", "%13", "%14", "%15", "%16")
WG_RS(wg_rs32, "m64n32k16", R16, L16, "%16", "%17", "%18", "%19", "%20", "%21", "%22", "%23", "%24")
WG_SS(wg_ss32, "m64n32k16", R16, L16, "%16", "%17", "%18", "%19", "%20", "%21", "%22", "%23", "%24")
WG_RS(wg_rs64, "m64n64k16", R32, L32, "%32", "%33", "%34", "%35", "%36", "%37", "%38", "%39", "%40")
WG_SS(wg_ss8, "m64n8k16", R4, L4, "%4", "%5", "%6", "%7", "%8", "%9", "%10", "%11", "%12")
WG_SS(wg_ss16, "m64n16k16", R8, L8, "%8", "%9", "%10", "%11", "%12", "%13", "%14", "%15", "%16")
WG_SS(wg_ss40, "m64n40k16", R20, L20, "%20", "%21", "%22", "%23", "%24", "%25", "%26", "%27", "%28")
WG_SS(wg_ss64, "m64n64k16", R32, L32, "%32", "%33", "%34", "%35", "%36", "%37", "%38", "%39", "%40")
#define L64(C) F32(C, 0), F32(C, 32)
WG_SS(wg_ss128, "m64n128k16", R64, L64, "%64", "%65", "%66", "%67", "%68", "%69", "%70", "%71", "%72")
template<int I> struct IC { __host__ __device__ constexpr operator int() const { return I; } };
template<int I, int N, class F> DEVI void sfor(F&& f) {
  if constexpr (I < N) { f(IC<I>{}); sfor<I + 1, N>(f); }
}

#define R_CL 6
namespace rec {
constexpr int NHI = 36, NLO = 5, NRS = NHI + NLO, NSS = 64 - NRS;
constexpr uint32_t WS = 0;
constexpr uint32_t WO = 2 * NSS * 2048;
constexpr uint32_t RING = WO + 65536;
constexpr uint32_t QB = RING + 40960, RG = 2080, POSQ = 0x64210, POSK = 0xB9753, POSV = 0xEDCA8;
#define JA 2
constexpr uint32_t WA = QB;
constexpr uint32_t OM = QB + 9 * RG, OMS = 2 * RG;
constexpr uint32_t OM2 = QB + 16384, OM2S = 2048;
constexpr uint32_t WH = QB + 20480;
constexpr uint32_t B_PART = QB + 15 * RG - 32, B_ML0 = B_PART + 8, REDO = B_PART + 16;
constexpr uint32_t PM0 = QB + 16384, PM1 = QB + 15 * RG, PM2 = PM1 + 256;
constexpr uint32_t BARS = PM2 + 128;
constexpr uint32_t B_FULL = BARS, B_EMPTY = BARS + 40, B_MLAND = BARS + 80, B_QK = BARS + 112, B_V = BARS + 120, B_OM = BARS + 128,
                   B_WA = BARS + 136, B_SDONE = BARS + 144, B_BFREE = BARS + 152, B_W1 = PM1, B_W2 = PM1 + 8, B_WO = PM1 + 16;
constexpr uint32_t SMEM = BARS + 160;
static_assert(SMEM <= 232448 && QB % 1024 == 0, "smem map");
constexpr int R1 = (PM1 - WO) / 4096;
constexpr int NB_WO = 1, NB_ST = 2, NB_P = 3, NB_TR = 4, NB_X = 5, NB_G = 6, NB_G1 = 7, NB_G2 = 8, NB_G4 = 9, NB_S = 10;
__host__ __device__ constexpr bool is_lo(int j) { return j % 12 == 8; }
__host__ __device__ constexpr int lo_before(int j) { return (j + 3) / 12; }
__host__ __device__ constexpr int ss_before(int j) { return (j - lo_before(j)) * NSS / (64 - NLO); }
__host__ __device__ constexpr bool is_ss(int j) { return ss_before(j + 1) != ss_before(j); }
__host__ __device__ constexpr int reg_idx(int j) { return is_lo(j) ? NHI + lo_before(j) : j - ss_before(j) - lo_before(j); }
template<int j> using OpW = Op<WS + ss_before(j) * 2048, 16, 1024, 1, 1>;
#define P_G1 1
#define P_G2 3
#define P_G2L 0
#define P_OS 1
#define P_NA 6
#define P_G4 10
#define P_G5 12
#define P_FW 1
#define P_SEND 0xff3210ffu
#define P_WB 2
#define P_WOL 0
#define P_G4L 2
#define P_S1 1
#define P_S2 2
#define P_SPEC 1
#define P_S0 3
#define P_MB 0
#define P_S4 5
#define P_S5 8
constexpr uint32_t SLOT1 = 0x32410324, USE1 = 0x22111110;
DEVI bool single(int s) { return s < LAG - 1 || s >= NSEG - 1; }
DEVI uint32_t flip(int s) { return (s < LAG - 1 ? s + 1 : s < NSEG - 1 ? LAG : LAG + s + 1) & 1; }
#define TUN(i, v) (v)
}
#define PROFW(wq, i)
DEVI uint32_t mapr(int h, uint32_t addr, int rank) { return mapa(addr, rank + (R_CL == 6 ? (h & 1) * 3 : 0)); }
template<int N> DEVI void pin(float* d) {
#pragma unroll
  for (int i = 0; i < N; i++) asm volatile("" : "+f"(d[i]) :: "memory");
}
DEVI void keep(const void* a) { asm volatile("{.reg .pred p; setp.eq.u64 p, %0, 0; vote.sync.any.pred p, p, 0xffffffff; @p exit;}" :: "l"(a) : "memory"); }
DEVI int lane_reg() { return __shfl_sync(0xffffffffu, threadIdx.x & 31, threadIdx.x & 31); }
#define LANE_NOW [[maybe_unused]] const int lane = lane0 + ((uint32_t)budget >> 30), g = lane >> 2, c = lane & 3

DEVI void rec_proj(const uint32_t sb, const int h, const int rank, const int w, const CUtensorMap* mW, const CUtensorMap* mWo, const uint32_t zero) {
  using namespace rec;
  const int lane0 = lane_reg(), wg = w >> 2, ww = w & 3;
  int budget = SPIN_BUDGET;
  uint32_t wr[NRS * 4];
  {
    LANE_NOW;
    const uint32_t wsw = ((lane & 7) + (lane >> 4) * 8) * 128 + (((ww * 2 + ((lane >> 3) & 1)) ^ (lane & 7)) << 4);
    mbar_wait(sb + B_W1, 0, budget);
#pragma unroll
    for (int r = 0; r < R1; r++) ldsm4t(sb + WO + (wg * R1 + r) * 2048 + wsw, wr[4*r], wr[4*r+1], wr[4*r+2], wr[4*r+3]);
    fence_proxy_async();
    nbar_sync<NB_ST, 256>();
    if (w == 0) {
      if (lane == 0) { mbar_expect_tx(sb + B_W2, (NRS - R1) * 4096); mbar_expect_tx(sb + B_WO, rank == 2 ? 65536 + 16384 + 8192 : 65536); }
      __syncwarp();
      for (int i = lane; i < 128; i += 32) {
        const int j = i & 63, t = i >> 6, r = reg_idx(j);
        if (!is_ss(j) && r >= R1) tma_load_2d(sb + RING + (t * (NRS - R1) + r - R1) * 2048, mW, h * DH + t * 64, j * 16, sb + B_W2);
      }
      const int t0 = (rank + 1) % 3;
      if (lane < 8) tma_load_2d(sb + WO + lane * 8192, mWo, (3 * ((lane >> 1) + (lane >> 1 >= JA)) + t0) * 64, h * DH + (lane & 1) * 64, sb + B_WO);
      else if (rank < 2 && lane < 10) tma_prefetch_2d(mWo, (3 * JA + t0) * 64, h * DH + (lane & 1) * 64);
      else if (rank == 2 && lane < 11) tma_load_2d(lane < 10 ? sb + WA + (lane - 8) * 8192 : sb + WH, mWo, lane < 10 ? 3 * JA * 64 : 15 * 64, h * DH + (lane > 8) * 64, sb + B_WO);
    }
    mbar_wait(sb + B_W2, 0, budget);
#pragma unroll
    for (int r = R1; r < NRS; r++) ldsm4t(sb + RING + (wg * (NRS - R1) + r - R1) * 2048 + wsw, wr[4*r], wr[4*r+1], wr[4*r+2], wr[4*r+3]);
    fence_proxy_async();
    cluster_arrive(); cluster_wait();
  }
  const uint32_t d0 = desc_base(sb), da = d0 + wg * (NSS * 128);
  const uint32_t pos = rank == 0 ? POSQ : rank == 1 ? POSK : POSV, bar = rank == 2 ? B_V : B_QK;
  uint32_t stg[2][4] = {}, pk[16] = {};
  auto stage = [&](uint32_t* t, int r) {
#pragma unroll
    for (int i = 0; i < 4; i++) asm volatile("xor.b32 %0, %1, %2;" : "+r"(t[i]) : "r"(wr[4 * r + i]), "r"(zero));
  };
#pragma unroll 1
  for (int s = -1; s < NSTEP; s++) {
    const uint32_t fl = flip(s);
    if (s >= 0) {
      float d[8];
      auto steps = [&](auto J0, auto J1, auto A0) {
        wg_fence();
        sfor<J0, J1>([&](auto J) {
          constexpr int j = J, acc = j ? 1 : A0;
          typedef Op<RING + j * 512, 256, 128, 0, 1> OB;
          if constexpr (is_ss(j)) wg_ss16<acc, OpW<j>, OB>(d, da, d0);
          else wg_rs16<acc, OB>(d, is_lo(j) ? stg[lo_before(j) & 1] : wr + 4 * reg_idx(j), d0);
        });
        wg_commit();
      };
      stage(stg[0], NHI);
      mbar_wait(sb + (P_SPEC ? B_ML0 : B_FULL), P_SPEC ? s & 1 : 0, budget);
      PROFW(0, 16);
      sfor<0, 8>([&](auto E) {
        constexpr int e = E, q = e >> 1;
        steps(IC<8 * e>{}, IC<8 * e + 8>{}, IC<0>{});
        if constexpr (e == 1 && P_SPEC) {
          mbar_wait(sb + B_FULL, 0, budget);
          if (__any_sync(0xffffffffu, lds32v(sb + REDO))) { wg_wait<0>(); steps(IC<0>{}, IC<16>{}, IC<2>{}); }
        }
        if constexpr (((P_SEND >> (4 * e)) & 15) == 0) { if (s > 0) mbar_wait(sb + B_BFREE, (s & 1) ^ 1, budget); }
        if constexpr (e > 0 && !(e & 1)) {
          wg_wait<1>();
          arrive_if_eq(sb + B_EMPTY + 8 * (q - 1), lane0, ww * 32);
        }
        if constexpr (!(e & 1)) stage(stg[(q + 1) & 1], NHI + q + 1);
        if constexpr (e < 6 && (e & 1) == P_FW) mbar_wait(sb + B_FULL + 8 * (q + 1), q ? fl : 0, budget);
        if constexpr (((P_SEND >> (4 * e)) & 15) < 4) {
          constexpr int n = (P_SEND >> (4 * e)) & 15;
          LANE_NOW;
          const uint32_t r = mapr(h, sb, n >> 1);
          uint32_t t[4];
#pragma unroll
          for (int i = 0; i < 4; i++) { if (n == 0) t[i] = pk[i]; else asm volatile("xor.b32 %0, %1, %2;" : "=r"(t[i]) : "r"(pk[4*n+i]), "r"(zero)); }
          st_cl128(rank == n >> 1, r + QB + ((pos >> (4 + 4 * c)) & 15) * RG + w * 256 + (n & 1) * 128 + g * 16, t[0], t[1], t[2], t[3], r + bar);
        }
      });
      LANE_NOW;
      const uint32_t dst = QB + (pos & 15) * RG + w * 256 + lane * 4;
      wg_wait<0>();
      pin<8>(d);
      {
        const uint32_t x0 = pack_bf16(d[0], d[1]), x1 = pack_bf16(d[2], d[3]), y0 = pack_bf16(d[4], d[5]), y1 = pack_bf16(d[6], d[7]);
        const uint32_t r = mapr(h, sb, rank == 0);
        if (rank < 2) { sts32v(sb + dst, rank ? y0 : x0); sts32v(sb + dst + 128, rank ? y1 : x1); fence_proxy_async(); }
        st_async32(r + dst, rank ? x0 : y0, r + bar); st_async32(r + dst + 128, rank ? x1 : y1, r + bar);
        if (rank < 2) e_arrive(sb + B_QK);
        else { const uint32_t r1 = mapr(h, sb, 1); st_async32(r1 + dst, y0, r1 + bar); st_async32(r1 + dst + 128, y1, r1 + bar); }
      }
      PROFW(0, 17);
      if (s == NSTEP - 1) break;
      arrive_if_eq(sb + B_EMPTY + 24, lane0, ww * 32);
    } else e_arrive(sb + B_EMPTY + 8 * ww);
    const bool gate = rank < 2 && s >= 0;
    if (single(s)) {
      float d[16];
      sfor<0, 8>([&](auto C) {
        constexpr int cc = C, sl = (SLOT1 >> (4 * cc)) & 15;
        if constexpr (cc == 0) mbar_wait(sb + B_FULL + 8 * sl, 0, budget);
        if constexpr (cc == P_S1) { if (gate) nbar_sync<NB_G1, 384>(); }
        if constexpr (cc == P_S2) { if (gate) nbar_sync<NB_G2, 384>(); }
        if constexpr (cc == P_S0) nbar_sync<NB_WO, 384>();
        if constexpr (cc == P_S4 || cc == P_S5) { if (gate && cc == (rank ? P_S5 : P_S4)) nbar_sync<NB_G4, 384>(); }
        if constexpr (lo_before(cc * 8 + 8) != lo_before(cc * 8)) stage(stg[0], NHI + lo_before(cc * 8));
        wg_fence();
        sfor<0, 8>([&](auto I) {
          constexpr int i = I, j = cc * 8 + i;
          typedef Op<RING + sl * 8192 + (i >> 2) * 4096 + (i & 3) * 32, 16, 1024, 1, 0> OB;
          if constexpr (is_ss(j)) wg_ss32<j != 0, OpW<j>, OB>(d, da, d0);
          else wg_rs32<j != 0, OB>(d, is_lo(j) ? stg[0] : wr + 4 * reg_idx(j), d0);
        });
        wg_commit();
        if constexpr (cc < 7) {
          constexpr int sn = (SLOT1 >> (4 * cc + 4)) & 15;
          mbar_wait(sb + B_FULL + 8 * sn, ((USE1 >> (4 * cc + 4)) & 1) ^ (sn >> 1 == 1 ? fl : 0), budget);
        }
        wg_wait<0>();
        arrive_if_eq(sb + B_EMPTY + 8 * sl, lane0, ww * 32);
      });
      pin<16>(d);
      if (gate && (rank ? P_S5 : P_S4) == 8) nbar_arrive<NB_G4, 384>();
      PROFW(0, 20);
#pragma unroll
      for (int i = 0; i < 8; i++) pk[i] = pk[8 + i] = pack_bf16(d[4 * (i & 3) + ((i >> 1) & 2)], d[4 * (i & 3) + ((i >> 1) & 2) + 1]);
      continue;
    }
    float d[32];
    sfor<0, 16>([&](auto C) {
      constexpr int cc = C, sl = (cc + 4) % 5;
      if constexpr (cc == 0) mbar_wait(sb + B_FULL + 8 * sl, 0, budget);
      if constexpr (cc == P_G1) { if (gate) nbar_sync<NB_G1, 384>(); }
      if constexpr (cc == P_G2) { if (gate) nbar_sync<NB_G2, 384>(); }
      if constexpr (cc == P_NA) {
        PROFW(0, 18);
        nbar_sync<NB_WO, 384>();
      }
      if constexpr (cc == P_G4 || cc == P_G5) { if (gate && cc == (rank ? P_G5 : P_G4)) nbar_sync<NB_G4, 384>(); }
      wg_fence();
      sfor<0, 4>([&](auto I) {
        constexpr int i = I, j = cc * 4 + i;
        typedef Op<RING + sl * 8192 + i * 32, 16, 1024, 1, 0> OB;
        if constexpr (is_ss(j)) wg_ss64<j != 0, OpW<j>, OB>(d, da, d0);
        else wg_rs64<j != 0, OB>(d, is_lo(j) ? stg[0] : wr + 4 * reg_idx(j), d0);
      });
      wg_commit();
      if constexpr (cc == P_NA) PROFW(0, 19);
      if constexpr (cc < 15) {
        if constexpr (is_lo(cc * 4 + 4)) stage(stg[0], reg_idx(cc * 4 + 4));
        mbar_wait(sb + B_FULL + 8 * ((sl + 1) % 5), ((cc + 5) / 5 + (sl == 1 || sl == 2 ? LAG : 0)) & 1, budget);
      }
      wg_wait<0>();
      arrive_if_eq(sb + B_EMPTY + 8 * sl, lane0, ww * 32);
    });
    pin<32>(d);
    if (gate && (rank ? P_G5 : P_G4) == 16) nbar_arrive<NB_G4, 384>();
    PROFW(0, 20);
#pragma unroll
    for (int i = 0; i < 16; i++) pk[i] = pack_bf16(d[16 * (i >> 3) + 4 * (i & 3) + ((i >> 1) & 2)], d[16 * (i >> 3) + 4 * (i & 3) + ((i >> 1) & 2) + 1]);
  }
}

DEVI float softmax_row(float* v, uint32_t* p) {
  constexpr float SC = 0.08838834764831845f * 1.4426950408889634f;
  float m = fmaxf(fmaxf(fmaxf(fmaxf(v[0], v[1]), fmaxf(v[2], v[3])), fmaxf(fmaxf(v[4], v[5]), fmaxf(v[6], v[7]))), fmaxf(v[8], v[9]));
  m = fmaxf(m, __shfl_xor_sync(0xffffffffu, m, 1));
  m = fmaxf(m, __shfl_xor_sync(0xffffffffu, m, 2));
  const float ms = -m * SC, mh = fmaf(m, -SC, -1.f);
#pragma unroll
  for (int i = 0; i < 10; i++) asm("ex2.approx.ftz.f32 %0, %1;" : "=f"(v[i]) : "f"(fmaf(v[i], SC, i < 8 ? ms : mh)));
#pragma unroll
  for (int n = 0; n < 5; n++) p[n] = pack_bf16(v[2*n], v[2*n+1]);
  return fmaf(v[8] + v[9], 2.f, ((v[0] + v[1]) + (v[2] + v[3])) + ((v[4] + v[5]) + (v[6] + v[7])));
}

template<bool ATT>
DEVI void rec_attn(const uint32_t sb, int h, int rank, int w, const bf16* __restrict__ Wo, const bf16* __restrict__ mem0) {
  using namespace rec;
  const int lane0 = lane_reg();
  int budget = SPIN_BUDGET;
  constexpr int NT = ATT ? 5 : 6;
  uint32_t wl[16];
  if (!ATT) {
    LANE_NOW;
#pragma unroll
    for (int i = 0; i < 16; i++) {
      const int dh = 8 * (i >> 1) + 2 * c;
      const unsigned short* p = (const unsigned short*)Wo + (size_t)(h * DH + dh) * DM + 15 * 64 + 16 * w + 8 * (i & 1) + g;
      wl[i] = p[0] | (uint32_t)p[DM] << 16;
    }
  }
  cluster_arrive(); cluster_wait();
  const uint32_t d0 = desc_base(sb);
  uint32_t pph = 0;
#pragma unroll 1
  for (int s = -1; s < NSTEP; s++) {
    asm volatile("" : "+r"(h), "+r"(rank), "+r"(w));
    const uint32_t sp = s & 1;
    const int t0 = ATT ? rank + 1 : 0;
    const bool more = s + 1 < NSTEP;
    if (s == 0) mbar_wait(sb + B_WO, 0, budget);
    float hold[10] = {0, 0, 0, 0, 0, 0, 0, 0, 0, 0};
    if (ATT && s >= 0) {
      float sc[20];
      LANE_NOW;
      mbar_wait(sb + B_QK, sp, budget);
      PROFW(0, 1);
      fence_proxy_async();
      wg_fence();
      sfor<0, 8>([&](auto K) { constexpr int k = K; wg_ss40<k != 0, Op<QB + k * 256, 128, RG, 0, 1>, Op<QB + 3 * RG + k * 256, 128, 2 * RG, 0, 1>>(sc, d0, d0); });
      wg_commit();
      if (P_G1 < 16 && more) nbar_arrive<NB_G1, 384>();
      wg_wait<0>();
      pin<20>(sc);
      if (w == 3 && more) nbar_arrive<NB_S, 64>();
      PROFW(1, 2);
      if (w == 0) {
        uint32_t p[5];
        float v[10];
#pragma unroll
        for (int i = 0; i < 10; i++) v[i] = sc[4 * (i >> 1) + (i & 1)];
        softmax_row(v, p);
        const uint32_t a = sb + lane * 4;
        sts32v(a + PM0, p[0]); sts32v(a + PM0 + 128, p[1]); sts32v(a + PM1, p[2]); sts32v(a + PM1 + 128, p[3]); sts32v(a + PM2, p[4]);
      }
      if (w || !more) mbar_wait(sb + B_V, sp, budget);
      if (w == 1 && more) e_expect_tx(sb + B_V, 10240);
      if (more) {
        float rs[4], ot[2][4];
        uint32_t one[4];
#pragma unroll
        for (int i = 0; i < 4; i++) one[i] = 0x3F803F80u + ((uint32_t)budget >> (31 - i));
        typedef Op<PM0, 128, 128, 0, 0> P0; typedef Op<PM1, 128, 128, 0, 0> P1; typedef Op<PM2, 0, 128, 0, 0> P2;
        fence_proxy_async();
        nbar_sync<NB_P, 128>();
        PROFW(0, 3);
        wg_fence();
        wg_rs8<0, P0>(rs, one, d0); wg_rs8<1, P1>(rs, one, d0); wg_rs8<1, P2>(rs, one, d0);
        wg_commit();
        sfor<0, 2>([&](auto T) {
          constexpr int t = T;
          wg_ss8<0, Op<QB + 8 * RG + t * 1024, 2 * RG, 128, 0, 0>, P0>(ot[t], d0, d0);
          wg_ss8<1, Op<QB + 12 * RG + t * 1024, RG, 128, 0, 0>, P1>(ot[t], d0, d0);
          wg_ss8<1, Op<QB + 14 * RG + t * 1024, 0, 128, 0, 0>, P2>(ot[t], d0, d0);
        });
        wg_commit();
        if (P_G2 < 16 && !P_G2L) nbar_arrive<NB_G2, 384>();
        const uint32_t oa = w * 256 + lane * 4, r1 = mapr(h, sb, rank ^ 1), r2 = mapr(h, sb, 2);
        mbar_wait(sb + B_SDONE, sp, budget);
        wg_wait<1>();
        pin<4>(rs);
        float i0, i1;
        asm volatile("rcp.approx.ftz.f32 %0, %1;" : "=f"(i0) : "f"(rs[0]));
        asm volatile("rcp.approx.ftz.f32 %0, %1;" : "=f"(i1) : "f"(rs[1]));
        wg_wait<0>();
        pin<4>(ot[0]); pin<4>(ot[1]);
        uint32_t x[4];
#pragma unroll
        for (int j = 0; j < 4; j++) {
          x[j] = pack_bf16(ot[j >> 1][2 * (j & 1)] * i0, ot[j >> 1][2 * (j & 1) + 1] * i1);
          sts32v(sb + OM + rank * OMS + oa + (j >> 1) * 1024 + (j & 1) * 128, x[j]);
        }
        fence_proxy_async();
#pragma unroll
        for (int j = 0; j < 8; j++) {
          const int i = P_OS ? j >> 1 : j & 3;
          if (P_OS ? j & 1 : j >> 2) st_async32(r1 + OM + rank * OMS + oa + (i >> 1) * 1024 + (i & 1) * 128, x[i], r1 + B_OM);
          else st_async32(r2 + OM2 + rank * OM2S + oa + (i >> 1) * 1024 + (i & 1) * 128, x[i], r2 + B_OM);
        }
        e_arrive(sb + B_OM);
        if (P_G2 < 16 && P_G2L) nbar_arrive<NB_G2, 384>();
        PROFW(0, 4);
      }
#pragma unroll
      for (int i = 0; i < 10; i++) hold[i] = w ? sc[4 * (i >> 1) + (i & 1)] : sc[4 * (i >> 1) + 2 + (i & 1)];
    }
    if (more && s >= 0) {
      LANE_NOW;
      char* const pw = (char*)g_part + (uint32_t)((t0 * 16 + w * 4 + (lane >> 3)) * 4096 + h * 128 + ((lane ^ h) & 7) * 16);
      mbar_wait(sb + B_OM, sp, budget);
      if (w == 0) nbar_arrive<NB_G, 128>();
      PROFW(1, 5);
      if (!ATT) fence_proxy_async();
      float acc[3][8];
      auto store = [&](auto J) {
        constexpr int j = J;
        float* d = acc[j % 3];
        pin<8>(d);
        uint32_t x[4];
#pragma unroll
        for (int i = 0; i < 4; i++) { const uint32_t m = (h >> 3) == i; x[i] = (pack_bf16(d[2*i], d[2*i+1]) & ~m) | (m & ~sp); }
        stg_rlx128(pw + j * (48 * 4096), x[0], x[1], x[2], x[3]);
        if constexpr (ATT && j == JA) nbar_arrive<NB_TR, 160>();
        if constexpr (j == 2) PROFW(3, 26);
      };
      sfor<0, NT>([&](auto J) {
        constexpr int j = J;
        if constexpr (ATT && j == JA) { mbar_wait(sb + B_WA, sp, budget); PROFW(2, 0); }
        wg_fence();
        sfor<0, 8>([&](auto K) {
          constexpr int k = K;
          typedef Op<(ATT ? OM : OM2) + k * 256, 128, ATT ? OMS : OM2S, 0, 1> OB;
          if constexpr (j == 5 && k < 4) wg_rs16<k ? 1 : 2, OB>(acc[j % 3], wl + 4 * k, d0);
          else wg_ss16<k ? 1 : j < 3 ? 0 : 2, Op<(j == JA ? WA : j < 5 ? WO + (j - (j > JA)) * 16384 : WH - 8192) + k * 2048, 16, 1024, 1, 1>, OB>(acc[j % 3], d0, d0);
        });
        wg_commit();
        if constexpr (j == 0) { if (w == 3) e_expect_tx(sb + B_OM, ATT ? 2048 : 4096); }
        if constexpr (j == NT - 1 && !P_WOL) nbar_arrive<NB_WO, 384>();
        if constexpr (j > 0 && j != P_WB + 1) { wg_wait<1>(); store(IC<j - 1>{}); }
        if constexpr (j == P_WB || j == NT - 1) { wg_wait<0>(); store(IC<j>{}); }
        if constexpr (j == P_WB) {
          const uint32_t t = clock32();
          if (ATT) {
            if (w == 3 && lane < 14) sts128(sb + PM1 + lane * 16, (lane >> 1) == 3 ? 0x3F803F80u : 0);
            if (w == 3 || P_MB) fence_proxy_async();
            nbar_sync<NB_P, 128>();
          } else if (P_MB) fence_proxy_async();
          spin_until(t, TUN(8, 100));
        }
      });
      if (P_WOL) { spin_until(clock32(), TUN(9, 0)); nbar_arrive<NB_WO, 384>(); }
    } else if (more) nbar_arrive<NB_WO, 384>();
    PROFW(0, 6);
    asm volatile("" : "+r"(h), "+r"(rank), "+r"(w));
#pragma unroll 1
    for (int pass = 0; ATT && pass < 2; pass++)
    if (pass != rank) {
      LANE_NOW;
      const int lim = 8 * (g >> 1) + (g & 1) + 2 * w - 8 * c;
      uint32_t p[5];
#pragma unroll
      for (int i = 0; i < 8; i++) hold[2+i] = i <= lim ? hold[2+i] : -INFINITY;
      const float psum = softmax_row(hold, p);
#pragma unroll
      for (int i = 0; i < 5; i++) hold[i] = __uint_as_float(p[i]);
      hold[5] = psum;
    } else if (more) {
      LANE_NOW;
      const int blk = rank * 32 + (h ^ 16);
      char* const mw = (char*)g_mem + (uint32_t)(sp * 32768 + blk * 512 + w * 128 + lane * 4);
      uint32_t v0 = 0;
      if (s == -1 || (s == LAG - 1 && (w & 1))) {
        const unsigned short* q = (const unsigned short*)mem0 + c * 2 * DM + blk * 16 + (w >> 1) * 8 + g;
        v0 = q[0] | (uint32_t)q[DM] << 16;
        if (v0 == 0) v0 = 0x8000u;
      }
      keep(mw);
      if (s >= 0) {
        const uint32_t ca = sb + WA + lane * 128 + (((2 * w) ^ lane) & 7) * 16 + (lane >> 3) * 4;
        const uint32_t sa = sb + OM + (((g >> 1) & 1) * 2 + (g >> 2)) * 128 + (2 * c + (w >> 1)) * 16 + (w & 1) * 8 + (g & 1) * 2;
        const bool g4l = P_G4L == 1 || (P_G4L == 2 && single(s));
        for (bool first = true; ; first = false) {
          float r[4];
          mbar_wait(sb + B_PART, pph, budget);
          PROFW(0, 11);
          pph ^= 1;
          wg_fence();
          sfor<0, 8>([&](auto K) { constexpr int k = K; wg_ss8<k != 0, Op<WA + k * 2048, 16, 1024, 1, 1>, Op<PM1 + (6 - (k & 6)) * 16, 0, 128, 0, 0>>(r, d0, d0); });
          wg_commit();
          if (!g4l && first) nbar_arrive<NB_G4, 384>();
          const uint32_t x0 = lds32v(ca), x1 = lds32v(ca + 4096), x2 = lds32v(ca + 8192), x3 = lds32v(ca + 12288);
          bool bad = __any_sync(0xffffffffu, (sp ? x0 | x1 | x2 | x3 : ~(x0 & x1 & x2 & x3)) & 1) && budget > 0;
          wg_wait<0>();
          pin<4>(r);
          uint32_t y = pack_bf16(r[0], r[2]);
          y |= (y & 0xffffu) ? 0 : 0x8000u;
          y |= (y >> 16) ? 0 : 0x80000000u;
          if (bad) y = 0;
          sts16(sa, y); sts16(sa + 4, y >> 16);
          nbar_sync<NB_P, 128>();
          y = lds32v(sb + OM + w * 128 + lane * 4);
          const bool ok = !__any_sync(0xffffffffu, y == 0);
          if (ok) stg_rlx32(mw, v0 ? v0 : y);
          if (g4l && first) nbar_arrive<NB_G4, 384>();
          if (ok) break;
          nbar_sync<NB_P, 128>();
          budget--;
          if (w == 0) { e_expect_tx(sb + B_PART, 16384); e_bulk_g2s(sb + WA, (const char*)g_part + blk * 16384, 16384, sb + B_PART); }
          __syncwarp();
        }
        nbar_sync<NB_P, 128>();
        if (w < 2) e_arrive_cl(mapr(h, sb + B_BFREE, w));
      } else stg_rlx32(mw, v0);
      stg_rlx32(mw + (sp ? -32768 : 32768), 0);
      PROFW(1, 8);
    }
    if (ATT && s >= 0) {
      const int seg = s - (rank ? LAG : 0);
      const bool act = (unsigned)seg < NSEG;
      LANE_NOW;
      uint32_t a[12];
#pragma unroll
      for (int i = 0; i < 12; i++) a[i] = __float_as_uint(hold[i < 10 ? i >> 1 : 4]) + ((uint32_t)budget >> (31 - (i & 3)));
      float o[32], inv, psum = hold[5];
      char* const ob = (char*)g_o[rank] + ((size_t)(seg * 32 + 8 * (g >> 1) + (g & 1) + 2 * w) * (NH * DH) + h * DH + c * 8) * 2;
      sfor<0, 2>([&](auto HF) {
        constexpr int hf = HF;
        wg_fence();
        wg_rs64<hf * 2, Op<QB + 8 * RG + hf * 1024, 2 * RG, 128, 0, 0>>(o, a, d0);
        wg_rs64<1, Op<QB + 12 * RG + hf * 1024, RG, 128, 0, 0>>(o, a + 4, d0);
        wg_rs64<1, Op<QB + 14 * RG + hf * 1024, 0, 128, 0, 0>>(o, a + 8, d0);
        wg_commit();
        if constexpr (hf == 0) {
          psum += __shfl_xor_sync(0xffffffffu, psum, 1);
          psum += __shfl_xor_sync(0xffffffffu, psum, 2);
          asm("rcp.approx.ftz.f32 %0, %1;" : "=f"(inv) : "f"(psum));
        }
        wg_wait<0>();
        pin<32>(o);
        if constexpr (hf == 1) { if (w == 2 && more) e_arrive_cl(mapr(h, sb + B_BFREE, 2)); }
        if (act) {
#pragma unroll
          for (int i = 0; i < 2; i++)
            stg128(ob + (hf * 2 + i) * 64, pack_bf16(o[16*i] * inv, o[16*i+1] * inv), pack_bf16(o[16*i+4] * inv, o[16*i+5] * inv),
                   pack_bf16(o[16*i+8] * inv, o[16*i+9] * inv), pack_bf16(o[16*i+12] * inv, o[16*i+13] * inv));
        }
      });
      PROFW(0, 7);
      if (act && (seg & 3) == 3) {
        nbar_sync<NB_P, 128>();
        if (w == 0) e_flag_add(g_fl.dep + grp(0, rank, seg >> 2), 4);
      }
    } else if (!ATT && w == 3) {
      if (s + 4 < NSEG) e_prefetch(g_xn[0] + (size_t)((s + 4) * 32 + h) * DM, 2048);
    }
  }
  cluster_arrive(); cluster_wait();
  char* const pw = (char*)g_part + (size_t)((ATT ? rank + 1 : 0) * 16 + w * 4 + (lane0 >> 3)) * 4096 + h * 128 + (lane0 & 7) * 16;
#pragma unroll
  for (int j = 0; j < NT; j++) stg_rlx128(pw + j * (48 * 4096), 0, 0, 0, 0);
}

DEVI void rec_load(const uint32_t sb, const int h, const int rank, const int w, const CUtensorMap* mX, const CUtensorMap* mWo) {
  using namespace rec;
  static_assert(((NSTEP - 1) & 31) > 3, "stale time stamps of the previous launch never match");
  const int lane0 = lane_reg(), mq = (w + 3) & 3;
  int budget = SPIN_BUDGET;
  if (w == 0) { e_flag_add(g_fl.xn[0][0]); flag_wait(g_fl.xn[0][0], 96, budget); }
  bool late = false;
  cluster_arrive(); cluster_wait();
  if (w == 0) { if (lane0 < 4) mbar_arrive(sb + B_FULL + 8 * lane0); __syncwarp(); }
  uint32_t lph = 0;
#pragma unroll 1
  for (int s = -1; s < NSTEP - 1; s++) {
    if (w == 0) {
      if (late) flag_wait(g_fl.xn[1][(s + 1 - LAG) >> 2], 128, budget);
      if (single(s)) {
#pragma unroll 1
        for (int i = 0; i < 8; i++) {
          const int k = i < 5 ? (0x21430 >> (4 * i)) & 15 : i;
          const int sl = (SLOT1 >> (4 * k)) & 15;
          mbar_wait(sb + B_EMPTY + 8 * sl, (((USE1 >> (4 * k)) ^ (sl >> 1 == 1 ? flip(s) : 0)) & 1) ^ 1, budget);
          e_expect_tx(sb + B_FULL + 8 * sl, 8192);
          e_tma_3d(sb + RING + sl * 8192, mX + 1, 0, (s + 1 + (s < LAG ? 0 : NSTEP)) * 32, k * 2, sb + B_FULL + 8 * sl);
        }
      } else {
        int sl = 4, ph = 1;
#pragma unroll 1
        for (int i = 0; i < 16; i++) {
          mbar_wait(sb + B_EMPTY + 8 * sl, ph ^ (sl >> 1 & LAG & 1), budget);
          e_expect_tx(sb + B_FULL + 8 * sl, 8192);
          e_tma_3d(sb + RING + sl * 8192, mX, i * 64, (s + 1) * 32, 0, sb + B_FULL + 8 * sl);
          if (++sl == 5) { sl = 0; ph ^= 1; }
        }
      }
      nbar_arrive<NB_X, 128>();
      const int sn = s + 2 - LAG;
      late = (sn & 3) == 0 && (unsigned)sn < NSEG && ld_acquire(g_fl.xn[1][sn >> 2]) < 128;
      asm volatile("fence.proxy.async.global;" ::: "memory");
    }
    uint32_t t = gtime();
    if (s >= 0) {
      uint2 a;
      if (w == 2 && rank < 2) {
        nbar_sync<NB_S, 64>();
        e_expect_tx(sb + B_WA, 16384);
        e_tma_2d(sb + WA, mWo, (3 * JA + 1 + rank) * 64, h * DH, sb + B_WA);
        e_tma_2d(sb + WA + 8192, mWo, (3 * JA + 1 + rank) * 64, h * DH + 64, sb + B_WA);
        e_arrive_cl(mapr(h, sb + B_SDONE, rank ^ 1));
        stg_rlx32(&g_ann[s & 1][lane0][h * 2 + rank], (gtime() & ~31u) | ((s + 1) & 31));
        e_expect_tx(sb + B_QK, 10240);
      }
      if (w) nbar_sync<NB_G, 128>();
      do { a = ldg_rlx64(&g_ann[s & 1][h][lane0 * 2]); } while (__any_sync(0xffffffffu, ((a.x ^ (s + 1)) | (a.y ^ (s + 1))) & 31) && --budget > 0);
      t += __reduce_max_sync(0xffffffffu, max((int)(a.x - t), (int)(a.y - t)));
      t &= ~31u;
      PROFW(1, 12);
      if (w == 1 && rank < 2) {
        nbar_sync<NB_TR, 160>();
        e_expect_tx(sb + B_PART, 16384);
        wait_time(t + (single(s) ? (rank ? TUN(11, 1600) : TUN(10, 1200)) : rank ? TUN(1, 1700) : TUN(0, 1300)), budget);
        e_bulk_g2s(sb + WA, (const char*)g_part + (rank * 32 + (h ^ 16)) * 16384, 16384, sb + B_PART);
        PROFW(1, 21);
      }
      t += single(s) ? (mq == 0 ? TUN(12, 2050) : mq == 1 ? TUN(13, 2250) : mq == 2 ? TUN(14, 2500) : TUN(15, 2750))
                     : (mq == 0 ? TUN(2, 2250) : mq == 1 ? TUN(3, 2450) : mq == 2 ? TUN(4, 2700) : TUN(5, 2950));
    }
    if (w) nbar_sync<NB_X, 128>();
    mbar_wait(sb + B_EMPTY + 8 * mq, mq >= 2 ? flip(s + 1) ^ 1 : 1, budget);
    PROFW(1, 9);
    uint32_t bar = sb + (P_SPEC && mq == 0 ? B_ML0 : B_MLAND + 8 * mq), redo = 0;
    e_expect_tx(bar, 8192);
    wait_time(t, budget);
    PROFW(1, 22); PROFW(3, 23);
    while (true) {
      e_bulk_g2s(sb + RING + mq * 8192, (const char*)g_mem + (s & 1) * 32768 + mq * 8192, 8192, bar);
      const uint32_t a = sb + RING + mq * 8192 + lane0 * 32 + (lane0 >> 2) * 4;
      if (bar == sb + B_ML0) mbar_wait(bar, (s + 1) & 1, budget);
      else { mbar_wait(bar, lph, budget); lph ^= 1; }
      PROFW(1, 24);
      uint32_t mn = 0xffffffffu;
#pragma unroll
      for (int i = 0; i < 8; i++) mn = min(mn, lds32v(a + i * 1024));
      if (!__any_sync(0xffffffffu, mn == 0) || --budget <= 0) break;
      bar = sb + B_MLAND + 8 * mq; redo = 1;
      e_expect_tx(bar, 8192);
    }
    if (mq == 0) sts32v(sb + REDO, redo);
    e_arrive(sb + B_FULL + 8 * mq);
    PROFW(1, 10); PROFW(2, 13); PROFW(3, 14); PROFW(0, 15);
  }
}

DEVI void ln_row(const uint4* u, bf16* dst, int lane) {
  const uint32_t* x = (const uint32_t*)u;
  float mean = 0, q = 0;
#pragma unroll
  for (int i = 0; i < 16; i++) mean += bf_lo(x[i]) + bf_hi(x[i]);
  mean *= 1.f / 32;
#pragma unroll
  for (int i = 0; i < 16; i++) { const float a = bf_lo(x[i]) - mean, b = bf_hi(x[i]) - mean; q = fmaf(a, a, fmaf(b, b, q)); }
#pragma unroll
  for (int o = 1; o < 32; o *= 2) {
    const float m2 = __shfl_xor_sync(0xffffffffu, mean, o), q2 = __shfl_xor_sync(0xffffffffu, q, o), dl = m2 - mean;
    q = fmaf(dl * dl, 16.f * o, q + q2);
    mean = 0.5f * (mean + m2);
  }
  const float rs = rsqrtf(q * (1.f / DM) + 1e-5f), mr = -mean * rs;
#pragma unroll
  for (int i = 0; i < 4; i++) {
    uint32_t y[4];
#pragma unroll
    for (int k = 0; k < 4; k++) y[k] = pack_bf16(fmaf(bf_lo(x[4*i+k]), rs, mr), fmaf(bf_hi(x[4*i+k]), rs, mr));
    stg128((uint4*)dst + i * 32 + lane, y[0], y[1], y[2], y[3]);
  }
}

struct RecMaps { CUtensorMap w[3], wo, x[2]; };
__global__ void __cluster_dims__(R_CL, 1, 1) __launch_bounds__(512, 1)
rec_kernel(const __grid_constant__ RecMaps M, const bf16* __restrict__ Wo, const bf16* __restrict__ mem0, const bf16* __restrict__ x, uint32_t zero) {
  using namespace rec;
  extern __shared__ __align__(1024) uint8_t smem[];
  const uint32_t sb = smem_u32(smem);
  const int tid = threadIdx.x, warp = __shfl_sync(0xffffffffu, tid >> 5, 0), wg = warp >> 2, lane = tid & 31;
  const int h = blockIdx.x / 3, rank = blockIdx.x % 3;
  if (warp == 0) {
    if (lane < 20) mbar_init(sb + BARS + 8 * lane, (lane >= 5 && lane < 10) || lane == 19 ? 2 : lane == 14 ? 9 : lane == 16 && rank < 2 ? 5 : 1);
    else if (lane < 23) mbar_init(sb + B_W1 + 8 * (lane - 20), 1);
    else if (lane < 25) mbar_init(sb + B_PART + 8 * (lane - 23), 1);
    fence_mbar_init();
    __syncwarp();
    if (lane == 0) { mbar_expect_tx(sb + B_W1, (NSS + R1) * 4096); mbar_expect_tx(sb + B_QK, 10240); mbar_expect_tx(sb + B_V, 10240); mbar_expect_tx(sb + B_OM, rank < 2 ? 2048 : 4096); }
    __syncwarp();
    for (int i = lane; i < 128; i += 32) {
      const int j = i >> 1, t = i & 1, r = reg_idx(j);
      if (is_ss(j)) tma_load_2d(sb + WS + (t * NSS + ss_before(j)) * 2048, &M.w[rank], h * DH + t * 64, j * 16, sb + B_W1);
      else if (r < R1) tma_load_2d(sb + WO + (t * R1 + r) * 2048, &M.w[rank], h * DH + t * 64, j * 16, sb + B_W1);
      else tma_prefetch_2d(&M.w[rank], h * DH + t * 64, j * 16);
    }
  } else if (warp == 1) {
    constexpr int N = (sizeof(Flags) - sizeof(g_fl.xn)) / 16;
    if (lane < 8 && blockIdx.x * 8 + lane < N) ((uint4*)g_fl.dep)[blockIdx.x * 8 + lane] = make_uint4(0, 0, 0, 0);
    static_assert(N <= 96 * 8, "flag reset");
    if (blockIdx.x < 64) ((uint4*)g_stat[4])[blockIdx.x * 64 + lane] = ((uint4*)g_stat[4])[blockIdx.x * 64 + 32 + lane] = make_uint4(0, 0, 0, 0);
    __threadfence();
    __syncwarp();
    asm volatile("griddepcontrol.launch_dependents;" ::: "memory");
  } else if (warp >= 5 && blockIdx.x * 11 + warp - 5 < SEQ / 2) {
    const size_t o = (size_t)(blockIdx.x * 11 + warp - 5) * (2 * DM);
    uint4 u[8];
#pragma unroll
    for (int i = 0; i < 8; i++) u[i] = __ldg((const uint4*)(x + o) + i * 32 + lane);
    ln_row(u, g_xn[0] + o, lane);
    ln_row(u + 4, g_xn[0] + o + DM, lane);
  }
  __syncthreads();
  if (wg == 3) {
    reg_dec<24>();
    rec_load(sb, h, rank, warp & 3, M.x, &M.wo);
    cluster_arrive(); cluster_wait();
  } else if (wg == 2) {
    reg_dec<72>();
    if (rank < 2) rec_attn<true>(sb, h, rank, warp & 3, Wo, mem0);
    else rec_attn<false>(sb, h, rank, warp & 3, Wo, mem0);
  } else {
    reg_inc<208>();
    rec_proj(sb, h, rank, warp, &M.w[rank], &M.wo, zero);
    cluster_arrive(); cluster_wait();
  }
}

namespace gm {
constexpr int STAGES = 6, STAGE_BYTES = 32768;
constexpr uint32_t SO = STAGES * STAGE_BYTES, B_FULL = SO + 32768, B_TRIG = B_FULL + 56, B_EMPTY = B_FULL + 64, B_JOB = B_FULL + 128,
                   B_MSG = B_FULL + 144, B_XF = B_FULL + 160, B_SF = B_FULL + 176, JOB = B_FULL + 192, MSG = JOB + 8, SMEM = B_FULL + 256;
constexpr int T_O = 0, T_GU = 1, T_D = 2, T_END = 3;
#define G_LOOK 8
#define G_FILL 7
#define G_SLEEP 100
#define G_SLEEP2 500
#define G_SLEEP3 100
#define G_DF 0
#define G_FL 10
#define G_DE 0
#define G_DS 16
DEVI bool is_split(int ty, int l, int cb) { return ty == T_O || (ty == T_D && (!l || cb >= G_DS)); }
#define G_ROLES 16, 17, 8, 9, 10, 0, 1, 2, 3, 4, 5, 6, 7, 11, 12, 13, 14, 15
constexpr uint64_t pack_roles(int i0, int i1) { constexpr int r[18] = {G_ROLES}; uint64_t v = 0; for (int i = i0; i < i1; i++) v |= (uint64_t)r[i] << (5 * (i - i0)); return v; }
constexpr uint64_t ROLE0 = pack_roles(0, 12), ROLE1 = pack_roles(12, 18);
struct Pipe { int s, ph; DEVI void next() { if (++s == STAGES) { s = 0; ph ^= 1; } } };
}
struct GemmMaps { CUtensorMap o, wo, x, x1, x1s, xm, xms, xn, wg, wu, h, hs, wd, x2, out, outs; };

DEVI float geglu(float g, float u) {
  const float z = g * (0.7978845608028654f + 0.035677408136300125f * g * g);
  float t; asm("tanh.approx.f32 %0, %1;" : "=f"(t) : "f"(z));
  const float hg = 0.5f * g;
  return fmaf(hg, t, hg) * u;
}
DEVI int h_ready(int v) { const int t = v ^ 0x10141014; return t & 0xff0000ff ? 0 : t & 0xff00 ? 20 : t ? 36 : 56; }
DEVI int a_ready(int ty, int l, int cb) {
  const int v = ld_acquire(g_fl.dep + grp(ty, l, cb));
  asm volatile("fence.proxy.async.global;" ::: "memory");
  return ty == gm::T_D ? h_ready(v) : v >= (ty == gm::T_O && l ? 256 : 128) ? 64 : 0;
}

__global__ void __cluster_dims__(2, 1, 1) __launch_bounds__(512, 1) gemm_kernel(const __grid_constant__ GemmMaps M) {
  using namespace gm;
  extern __shared__ __align__(1024) uint8_t smem[];
  const uint32_t sb = smem_u32(smem);
  const int tid = threadIdx.x, wid = __shfl_sync(0xffffffffu, tid >> 5, 0), wg = wid >> 2, warp = wid & 3;
  int budget = SPIN_BUDGET;
  const int rank = blockIdx.x & 1;
  const uint32_t peer = mapa(sb, rank ^ 1);
  if (tid < 24) mbar_init(sb + B_FULL + 8 * tid, tid >> 3 == 1 ? 2 : 1);
  fence_mbar_init();
  if (wid == 1 && rank == 0) {
    uint32_t sm; asm volatile("mov.u32 %0, %%smid;" : "=r"(sm));
    const bool crowd = sm >= 124 || sm < 50;
    const int t = bcast(e_ticket(g_fl.ticket, crowd ? 1 : 256)), a = t & 255, b = t >> 8, i = crowd ? a : 17 - b;
    sts32v(sb + JOB + 16, a + b >= 18 ? a + b : (int)((i < 12 ? ROLE0 >> (5 * i) : ROLE1 >> (5 * i - 60)) & 31));
  }
  cluster_arrive(); cluster_wait();
  int pair;
  asm volatile("ld.shared::cluster.u32 %0, [%1];" : "=r"(pair) : "r"(mapa(sb + JOB + 16, 0)) : "memory");
  pair = __shfl_sync(0xffffffffu, pair, 0);
  const int cta = pair * 2 + rank, lane = lane_reg();
  if (wg >= 2) {
    reg_dec<72>();
    if (wid == 8 || wid == 10) {
      Pipe p; p.s = 0; p.ph = 1;
      for (int n = 0; ; n++) {
        if (wid == 8) e_expect_tx(sb + B_MSG + 8 * (n & 1), 4);
        mbar_wait(sb + B_MSG + 8 * (n & 1), (n >> 1) & 1, budget);
        const int msg = __shfl_sync(0xffffffffu, lds32v(sb + MSG + 4 * (n & 1)), 0);
        const int ty = (msg >> 11) & 3, l = (msg >> 10) & 1;
        const bool shb = ty == T_GU && l, spl = is_split(ty, l, (msg >> 6) & 15);
        const int cb = ((msg >> 6) & 15) + (shb ? rank : 0), j = (msg & 63) + (ty == T_END || shb ? 0 : rank);
        const int ke = ty == T_O ? 64 : ty == T_GU ? 16 : 56, k0 = spl ? rank : 0, dk = spl ? 2 : 1;
        const int c0 = ty == T_GU ? j * 64 : spl ? (j >> 1) * 128 : j * 128, c1 = ty == T_GU ? c0 : c0 + 64;
        mbar_wait(sb + B_EMPTY + 8 * p.s, p.ph, budget);
        trap_if_spent(budget);
        auto stages = [&](auto f) {
#pragma unroll 1
          for (int k = k0; k < ke; k += dk) {
            mbar_wait(sb + B_EMPTY + 8 * p.s, p.ph, budget);
            f(k, sb + p.s * STAGE_BYTES, sb + B_FULL + 8 * p.s);
            p.next();
          }
        };
        if (wid == 8) {
          const int job = ty << 11 | l << 10 | cb << 6 | j;
          sts32v(sb + JOB + 4 * (n & 1), job | p.s << 16 | (p.ph ^ 1) << 20);
          e_arrive(sb + B_JOB + 8 * (n & 1));
          if (ty == T_END) break;
          if (ty != T_GU) { e_expect_tx(sb + B_FULL + 8 * p.s, spl ? 16384 : STAGE_BYTES); p.next(); }
          const CUtensorMap* const m0 = ty == T_D ? &M.wd : shb && rank ? &M.wu : &M.wg, * const m1 = ty == T_D ? &M.wd : &M.wu;
          if (ty == T_O) stages([&](int k, uint32_t a, uint32_t fb) { e_expect_tx(fb, STAGE_BYTES); e_tma_5d(a + 16384, &M.wo, c0, k * 2, fb); e_tma_5d(a + 24576, &M.wo, c1, k * 2, fb); });
          else if (shb) stages([&](int k, uint32_t a, uint32_t fb) { e_expect_tx(fb, STAGE_BYTES); e_tma_2d_mc(a + 16384 + rank * 8192, m0, c0, k * 64, fb); });
          else stages([&](int k, uint32_t a, uint32_t fb) { e_expect_tx(fb, STAGE_BYTES); e_tma_2d(a + 16384, m0, c0, k * 64, fb); e_tma_2d(a + 24576, m1, c1, k * 64, fb); });
        } else {
          if (ty == T_END) break;
          const int row = l * SEQ + cb * 128, kt = ke + k0 - G_LOOK * dk;
          const uint64_t polA = ty != T_GU ? EVICT_FIRST : EVICT_NORMAL;
          int rdy = msg >> 16;
          auto need = [&](int k) {
            if (k == kt) e_arrive(sb + B_TRIG);
            while (k >= rdy && k >= (rdy = a_ready(ty, l, cb))) { __nanosleep(G_SLEEP); trap_if_spent(--budget); }
          };
          if (ty != T_GU) {
            need(0);
            const uint32_t a = sb + p.s * STAGE_BYTES, fb = sb + B_FULL + 8 * p.s;
            const CUtensorMap* const m = ty == T_D ? (spl ? &M.x1 : &M.x1s) : l ? &M.x2 : &M.x;
            const int r = (ty == T_D ? row : cb * 128) + (spl ? rank * 64 : 0);
            e_tma_2d(a, m, c0, r, fb, polA); e_tma_2d(a + 16384, m, c1, r, fb, polA);
            p.next();
          }
          if (shb || spl) {
            const CUtensorMap* const ma = ty == T_O ? &M.o : ty == T_GU ? &M.xms : &M.hs;
            stages([&](int k, uint32_t a, uint32_t fb) { need(k); e_tma_2d(a, ma, k * 64, row, fb, polA); });
          } else {
            const CUtensorMap* const ma = ty == T_GU ? &M.xm : &M.h;
            stages([&](int k, uint32_t a, uint32_t fb) { need(k); e_tma_2d_mc(a + rank * 8192, ma, k * 64, row + rank * 64, fb, polA); });
          }
        }
      }
    } else if (wid == 9 && rank == 0) {
      int k1 = pair < 18 ? 0 : 48;
      bool late = false;
      for (int n = 0, ty = 0; ty != T_END; n++) {
        mbar_wait(sb + B_TRIG, (n & 1) ^ 1, budget);
        int l, cb, j, rdy = 64;
        while (true) {
          const int ph = k1 % 3;
          const bool gap = pair < 8 ? ph == 1 : pair >= 16 && ph == 2;
          if (k1 < 48) {
            cb = k1++ / 3;
            if (gap && (late || !(G_FILL & (pair < 8 ? 1 : 2)))) continue;
            if (!gap) {
              l = 0;
              ty = pair < 8 ? (ph ? T_GU : T_O) : ph == 2 ? T_D : T_GU;
              j = 2 * (pair < 8 ? (ph ? pair + 10 : pair) : ph == 1 ? pair + 10 : pair - 8);
              rdy = a_ready(ty, 0, cb);
              if (ph == 0) late = rdy != 0;
              break;
            }
          }
          int d0 = ld_relaxed(g_fl.dep + lane), d1 = ld_relaxed(g_fl.dep + 32 + lane);
          const int t0 = ld_relaxed(g_fl.taken + lane), t1 = ld_relaxed(g_fl.taken + 32 + lane);
          const bool l0 = t0 < (lane < 16 ? 8 : lane & 1 ? 0 : 56), l1 = lane < 16 && t1 < (lane < G_DS ? 4 : 8);
          const uint32_t rd = __ballot_sync(0xffffffffu, d0 >= (lane < 16 ? 256 : 128));
          uint32_t ok0 = __ballot_sync(0xffffffffu, l0) & rd & (rd >> 1 | 0xffff), ok1 = __ballot_sync(0xffffffffu, l1 && h_ready(d1) > 0);
          if (gap) { ok1 = 0; if (pair < 16) ok0 &= G_FILL & 4 ? 0xffff0003u : 0xffff0000u; }
          ty = T_END; l = 1; cb = j = 0;
          if (!gap && !__any_sync(0xffffffffu, l0 || l1)) break;
          if (ok1 & ((1u << G_DS) - 1)) ok1 &= (1u << G_DS) - 1;
          const uint32_t dfirst = ok1 & __ballot_sync(0xffffffffu, lane < G_DF && d1 == 0x10141014);
          if (dfirst && !(ok0 & 0xffff)) { ok0 = 0; ok1 = dfirst; }
          else if (__any_sync(0xffffffffu, l0)) ok1 &= (1u << G_DE) - 1;
          uint32_t m = ok0 ? ok0 : ok1;
          if (!m && !gap) __nanosleep(100);
          while (m) {
            const int nth = ok0 ? 0 : pair % __popc(m);
            const int b = __ffs(__ballot_sync(0xffffffffu, __popc(m << (31 - lane)) > nth)) - 1, gn = b + (ok0 ? 0 : 32);
            const int t = bcast(e_ticket(g_fl.taken + gn));
            if (t < (gn < 16 ? 8 : gn < 32 ? 56 : gn < 32 + G_DS ? 4 : 8)) { ty = gn >> 4; cb = gn & 15; j = ty == T_GU ? t : 2 * t; break; }
            m &= ~(1u << b);
          }
          if (ty != T_END) {
            rdy = a_ready(ty, 1, cb);
            if (ty == T_GU) a_ready(ty, 1, cb + 1);
            break;
          }
          trap_if_spent(--budget);
        }
        const int msg = rdy << 16 | ty << 11 | l << 10 | cb << 6 | j;
        e_st_async32(peer + MSG + 4 * (n & 1), msg, peer + B_MSG + 8 * (n & 1));
        e_st_async32(sb + MSG + 4 * (n & 1), msg, sb + B_MSG + 8 * (n & 1));
      }
    } else if (wg == 3) {
      bool open = lane < G_FL && ld_relaxed(g_fl.rows + lane) < 128;
      while (__any_sync(0xffffffffu, open)) {
        int v = 0;
        if (open) asm volatile("ld.acquire.gpu.global.s32 %0, [%1];" : "=r"(v) : "l"(g_fl.part + lane) : "memory");
        const uint32_t ok = __ballot_sync(0xffffffffu, open && v >= 128);
        if (!ok) {
          if (--budget <= 0) break;
          __nanosleep(G_SLEEP2);
          continue;
        }
        const int cb = __ffs(__ballot_sync(0xffffffffu, __popc(ok << (31 - lane)) > (cta >> 5) % __popc(ok))) - 1;
        const int r = bcast(e_ticket(g_fl.rows + cb));
        if (r >= 128) { open = open && lane != cb; continue; }
        uint4 u[4];
#pragma unroll
        for (int i = 0; i < 4; i++) u[i] = ldg_rlx128((const uint4*)(g_x1[1] + (size_t)(cb * 128 + r) * DM) + i * 32 + lane);
        ln_row(u, g_xm[1] + (size_t)(cb * 128 + r) * DM, lane);
        __syncwarp();
        e_flag_add(g_fl.dep + grp(T_GU, 1, cb));
      }
      if (cta == 0 && wid == 12) {
        asm volatile("griddepcontrol.wait;" ::: "memory");
        g_fl.xn[lane >> 4][lane & 15][0] = 0;
        if (NSTEP & 1) for (int i = lane; i < 2048; i += 32) g_mem[1][i] = make_uint4(0, 0, 0, 0);
      }
    }
    cluster_arrive(); cluster_wait();
  } else {
    reg_inc<184>();
    const bool lead = warp == 0;
    const uint32_t eb = (warp == 1 ? peer : sb) + B_EMPTY;
    const int rl = warp < 2 ? 0 : -1;
    const uint32_t so = sb + SO + wg * 16384;
    const int r0 = warp * 16 + (lane & 7) + ((lane >> 3) & 1) * 8;
    const uint32_t sw = r0 * 128 + (((lane >> 4) ^ (r0 & 7)) << 4);
    int xph = 0;
    for (int n = wg; ; n += 2) {
      float d0[64], d1[64];
      mbar_wait(sb + B_JOB + 8 * wg, (n >> 1) & 1, budget);
      fault_if_spent(budget);
      const int job = __shfl_sync(0xffffffffu, lds32v(sb + JOB + 4 * wg), 0);
      const int ty = (job >> 11) & 3, l = (job >> 10) & 1, cb = (job >> 6) & 15, j = job & 63;
      if (ty == T_END) {
        if (n > 0) nbar_sync_r(1 + wg, 256);
        if (lead && !(job & 1)) { sts32v(sb + JOB + 4 * (wg ^ 1), job | 1); e_arrive(sb + B_JOB + 8 * (wg ^ 1)); }
        if (!(job & 1)) nbar_arrive_r(1 + (wg ^ 1), 256);
        break;
      }
      Pipe q; q.s = (job >> 16) & 15; q.ph = job >> 20;
      const bool spl = is_split(ty, l, cb);
      if (ty != T_GU) mbar_wait(sb + B_FULL + 8 * q.s, q.ph, budget);
#pragma unroll
      for (int m = 0; m < 2; m++) {
        float* d = m ? d1 : d0;
        if (ty != T_GU && !(m && spl)) {
#pragma unroll
          for (int c = 0; c < 8; c++) {
            uint32_t r[4];
            ldsm4(sb + q.s * STAGE_BYTES + (c >> 2) * 16384 + m * 8192 + (sw ^ ((c & 3) << 5)), r[0], r[1], r[2], r[3]);
#pragma unroll
            for (int i = 0; i < 4; i++) { d[8*c+2*i] = bf_lo(r[i]); d[8*c+2*i+1] = bf_hi(r[i]); }
          }
        } else {
#pragma unroll
          for (int i = 0; i < 64; i++) d[i] = 0.f;
        }
      }
      if (ty != T_GU) {
        fence_proxy_async();
        nbar_sync_r(3 + wg, 128);
        arrive_cl_if_eq(eb + 8 * q.s, lane, rl);
        q.next();
      }
      pin<64>(d0); pin<64>(d1);
      if (n > 0) nbar_sync_r(1 + wg, 256);
      const int nk = ty == T_O ? 32 : ty == T_GU ? 16 : spl ? 28 : 56;
      const uint32_t ro = spl ? rank * 512 : 0;
      int prev = 0;
      for (int i = 0; i < nk; i++) {
        mbar_wait(sb + B_FULL + 8 * q.s, q.ph, budget);
        const uint32_t da = desc_base(sb) + q.s * (STAGE_BYTES / 16);
        wg_fence();
        sfor<0, 4>([&](auto K) {
          constexpr int k = K;
          typedef Op<16384 + k * 2048, 8192, 1024, 1, 1> OB;
          wg_ss128<1, Op<k * 32, 16, 1024, 1, 0>, OB>(d0, da + ro, da);
          wg_ss128<1, Op<8192 + k * 32, 16, 1024, 1, 0>, OB>(d1, da - ro, da);
        });
        wg_commit();
        wg_wait<1>();
        arrive_cl_if_eq(eb + 8 * prev, lane, i ? rl : -1);
        prev = q.s;
        q.next();
      }
      nbar_arrive_r(1 + (wg ^ 1), 256);
      wg_wait<0>();
      pin<64>(d0); pin<64>(d1);
      arrive_cl_if_eq(eb + 8 * prev, lane, rl);
      if (spl) {
        const uint32_t xa = SO + wg * 16384 + warp * 512 + lane * 16;
        if (lead) e_expect_tx(sb + B_XF + 8 * wg, 16384);
        mbar_wait(sb + B_SF + 8 * wg, ((n >> 1) & 1) ^ 1, budget);
#pragma unroll
        for (int i = 0; i < 8; i++) {
          const float* d = d1 + 8 * i;
          st_async128(peer + xa + i * 2048, pack_bf16(d[0], d[1]), pack_bf16(d[2], d[3]), pack_bf16(d[4], d[5]), pack_bf16(d[6], d[7]), peer + B_XF + 8 * wg);
        }
        mbar_wait(sb + B_XF + 8 * wg, xph, budget);
        xph ^= 1;
        uint32_t y[32];
#pragma unroll
        for (int i = 0; i < 8; i++) {
          const float* d = d0 + 8 * i;
          const uint4 v = lds128(sb + xa + i * 2048);
          y[4*i] = pack_bf16(d[0] + bf_lo(v.x), d[1] + bf_hi(v.x)); y[4*i+1] = pack_bf16(d[2] + bf_lo(v.y), d[3] + bf_hi(v.y));
          y[4*i+2] = pack_bf16(d[4] + bf_lo(v.z), d[5] + bf_hi(v.z)); y[4*i+3] = pack_bf16(d[6] + bf_lo(v.w), d[7] + bf_hi(v.w));
        }
        const bool fuse = !l || (ty == T_O && cb >= G_FL);
        float2* const st = &g_stat[l ? 4 + (cb & 7) : ty + (cb & 1)][0][rank * 64 + warp * 16 + (lane >> 2) * 2];
        if (fuse) {
          float mn[2], sq[2];
#pragma unroll
          for (int z = 0; z < 2; z++) {
            float m = 0, s2 = 0;
#pragma unroll
            for (int i = 0; i < 16; i++) m += bf_lo(y[2*i+z]) + bf_hi(y[2*i+z]);
            m += __shfl_xor_sync(0xffffffffu, m, 1); m += __shfl_xor_sync(0xffffffffu, m, 2);
            m *= 1.f / 128;
#pragma unroll
            for (int i = 0; i < 16; i++) { const float a = bf_lo(y[2*i+z]) - m, b = bf_hi(y[2*i+z]) - m; s2 = fmaf(a, a, fmaf(b, b, s2)); }
            s2 += __shfl_xor_sync(0xffffffffu, s2, 1); s2 += __shfl_xor_sync(0xffffffffu, s2, 2);
            mn[z] = m; sq[z] = s2;
          }
          if ((lane & 3) == 0) stg_rlx128(st + (j >> 1) * 128, __float_as_uint(mn[0]), (__float_as_uint(sq[0]) & ~31u) | (cb + 1), __float_as_uint(mn[1]), __float_as_uint(sq[1]));
          __syncwarp();
        }
        const int row = (ty == T_O ? l * SEQ : 0) + cb * 128 + rank * 64;
        auto put = [&](const CUtensorMap* mo, auto f) {
          nbar_sync_r(3 + wg, 128);
#pragma unroll
          for (int c = 0; c < 8; c++) stsm4(so + (c >> 2) * 8192 + (sw ^ ((c & 3) << 5)), f(4*c), f(4*c+1), f(4*c+2), f(4*c+3));
          fence_proxy_async();
          nbar_sync_r(3 + wg, 128);
          if (lead) { e_tma_store_2d(mo, so, (j >> 1) * 128, row); e_tma_store_2d(mo, so + 8192, (j >> 1) * 128 + 64, row); bulk_commit(); }
        };
        if (fuse) {
          uint4 u[2];
          while (true) {
            __nanosleep(G_SLEEP3);
            u[0] = ldg_rlx128(st + (lane & 3) * 256); u[1] = ldg_rlx128(st + (lane & 3) * 256 + 128);
            if (!__any_sync(0xffffffffu, ((u[0].y ^ (cb + 1)) | (u[1].y ^ (cb + 1))) & 31) || --budget <= 0) break;
          }
          float rs[2], mr[2];
#pragma unroll
          for (int z = 0; z < 2; z++) {
            const float ma = __uint_as_float(z ? u[0].z : u[0].x), mb = __uint_as_float(z ? u[1].z : u[1].x);
            float m = ma + mb;
            m += __shfl_xor_sync(0xffffffffu, m, 1); m += __shfl_xor_sync(0xffffffffu, m, 2);
            m *= 0.125f;
            float s2 = __uint_as_float(z ? u[0].w : u[0].y & ~31u) + __uint_as_float(z ? u[1].w : u[1].y & ~31u) + 128.f * ((ma - m) * (ma - m) + (mb - m) * (mb - m));
            s2 += __shfl_xor_sync(0xffffffffu, s2, 1); s2 += __shfl_xor_sync(0xffffffffu, s2, 2);
            rs[z] = rsqrtf(s2 * (1.f / DM) + 1e-5f); mr[z] = -m * rs[z];
          }
          put(ty == T_O ? &M.xm : &M.xn, [&](int i) { return pack_bf16(fmaf(bf_lo(y[i]), rs[i & 1], mr[i & 1]), fmaf(bf_hi(y[i]), rs[i & 1], mr[i & 1])); });
          if (lead) {
            bulk_wait<0>();
            e_flag_add_bulk(ty == T_D ? g_fl.xn[1][cb] : g_fl.dep + grp(T_GU, l, cb), 8);
          }
        }
        put(ty == T_O ? &M.x1 : l ? &M.out : &M.x2, [&](int i) { return y[i]; });
      } else {
        if (ty == T_GU) {
#pragma unroll
          for (int i = 0; i < 32; i++) { d0[i] = geglu(d0[i], d0[32 + i]); d1[i] = geglu(d1[i], d1[32 + i]); }
        }
#pragma unroll
        for (int hf = 0; hf < 2; hf++) {
          if (hf) {
            if (ty == T_GU) break;
            if (lead) bulk_wait_read<0>();
            nbar_sync_r(3 + wg, 128);
          }
#pragma unroll
          for (int m = 0; m < 2; m++)
#pragma unroll
            for (int c = 0; c < 4; c++) {
              const float* d = (m ? d1 : d0) + 32 * hf + 8 * c;
              stsm4(so + m * 8192 + (sw ^ (c << 5)), pack_bf16(d[0], d[1]), pack_bf16(d[2], d[3]), pack_bf16(d[4], d[5]), pack_bf16(d[6], d[7]));
            }
          fence_proxy_async();
          nbar_sync_r(3 + wg, 128);
          if (lead) {
            if (ty == T_GU) e_tma_store_2d(&M.hs, so, j * 64, l * SEQ + cb * 128); else e_tma_store_2d(&M.outs, so, j * 128 + hf * 64, cb * 128);
            bulk_commit();
          }
        }
      }
      if (lead) {
        bulk_wait<0>();
        e_arrive_cl(peer + B_SF + 8 * wg);
        if (ty == T_GU) e_flag_add_bulk(g_fl.dep + grp(T_D, l, cb), j < 20 ? 1 : j < 36 ? 1 << 8 : 1 << 16);
        else if (ty == T_O) { e_flag_add_bulk(g_fl.dep + grp(T_D, l, cb), 1 << 24); if (l && cb < G_FL) e_flag_add_bulk(g_fl.part + cb, 8); }
        else if (!l) e_flag_add_bulk(g_fl.dep + grp(T_O, 1, cb), 8);
      }
    }
    cluster_arrive(); cluster_wait();
  }
}

typedef CUresult (*PFN_encodeTiled)(CUtensorMap*, CUtensorMapDataType, cuuint32_t, void*, const cuuint64_t*, const cuuint64_t*,
                                    const cuuint32_t*, const cuuint32_t*, CUtensorMapInterleave, CUtensorMapSwizzle,
                                    CUtensorMapL2promotion, CUtensorMapFloatOOBfill);
static PFN_encodeTiled g_encode = nullptr;
static int g_sms = 0;
static CUtensorMap encode(const void* ptr, int rank, const cuuint64_t* dims, const cuuint64_t* strides, const cuuint32_t* box) {
  CUtensorMap m;
  const cuuint32_t es[5] = {1, 1, 1, 1, 1};
  g_encode(&m, CU_TENSOR_MAP_DATA_TYPE_BFLOAT16, rank, (void*)ptr, dims, strides, box, es, CU_TENSOR_MAP_INTERLEAVE_NONE,
           CU_TENSOR_MAP_SWIZZLE_128B, CU_TENSOR_MAP_L2_PROMOTION_L2_256B, CU_TENSOR_MAP_FLOAT_OOB_FILL_NONE);
  return m;
}
static CUtensorMap make_map(const void* ptr, uint64_t rows, uint64_t cols, uint32_t box_rows) {
  const cuuint64_t dims[2] = {cols, rows}, strides[1] = {cols * 2};
  const cuuint32_t box[2] = {64, box_rows};
  return encode(ptr, 2, dims, strides, box);
}
static CUtensorMap make_map_x(const void* ptr) {
  const cuuint64_t dims[3] = {DM, NSTEP * 32, 2}, strides[2] = {DM * 2, (cuuint64_t)NSTEP * 32 * DM * 2};
  const cuuint32_t box[3] = {64, 32, 2};
  return encode(ptr, 3, dims, strides, box);
}
static CUtensorMap make_map_x1(const void* ptr) {
  const cuuint64_t dims[3] = {64, 2 * NSTEP * 32, DM / 64}, strides[2] = {DM * 2, 128};
  const cuuint32_t box[3] = {64, 32, 2};
  return encode(ptr, 3, dims, strides, box);
}
static CUtensorMap make_map_wo(const void* ptr) {
  const cuuint64_t dims[5] = {DM, 2, 4, 4, NH * DH / 32}, strides[4] = {DM * 2, 8 * DM * 2, 2 * DM * 2, 32 * DM * 2};
  const cuuint32_t box[5] = {64, 2, 4, 4, 2};
  return encode(ptr, 5, dims, strides, box);
}

extern "C" void kernel_launch(void* const* d_in, const int* in_sizes, int n_in, void* d_out, int out_size) {
  const bf16 *x = (const bf16*)d_in[0], *mem0 = (const bf16*)d_in[1], *Wo = (const bf16*)d_in[5];
  if (!g_encode) {
    void* p = nullptr; cudaDriverEntryPointQueryResult q;
    cudaGetDriverEntryPoint("cuTensorMapEncodeTiled", &p, cudaEnableDefault, &q);
    g_encode = (PFN_encodeTiled)p;
    int dev = 0;
    cudaGetDevice(&dev);
    cudaDeviceGetAttribute(&g_sms, cudaDevAttrMultiProcessorCount, dev);
    cudaFuncSetAttribute(rec_kernel, cudaFuncAttributeMaxDynamicSharedMemorySize, rec::SMEM);
    cudaFuncSetAttribute(gemm_kernel, cudaFuncAttributeMaxDynamicSharedMemorySize, gm::SMEM);
  }
  void *xn, *o, *x1, *xm, *x2, *hh;
  cudaGetSymbolAddress(&xn, g_xn); cudaGetSymbolAddress(&o, g_o); cudaGetSymbolAddress(&x1, g_x1);
  cudaGetSymbolAddress(&xm, g_xm); cudaGetSymbolAddress(&x2, g_x2); cudaGetSymbolAddress(&hh, g_h);
  RecMaps R;
  for (int i = 0; i < 3; i++) R.w[i] = make_map(d_in[2 + i], DM, NH * DH, 16);
  R.wo = make_map(Wo, NH * DH, DM, 64); R.x[0] = make_map_x(xn); R.x[1] = make_map_x1(xn);
  rec_kernel<<<96, 512, rec::SMEM>>>(R, Wo, mem0, x, 0);
  GemmMaps G;
  G.o = make_map(o, 2 * SEQ, NH * DH, 128); G.wo = make_map_wo(Wo);
  G.x1 = make_map(x1, 2 * SEQ, DM, 64); G.x1s = make_map(x1, 2 * SEQ, DM, 128);
  G.xn = make_map((bf16*)xn + (NSTEP + LAG) * 32 * DM, SEQ, DM, 64);
  G.xm = make_map(xm, 2 * SEQ, DM, 64); G.xms = make_map(xm, 2 * SEQ, DM, 128);
  G.wg = make_map(d_in[8], DM, DF, 64); G.wu = make_map(d_in[9], DM, DF, 64); G.wd = make_map(d_in[10], DF, DM, 64);
  G.h = make_map(hh, 2 * SEQ, DF, 64); G.hs = make_map(hh, 2 * SEQ, DF, 128);
  G.x = make_map(x, SEQ, DM, 64); G.x2 = make_map(x2, SEQ, DM, 64); G.out = make_map(d_out, SEQ, DM, 64); G.outs = make_map(d_out, SEQ, DM, 128);
  cudaLaunchConfig_t cfg = {};
  cfg.gridDim = dim3(g_sms & ~1); cfg.blockDim = dim3(512); cfg.dynamicSmemBytes = gm::SMEM; cfg.stream = cudaStreamPerThread;
  cudaLaunchAttribute at;
  at.id = cudaLaunchAttributeProgrammaticStreamSerialization; at.val.programmaticStreamSerializationAllowed = 1;
  cfg.attrs = &at; cfg.numAttrs = 1;
  cudaLaunchKernelEx(&cfg, gemm_kernel, G);
}
```

```cpp
#include <cuda_runtime.h>
#include <cuda_bf16.h>
#include <cuda.h>
#include <stdint.h>

#define DEVI __device__ __forceinline__
typedef __nv_bfloat16 bf16;

#define LAG 14
constexpr int SEQ = 2048, DM = 1024, NH = 32, DH = 128, DF = 3584, NSEG = 64, NSTEP = NSEG + LAG;

__device__ __align__(1024) bf16 g_xn[2][NSTEP * 32 * DM];
__device__ __align__(1024) bf16 g_o[2][SEQ * NH * DH];
__device__ __align__(1024) bf16 g_x1[2][SEQ * DM];
__device__ __align__(1024) bf16 g_xm[2][SEQ * DM];
__device__ __align__(1024) bf16 g_x2[SEQ * DM];
__device__ __align__(1024) bf16 g_h[2][SEQ * DF];
__device__ __align__(1024) uint4 g_part[256 * 32 * 8];
__device__ __align__(1024) uint32_t g_ann[2][32][64];
__device__ __align__(1024) uint4 g_mem[2][2048];
__device__ __align__(128) float2 g_stat[12][8][128];
__host__ __device__ constexpr int grp(int type, int layer, int blk) { return layer ? 16 * type + blk : 64 + (16 * type + blk) * 32; }
struct Flags {
  int xn[2][16][32];
  int dep[64 + 48 * 32];
  int taken[64];
  int rows[32];
  int part[32];
  int ticket[32];
};
__device__ __align__(128) Flags g_fl;

DEVI uint32_t smem_u32(const void* p) { return (uint32_t)__cvta_generic_to_shared(p); }
DEVI void mbar_init(uint32_t bar, uint32_t cnt) { asm volatile("mbarrier.init.shared::cta.b64 [%0], %1;" :: "r"(bar), "r"(cnt) : "memory"); }
DEVI void mbar_expect_tx(uint32_t bar, uint32_t bytes) { asm volatile("mbarrier.arrive.expect_tx.shared::cta.b64 _, [%0], %1;" :: "r"(bar), "r"(bytes) : "memory"); }
DEVI void mbar_arrive(uint32_t bar) { asm volatile("mbarrier.arrive.shared::cta.b64 _, [%0];" :: "r"(bar) : "memory"); }
DEVI bool mbar_try(uint32_t bar, uint32_t parity) {
  uint32_t p;
  asm volatile("{.reg .pred p; mbarrier.try_wait.parity.shared::cta.b64 p, [%1], %2; selp.u32 %0, 1, 0, p;}" : "=r"(p) : "r"(bar), "r"(parity) : "memory");
  return p;
}
DEVI bool mbar_test(uint32_t bar, uint32_t parity) {
  uint32_t p;
  asm volatile("{.reg .pred p; mbarrier.test_wait.parity.shared::cta.b64 p, [%1], %2; selp.u32 %0, 1, 0, p;}" : "=r"(p) : "r"(bar), "r"(parity) : "memory");
  return p;
}
constexpr int SPIN_BUDGET = 1 << 20;
DEVI void mbar_wait(uint32_t bar, uint32_t parity, int& budget) {
  while (!mbar_try(bar, parity)) { if (--budget < 0) break; }
}
DEVI void trap_if_spent(int budget) { asm volatile("{.reg .pred p; setp.le.s32 p, %0, 0; @p trap;}" :: "r"(budget) : "memory"); }
DEVI void fault_if_spent(int budget) { asm volatile("{.reg .pred p; setp.le.s32 p, %0, 0; @p st.global.u32 [%1], 0;}" :: "r"(budget), "l"(0ull) : "memory"); }
DEVI uint32_t mapa(uint32_t addr, uint32_t rank) { uint32_t r; asm("mapa.shared::cluster.u32 %0, %1, %2;" : "=r"(r) : "r"(addr), "r"(rank)); return r; }
DEVI void cluster_sync() { asm volatile("barrier.cluster.arrive.relaxed.aligned; barrier.cluster.wait.aligned;" ::: "memory"); }
DEVI void fence_mbar_init() { asm volatile("fence.mbarrier_init.release.cluster;" ::: "memory"); }
DEVI void fence_proxy_async() { asm volatile("fence.proxy.async.shared::cta;" ::: "memory"); }
DEVI void tma_load_2d(uint32_t dst, const CUtensorMap* m, int c0, int c1, uint32_t bar) {
  asm volatile("cp.async.bulk.tensor.2d.shared::cluster.global.mbarrier::complete_tx::bytes [%0], [%1, {%3, %4}], [%2];"
    :: "r"(dst), "l"(m), "r"(bar), "r"(c0), "r"(c1) : "memory");
}
DEVI void tma_load_5d(uint32_t dst, const CUtensorMap* m, int c0, int c4, uint32_t bar) {
  asm volatile("cp.async.bulk.tensor.5d.shared::cluster.global.mbarrier::complete_tx::bytes [%0], [%1, {%3, %5, %5, %5, %4}], [%2];"
    :: "r"(dst), "l"(m), "r"(bar), "r"(c0), "r"(c4), "r"(0) : "memory");
}
DEVI void tma_prefetch_2d(const CUtensorMap* m, int c0, int c1) {
  asm volatile("cp.async.bulk.prefetch.tensor.2d.L2.global [%0, {%1, %2}];" :: "l"(m), "r"(c0), "r"(c1) : "memory");
}
DEVI void tma_prefetch_5d(const CUtensorMap* m, int c0, int c4) {
  asm volatile("cp.async.bulk.prefetch.tensor.5d.L2.global [%0, {%1, %3, %3, %3, %2}];" :: "l"(m), "r"(c0), "r"(c4), "r"(0) : "memory");
}
#define ELECT "{.reg .pred p; elect.sync _|p, 0xffffffff;\n @p "
DEVI void e_expect_tx(uint32_t bar, uint32_t bytes) { asm volatile(ELECT "mbarrier.arrive.expect_tx.shared::cta.b64 _, [%0], %1;}" :: "r"(bar), "r"(bytes) : "memory"); }
DEVI void e_arrive(uint32_t bar) { asm volatile(ELECT "mbarrier.arrive.shared::cta.b64 _, [%0];}" :: "r"(bar) : "memory"); }
DEVI void e_arrive_cl(uint32_t bar) { asm volatile(ELECT "mbarrier.arrive.shared::cluster.b64 _, [%0];}" :: "r"(bar) : "memory"); }
constexpr uint64_t EVICT_NORMAL = 0x1000000000000000ull, EVICT_FIRST = 0x12F0000000000000ull;
DEVI void e_tma_2d(uint32_t dst, const CUtensorMap* m, int c0, int c1, uint32_t bar, uint64_t pol = EVICT_NORMAL) {
  asm volatile(ELECT "cp.async.bulk.tensor.2d.shared::cluster.global.mbarrier::complete_tx::bytes.L2::cache_hint [%0], [%1, {%3, %4}], [%2], %5;}"
    :: "r"(dst), "l"(m), "r"(bar), "r"(c0), "r"(c1), "l"(pol) : "memory");
}
DEVI void e_tma_2d_mc(uint32_t dst, const CUtensorMap* m, int c0, int c1, uint32_t bar, uint64_t pol = EVICT_NORMAL) {
  asm volatile(ELECT "cp.async.bulk.tensor.2d.shared::cluster.global.mbarrier::complete_tx::bytes.multicast::cluster.L2::cache_hint [%0], [%1, {%3, %4}], [%2], %5, %6;}"
    :: "r"(dst), "l"(m), "r"(bar), "r"(c0), "r"(c1), "h"((unsigned short)3), "l"(pol) : "memory");
}
DEVI void e_st_async32(uint32_t a, uint32_t x, uint32_t bar) {
  asm volatile(ELECT "st.async.weak.shared::cluster.mbarrier::complete_tx::bytes.b32 [%0], %1, [%2];}" :: "r"(a), "r"(x), "r"(bar) : "memory");
}
DEVI void e_tma_store_2d(const CUtensorMap* m, uint32_t src, int c0, int c1) {
  asm volatile(ELECT "cp.async.bulk.tensor.2d.global.shared::cta.bulk_group [%0, {%2, %3}], [%1];}" :: "l"(m), "r"(src), "r"(c0), "r"(c1) : "memory");
}
DEVI void e_flag_add(int* p, int v = 1) {
  asm volatile("{.reg .pred p; elect.sync _|p, 0xffffffff;\n fence.proxy.async.global; @p red.release.gpu.global.add.s32 [%0], %1;}" :: "l"(p), "r"(v) : "memory");
}
DEVI void e_flag_add_bulk(int* p, int v) {
  asm volatile(ELECT "red.relaxed.gpu.global.add.s32 [%0], %1;}" :: "l"(p), "r"(v) : "memory");
}
DEVI int e_ticket(int* p, int n = 1) { int v = 0; asm volatile(ELECT "atom.relaxed.gpu.global.add.s32 %0, [%1], %2;}" : "+r"(v) : "l"(p), "r"(n) : "memory"); __syncwarp(); return v; }
DEVI int bcast(int v) { return __reduce_max_sync(0xffffffffu, v); }
DEVI int ld_relaxed(const int* p) { int v; asm volatile("ld.relaxed.gpu.global.s32 %0, [%1];" : "=r"(v) : "l"(p) : "memory"); return v; }
DEVI int ld_acquire(const int* p) { int v; asm volatile("ld.acquire.gpu.global.s32 %0, [%1];" : "=r"(v) : "l"(p) : "memory"); return __shfl_sync(0xffffffffu, v, 0); }
DEVI void e_tma_3d(uint32_t dst, const CUtensorMap* m, int c0, int c1, int c2, uint32_t bar) {
  asm volatile(ELECT "cp.async.bulk.tensor.3d.shared::cluster.global.mbarrier::complete_tx::bytes [%0], [%1, {%3, %4, %5}], [%2];}"
    :: "r"(dst), "l"(m), "r"(bar), "r"(c0), "r"(c1), "r"(c2) : "memory");
}
DEVI void e_tma_5d(uint32_t dst, const CUtensorMap* m, int c0, int c4, uint32_t bar) {
  asm volatile(ELECT "cp.async.bulk.tensor.5d.shared::cluster.global.mbarrier::complete_tx::bytes [%0], [%1, {%3, %5, %5, %5, %4}], [%2];}"
    :: "r"(dst), "l"(m), "r"(bar), "r"(c0), "r"(c4), "r"(0) : "memory");
}
DEVI void e_bulk_g2s(uint32_t dst, const void* src, uint32_t bytes, uint32_t bar) {
  asm volatile(ELECT "cp.async.bulk.shared::cluster.global.mbarrier::complete_tx::bytes [%0], [%1], %2, [%3];}" :: "r"(dst), "l"(src), "r"(bytes), "r"(bar) : "memory");
}
DEVI void e_prefetch(const void* src, uint32_t bytes) {
  asm volatile(ELECT "cp.async.bulk.prefetch.L2.global [%0], %1;}" :: "l"(src), "r"(bytes) : "memory");
}
DEVI void bulk_commit() { asm volatile("cp.async.bulk.commit_group;" ::: "memory"); }
template<int N> DEVI void bulk_wait_read() { asm volatile("cp.async.bulk.wait_group.read %0;" :: "n"(N) : "memory"); }
template<int N> DEVI void bulk_wait() { asm volatile("cp.async.bulk.wait_group %0;" :: "n"(N) : "memory"); }
template<int ID, int N> DEVI void nbar_sync() { asm volatile("bar.sync %0, %1;" :: "n"(ID), "n"(N) : "memory"); }
template<int ID, int N> DEVI void nbar_arrive() { asm volatile("bar.arrive %0, %1;" :: "n"(ID), "n"(N) : "memory"); }
DEVI void nbar_sync_r(int id, int n) { asm volatile("bar.sync %0, %1;" :: "r"(id), "r"(n) : "memory"); }
DEVI void nbar_arrive_r(int id, int n) { asm volatile("bar.arrive %0, %1;" :: "r"(id), "r"(n) : "memory"); }
template<int R> DEVI void reg_inc() { asm volatile("setmaxnreg.inc.sync.aligned.u32 %0;" :: "n"(R)); }
template<int R> DEVI void reg_dec() { asm volatile("setmaxnreg.dec.sync.aligned.u32 %0;" :: "n"(R)); }
DEVI void wg_fence() { asm volatile("wgmma.fence.sync.aligned;" ::: "memory"); }
DEVI void wg_commit() { asm volatile("wgmma.commit_group.sync.aligned;" ::: "memory"); }
template<int N> DEVI void wg_wait() { asm volatile("wgmma.wait_group.sync.aligned %0;" :: "n"(N) : "memory"); }
DEVI uint32_t pack_bf16(float lo, float hi) { uint32_t r; asm("cvt.rn.bf16x2.f32 %0, %1, %2;" : "=r"(r) : "f"(hi), "f"(lo)); return r; }
DEVI float bf_lo(uint32_t v) { return __uint_as_float(v << 16); }
DEVI float bf_hi(uint32_t v) { return __uint_as_float(v & 0xffff0000u); }
DEVI uint32_t movmat(uint32_t a) { uint32_t r; asm volatile("movmatrix.sync.aligned.m8n8.trans.b16 %0, %1;" : "=r"(r) : "r"(a)); return r; }
DEVI void ldsm4(uint32_t addr, uint32_t& r0, uint32_t& r1, uint32_t& r2, uint32_t& r3) {
  asm volatile("ldmatrix.sync.aligned.m8n8.x4.shared.b16 {%0,%1,%2,%3}, [%4];" : "=r"(r0), "=r"(r1), "=r"(r2), "=r"(r3) : "r"(addr) : "memory");
}
DEVI void ldsm4t(uint32_t addr, uint32_t& r0, uint32_t& r1, uint32_t& r2, uint32_t& r3) {
  asm volatile("ldmatrix.sync.aligned.m8n8.x4.trans.shared.b16 {%0,%1,%2,%3}, [%4];" : "=r"(r0), "=r"(r1), "=r"(r2), "=r"(r3) : "r"(addr) : "memory");
}
DEVI void stsm4(uint32_t addr, uint32_t r0, uint32_t r1, uint32_t r2, uint32_t r3) {
  asm volatile("stmatrix.sync.aligned.m8n8.x4.shared.b16 [%0], {%1,%2,%3,%4};" :: "r"(addr), "r"(r0), "r"(r1), "r"(r2), "r"(r3) : "memory");
}
DEVI uint4 lds128(uint32_t a) { uint4 v; asm volatile("ld.shared.v4.u32 {%0,%1,%2,%3}, [%4];" : "=r"(v.x), "=r"(v.y), "=r"(v.z), "=r"(v.w) : "r"(a) : "memory"); return v; }
DEVI uint32_t lds32v(uint32_t a) { uint32_t v; asm volatile("ld.volatile.shared.u32 %0, [%1];" : "=r"(v) : "r"(a) : "memory"); return v; }
DEVI void sts32v(uint32_t a, uint32_t v) { asm volatile("st.volatile.shared.u32 [%0], %1;" :: "r"(a), "r"(v) : "memory"); }
DEVI void st_async128(uint32_t a, uint32_t x, uint32_t y, uint32_t z, uint32_t w, uint32_t bar) {
  asm volatile("st.async.weak.shared::cluster.mbarrier::complete_tx::bytes.v4.b32 [%0], {%1,%2,%3,%4}, [%5];" :: "r"(a), "r"(x), "r"(y), "r"(z), "r"(w), "r"(bar) : "memory");
}
DEVI void st_async32(uint32_t a, uint32_t x, uint32_t bar) {
  asm volatile("st.async.weak.shared::cluster.mbarrier::complete_tx::bytes.b32 [%0], %1, [%2];" :: "r"(a), "r"(x), "r"(bar) : "memory");
}
DEVI void st_cl128(bool own, uint32_t a, uint32_t x, uint32_t y, uint32_t z, uint32_t w, uint32_t bar) {
  asm volatile("{.reg .pred p; setp.ne.u32 p, %6, 0; @p st.shared.v4.b32 [%0], {%1,%2,%3,%4};\n"
               "@!p st.async.weak.shared::cluster.mbarrier::complete_tx::bytes.v4.b32 [%0], {%1,%2,%3,%4}, [%5];}"
               :: "r"(a), "r"(x), "r"(y), "r"(z), "r"(w), "r"(bar), "r"((uint32_t)own) : "memory");
}
DEVI void st_cl32(bool own, uint32_t a, uint32_t x, uint32_t bar) {
  asm volatile("{.reg .pred p; setp.ne.u32 p, %3, 0; @p st.shared.b32 [%0], %1;\n"
               "@!p st.async.weak.shared::cluster.mbarrier::complete_tx::bytes.b32 [%0], %1, [%2];}" :: "r"(a), "r"(x), "r"(bar), "r"((uint32_t)own) : "memory");
}
DEVI uint4 ldg_rlx128(const void* p) {
  uint4 v;
  asm volatile("ld.relaxed.gpu.global.v4.b32 {%0,%1,%2,%3}, [%4];" : "=r"(v.x), "=r"(v.y), "=r"(v.z), "=r"(v.w) : "l"(p) : "memory");
  return v;
}
DEVI void stg_rlx128(void* p, uint32_t x, uint32_t y, uint32_t z, uint32_t w) {
  asm volatile("st.relaxed.gpu.global.v4.b32 [%0], {%1,%2,%3,%4};" :: "l"(p), "r"(x), "r"(y), "r"(z), "r"(w) : "memory");
}
DEVI void stg128(void* p, uint32_t x, uint32_t y, uint32_t z, uint32_t w) {
  asm volatile("st.global.v4.b32 [%0], {%1,%2,%3,%4};" :: "l"(p), "r"(x), "r"(y), "r"(z), "r"(w) : "memory");
}
DEVI void stg_rlx64(void* p, uint32_t x, uint32_t y) { asm volatile("st.relaxed.gpu.global.v2.b32 [%0], {%1,%2};" :: "l"(p), "r"(x), "r"(y) : "memory"); }
DEVI void stg_rlx32(void* p, uint32_t x) { asm volatile("st.relaxed.gpu.global.b32 [%0], %1;" :: "l"(p), "r"(x) : "memory"); }
DEVI uint32_t clock32() { uint32_t c; asm volatile("mov.u32 %0, %%clock;" : "=r"(c) :: "memory"); return c; }
DEVI uint32_t gtime() { uint32_t c; asm volatile("mov.u32 %0, %%globaltimer_lo;" : "=r"(c) :: "memory"); return c; }
DEVI void wait_time(uint32_t t, int& budget) { while ((int)(gtime() - t) < 0 && --budget > 0) {} }
DEVI uint2 ldg_rlx64(const void* p) { uint2 v; asm volatile("ld.relaxed.gpu.global.v2.b32 {%0,%1}, [%2];" : "=r"(v.x), "=r"(v.y) : "l"(p) : "memory"); return v; }
DEVI void sts16(uint32_t a, uint32_t x) { asm volatile("st.shared.b16 [%0], %1;" :: "r"(a), "h"((unsigned short)x) : "memory"); }
DEVI void sts128(uint32_t a, uint32_t x) { asm volatile("st.shared.v4.b32 [%0], {%1,%1,%1,%1};" :: "r"(a), "r"(x) : "memory"); }
DEVI void arrive_if_eq(uint32_t bar, int a, int b) { asm volatile("{.reg .pred p; setp.eq.s32 p, %1, %2; @p mbarrier.arrive.shared::cta.b64 _, [%0];}" :: "r"(bar), "r"(a), "r"(b) : "memory"); }
DEVI void arrive_cl_if_eq(uint32_t bar, int a, int b) { asm volatile("{.reg .pred p; setp.eq.s32 p, %1, %2; @p mbarrier.arrive.shared::cluster.b64 _, [%0];}" :: "r"(bar), "r"(a), "r"(b) : "memory"); }
template<int ID, int N> DEVI bool nbar_or(bool x) {
  uint32_t r;
  asm volatile("{.reg .pred p, q; setp.ne.u32 p, %1, 0; bar.red.or.pred q, %2, %3, p; selp.u32 %0, 1, 0, q;}" : "=r"(r) : "r"((uint32_t)x), "n"(ID), "n"(N) : "memory");
  return __any_sync(0xffffffffu, r);
}
DEVI void spin_until(uint32_t t0, int d) { while ((int)(clock32() - t0) < d) {} }
DEVI void flag_wait(const int* p, int n, int& budget) {
  while (ld_acquire(p) < n && --budget > 0) __nanosleep(128);
  asm volatile("fence.proxy.async.global;" ::: "memory");
}

#define F4(C, o)  C(d[o+0]), C(d[o+1]), C(d[o+2]), C(d[o+3])
#define F8(C, o)  F4(C, o), F4(C, o+4)
#define F32(C, o) F8(C, o), F8(C, o+8), F8(C, o+16), F8(C, o+24)
#define R4  "{%0,%1,%2,%3}"
#define R8  "{%0,%1,%2,%3,%4,%5,%6,%7}"
#define R16 "{%0,%1,%2,%3,%4,%5,%6,%7,%8,%9,%10,%11,%12,%13,%14,%15}"
#define R20 "{%0,%1,%2,%3,%4,%5,%6,%7,%8,%9,%10,%11,%12,%13,%14,%15,%16,%17,%18,%19}"
#define R32 "{%0,%1,%2,%3,%4,%5,%6,%7,%8,%9,%10,%11,%12,%13,%14,%15,%16,%17,%18,%19,%20,%21,%22,%23,%24,%25,%26,%27,%28,%29,%30,%31}"
#define R64 "{%0,%1,%2,%3,%4,%5,%6,%7,%8,%9,%10,%11,%12,%13,%14,%15,%16,%17,%18,%19,%20,%21,%22,%23,%24,%25,%26,%27,%28,%29,%30,%31," \
  "%32,%33,%34,%35,%36,%37,%38,%39,%40,%41,%42,%43,%44,%45,%46,%47,%48,%49,%50,%51,%52,%53,%54,%55,%56,%57,%58,%59,%60,%61,%62,%63}"
template<uint32_t OFF, uint32_t LBO, uint32_t SBO, uint32_t SW, int T> struct Op {
  static constexpr uint32_t lo = (OFF >> 4) | ((LBO >> 4) << 16), hi = (SBO >> 4) | (SW << 30);
  static constexpr int t = T;
};
DEVI uint32_t desc_base(uint32_t addr) { return (addr & 0x3FFFF) >> 4; }
#define RS_ASM(SHAPE, REGS, A0, A1, A2, A3, B, LO, HI, T, SD) \
  "{.reg .b64 tb; .reg .b32 lb; add.u32 lb, " B ", " LO "; mov.b64 tb, {lb, " HI "};\n" \
  "wgmma.mma_async.sync.aligned." SHAPE ".f32.bf16.bf16 " REGS ", {" A0 "," A1 "," A2 "," A3 "}, tb, " SD ", 1, 1, " T ";}"
#define WG_RS(NAME, SHAPE, REGS, LIST, ...) \
  template<int ACC, class OB> DEVI void NAME(float* d, const uint32_t* a, uint32_t b) { \
    if (ACC) asm volatile(RS_ASM(SHAPE, REGS, __VA_ARGS__) \
      : LIST("+f") : "r"(a[0]), "r"(a[1]), "r"(a[2]), "r"(a[3]), "r"(b), "n"(OB::lo), "n"(OB::hi), "n"(OB::t), "n"(ACC & 1)); \
    else asm volatile(RS_ASM(SHAPE, REGS, __VA_ARGS__) \
      : LIST("=f") : "r"(a[0]), "r"(a[1]), "r"(a[2]), "r"(a[3]), "r"(b), "n"(OB::lo), "n"(OB::hi), "n"(OB::t), "n"(0)); \
  }
#define SS_ASM(SHAPE, REGS, A, B, LA, HA, TA, LB, HB, TB, SD) \
  "{.reg .b64 ta, tb; .reg .b32 la, lb; add.u32 la, " A ", " LA "; mov.b64 ta, {la, " HA "}; add.u32 lb, " B ", " LB "; mov.b64 tb, {lb, " HB "};\n" \
  "wgmma.mma_async.sync.aligned." SHAPE ".f32.bf16.bf16 " REGS ", ta, tb, " SD ", 1, 1, " TA ", " TB ";}"
#define WG_SS(NAME, SHAPE, REGS, LIST, ...) \
  template<int ACC, class OA, class OB> DEVI void NAME(float* d, uint32_t a, uint32_t b) { \
    if (ACC) asm volatile(SS_ASM(SHAPE, REGS, __VA_ARGS__) \
      : LIST("+f") : "r"(a), "r"(b), "n"(OA::lo), "n"(OA::hi), "n"(OA::t), "n"(OB::lo), "n"(OB::hi), "n"(OB::t), "n"(ACC & 1)); \
    else asm volatile(SS_ASM(SHAPE, REGS, __VA_ARGS__) \
      : LIST("=f") : "r"(a), "r"(b), "n"(OA::lo), "n"(OA::hi), "n"(OA::t), "n"(OB::lo), "n"(OB::hi), "n"(OB::t), "n"(0)); \
  }
#define L4(C)  F4(C, 0)
#define L8(C)  F8(C, 0)
#define L16(C) F8(C, 0), F8(C, 8)
#define L20(C) F8(C, 0), F8(C, 8), F4(C, 16)
#define L32(C) F32(C, 0)
WG_RS(wg_rs8, "m64n8k16", R4, L4, "%4", "%5", "%6", "%7", "%8", "%9", "%10", "%11", "%12")
WG_RS(wg_rs16, "m64n16k16", R8, L8, "%8", "%9", "%10", "%11", "%12", "%13", "%14", "%15", "%16")
WG_RS(wg_rs32, "m64n32k16", R16, L16, "%16", "%17", "%18", "%19", "%20", "%21", "%22", "%23", "%24")
WG_SS(wg_ss32, "m64n32k16", R16, L16, "%16", "%17", "%18", "%19", "%20", "%21", "%22", "%23", "%24")
WG_RS(wg_rs64, "m64n64k16", R32, L32, "%32", "%33", "%34", "%35", "%36", "%37", "%38", "%39", "%40")
WG_SS(wg_ss8, "m64n8k16", R4, L4, "%4", "%5", "%6", "%7", "%8", "%9", "%10", "%11", "%12")
WG_SS(wg_ss16, "m64n16k16", R8, L8, "%8", "%9", "%10", "%11", "%12", "%13", "%14", "%15", "%16")
WG_SS(wg_ss40, "m64n40k16", R20, L20, "%20", "%21", "%22", "%23", "%24", "%25", "%26", "%27", "%28")
WG_SS(wg_ss64, "m64n64k16", R32, L32, "%32", "%33", "%34", "%35", "%36", "%37", "%38", "%39", "%40")
#define L64(C) F32(C, 0), F32(C, 32)
WG_SS(wg_ss128, "m64n128k16", R64, L64, "%64", "%65", "%66", "%67", "%68", "%69", "%70", "%71", "%72")
template<int I> struct IC { __host__ __device__ constexpr operator int() const { return I; } };
template<int I, int N, class F> DEVI void sfor(F&& f) {
  if constexpr (I < N) { f(IC<I>{}); sfor<I + 1, N>(f); }
}

#define R_CL 6
namespace rec {
constexpr int NHI = 36, NLO = 5, NRS = NHI + NLO, NSS = 64 - NRS;
constexpr uint32_t WS = 0;
constexpr uint32_t WO = 2 * NSS * 2048;
constexpr uint32_t RING = WO + 65536;
constexpr uint32_t QB = RING + 40960, RG = 2080, POSQ = 0x64210, POSK = 0xB9753, POSV = 0xEDCA8;
#define JA 2
constexpr uint32_t WA = QB;
constexpr uint32_t OM = QB + 9 * RG, OMS = 2 * RG;
constexpr uint32_t OM2 = QB + 16384, OM2S = 2048;
constexpr uint32_t WH = QB + 20480;
constexpr uint32_t B_PART = QB + 15 * RG - 32, B_ML0 = B_PART + 8, REDO = B_PART + 16;
constexpr uint32_t PM0 = QB + 16384, PM1 = QB + 15 * RG, PM2 = PM1 + 256;
constexpr uint32_t BARS = PM2 + 128;
constexpr uint32_t B_FULL = BARS, B_EMPTY = BARS + 40, B_MLAND = BARS + 80, B_QK = BARS + 112, B_V = BARS + 120, B_OM = BARS + 128,
                   B_WA = BARS + 136, B_SDONE = BARS + 144, B_BFREE = BARS + 152, B_W1 = PM1, B_W2 = PM1 + 8, B_WO = PM1 + 16;
constexpr uint32_t SMEM = BARS + 160;
static_assert(SMEM <= 232448 && QB % 1024 == 0, "smem map");
constexpr int R1 = (PM1 - WO) / 4096, RB = NRS - R1;
__host__ __device__ constexpr uint32_t stage_at(int t, int r) { return r < R1 ? WO + (t * R1 + r) * 2048 : WS + (t * NSS + NSS - RB + r - R1) * 2048; }
constexpr int NB_WO = 1, NB_ST = 2, NB_P = 3, NB_TR = 4, NB_X = 5, NB_G = 6, NB_G1 = 7, NB_G2 = 8, NB_G4 = 9, NB_S = 10;
__host__ __device__ constexpr bool is_lo(int j) { return j % 12 == 8; }
__host__ __device__ constexpr int lo_before(int j) { return (j + 3) / 12; }
__host__ __device__ constexpr int ss_before(int j) { return (j - lo_before(j)) * NSS / (64 - NLO); }
__host__ __device__ constexpr bool is_ss(int j) { return ss_before(j + 1) != ss_before(j); }
__host__ __device__ constexpr int reg_idx(int j) { return is_lo(j) ? NHI + lo_before(j) : j - ss_before(j) - lo_before(j); }
template<int j> using OpW = Op<WS + ss_before(j) * 2048, 16, 1024, 1, 1>;
#define P_G1 1
#define P_G2 3
#define P_G2L 0
#define P_OS 1
#define P_NA 6
#define P_G4 10
#define P_G5 12
#define P_FW 1
#define P_SEND 0xff3210ffu
#define P_WB 2
#define P_WOL 0
#define P_G4L 2
#define P_S1 1
#define P_S2 2
#define P_SPEC 1
#define X_ST 32
#define P_S0 3
#define P_MB 0
#define P_S4 5
#define P_S5 8
constexpr uint32_t SLOT1 = 0x32410324, USE1 = 0x22111110;
DEVI bool single(int s) { return s < LAG - 1 || s >= NSEG - 1; }
DEVI uint32_t flip(int s) { return (s < LAG - 1 ? s + 1 : s < NSEG - 1 ? LAG : LAG + s + 1) & 1; }
#define TUN(i, v) (v)
}
#define PROFW(wq, i)
#define SPROF(i)
DEVI uint32_t mapr(int h, uint32_t addr, int rank) { return mapa(addr, rank + (R_CL == 6 ? (h & 1) * 3 : 0)); }
template<int N> DEVI void pin(float* d) {
#pragma unroll
  for (int i = 0; i < N; i++) asm volatile("" : "+f"(d[i]) :: "memory");
}
DEVI void keep(const void* a) { asm volatile("{.reg .pred p; setp.eq.u64 p, %0, 0; vote.sync.any.pred p, p, 0xffffffff; @p exit;}" :: "l"(a) : "memory"); }
DEVI int lane_reg() { return __shfl_sync(0xffffffffu, threadIdx.x & 31, threadIdx.x & 31); }
#define LANE_NOW [[maybe_unused]] const int lane = lane0 + ((uint32_t)budget >> 30), g = lane >> 2, c = lane & 3

DEVI void rec_proj(const uint32_t sb, const int h, const int rank, const int w, const CUtensorMap* mW, const uint32_t zero) {
  using namespace rec;
  const int lane0 = lane_reg(), wg = w >> 2, ww = w & 3;
  int budget = SPIN_BUDGET;
  uint32_t wr[NRS * 4];
  {
    LANE_NOW;
    const uint32_t wsw = ((lane & 7) + (lane >> 4) * 8) * 128 + (((ww * 2 + ((lane >> 3) & 1)) ^ (lane & 7)) << 4);
    SPROF(0);
    mbar_wait(sb + B_W1, 0, budget);
    SPROF(1);
#pragma unroll
    for (int r = 0; r < NRS; r++) ldsm4t(sb + stage_at(wg, r) + wsw, wr[4*r], wr[4*r+1], wr[4*r+2], wr[4*r+3]);
    fence_proxy_async();
    nbar_sync<NB_ST, 256>();
    if (w < 4) {
      const int j = w * 16 + (lane >> 1), t = lane & 1;
      if (is_ss(j) && ss_before(j) >= NSS - RB) tma_load_2d(sb + WS + (t * NSS + ss_before(j)) * 2048, mW, h * DH + t * 64, j * 16, sb + B_W2);
    }
    __syncwarp();
    cluster_sync();
  }
  const uint32_t d0 = desc_base(sb), da = d0 + wg * (NSS * 128);
  const uint32_t pos = rank == 0 ? POSQ : rank == 1 ? POSK : POSV, bar = rank == 2 ? B_V : B_QK;
  uint32_t stg[2][4] = {}, pk[16] = {};
  auto stage = [&](uint32_t* t, int r) {
#pragma unroll
    for (int i = 0; i < 4; i++) asm volatile("xor.b32 %0, %1, %2;" : "+r"(t[i]) : "r"(wr[4 * r + i]), "r"(zero));
  };
#pragma unroll 1
  for (int s = -1; s < NSTEP; s++) {
    const uint32_t fl = flip(s);
    if (s >= 0) {
      float d[8];
      auto steps = [&](auto J0, auto J1, auto A0) {
        wg_fence();
        sfor<J0, J1>([&](auto J) {
          constexpr int j = J, acc = j ? 1 : A0;
          typedef Op<RING + j * 512, 256, 128, 0, 1> OB;
          if constexpr (is_ss(j)) wg_ss16<acc, OpW<j>, OB>(d, da, d0);
          else wg_rs16<acc, OB>(d, is_lo(j) ? stg[lo_before(j) & 1] : wr + 4 * reg_idx(j), d0);
        });
        wg_commit();
      };
      stage(stg[0], NHI);
      mbar_wait(sb + (P_SPEC ? B_ML0 : B_FULL), P_SPEC ? s & 1 : 0, budget);
      PROFW(0, 16);
      sfor<0, 8>([&](auto E) {
        constexpr int e = E, q = e >> 1;
        steps(IC<8 * e>{}, IC<8 * e + 8>{}, IC<0>{});
        if constexpr (e == 1 && P_SPEC) {
          mbar_wait(sb + B_FULL, 0, budget);
          if (__any_sync(0xffffffffu, lds32v(sb + REDO))) { wg_wait<0>(); steps(IC<0>{}, IC<16>{}, IC<2>{}); }
        }
        if constexpr (((P_SEND >> (4 * e)) & 15) == 0) { if (s > 0) mbar_wait(sb + B_BFREE, (s & 1) ^ 1, budget); }
        if constexpr (e > 0 && !(e & 1)) {
          wg_wait<1>();
          arrive_if_eq(sb + B_EMPTY + 8 * (q - 1), lane0, ww * 32);
        }
        if constexpr (!(e & 1)) stage(stg[(q + 1) & 1], NHI + q + 1);
        if constexpr (e < 6 && (e & 1) == P_FW) mbar_wait(sb + B_FULL + 8 * (q + 1), q ? fl : 0, budget);
        if constexpr (((P_SEND >> (4 * e)) & 15) < 4) {
          constexpr int n = (P_SEND >> (4 * e)) & 15;
          LANE_NOW;
          const uint32_t r = mapr(h, sb, n >> 1);
          uint32_t t[4];
#pragma unroll
          for (int i = 0; i < 4; i++) { if (n == 0) t[i] = pk[i]; else asm volatile("xor.b32 %0, %1, %2;" : "=r"(t[i]) : "r"(pk[4*n+i]), "r"(zero)); }
          st_cl128(rank == n >> 1, r + QB + ((pos >> (4 + 4 * c)) & 15) * RG + w * 256 + (n & 1) * 128 + g * 16, t[0], t[1], t[2], t[3], r + bar);
        }
      });
      LANE_NOW;
      const uint32_t dst = QB + (pos & 15) * RG + w * 256 + lane * 4;
      wg_wait<0>();
      pin<8>(d);
      {
        const uint32_t x0 = pack_bf16(d[0], d[1]), x1 = pack_bf16(d[2], d[3]), y0 = pack_bf16(d[4], d[5]), y1 = pack_bf16(d[6], d[7]);
        const uint32_t r = mapr(h, sb, rank == 0);
        if (rank < 2) { sts32v(sb + dst, rank ? y0 : x0); sts32v(sb + dst + 128, rank ? y1 : x1); fence_proxy_async(); }
        st_async32(r + dst, rank ? x0 : y0, r + bar); st_async32(r + dst + 128, rank ? x1 : y1, r + bar);
        if (rank < 2) e_arrive(sb + B_QK);
        else { const uint32_t r1 = mapr(h, sb, 1); st_async32(r1 + dst, y0, r1 + bar); st_async32(r1 + dst + 128, y1, r1 + bar); }
      }
      PROFW(0, 17);
      if (s == NSTEP - 1) break;
      arrive_if_eq(sb + B_EMPTY + 24, lane0, ww * 32);
    } else {
      e_arrive(sb + B_EMPTY + 8 * ww);
      mbar_wait(sb + B_W2, 0, budget);
      SPROF(2);
    }
    const bool gate = rank < 2 && s >= 0;
    if (single(s)) {
      float d[16];
      sfor<0, 8>([&](auto C) {
        constexpr int cc = C, sl = (SLOT1 >> (4 * cc)) & 15;
        if constexpr (cc == 0) mbar_wait(sb + B_FULL + 8 * sl, 0, budget);
        if constexpr (cc == P_S1) { if (gate) nbar_sync<NB_G1, 384>(); }
        if constexpr (cc == P_S2) { if (gate) nbar_sync<NB_G2, 384>(); }
        if constexpr (cc == P_S0) nbar_sync<NB_WO, 384>();
        if constexpr (cc == P_S4 || cc == P_S5) { if (gate && cc == (rank ? P_S5 : P_S4)) nbar_sync<NB_G4, 384>(); }
        if constexpr (lo_before(cc * 8 + 8) != lo_before(cc * 8)) stage(stg[0], NHI + lo_before(cc * 8));
        wg_fence();
        sfor<0, 8>([&](auto I) {
          constexpr int i = I, j = cc * 8 + i;
          typedef Op<RING + sl * 8192 + (i >> 2) * 4096 + (i & 3) * 32, 16, 1024, 1, 0> OB;
          if constexpr (is_ss(j)) wg_ss32<j != 0, OpW<j>, OB>(d, da, d0);
          else wg_rs32<j != 0, OB>(d, is_lo(j) ? stg[0] : wr + 4 * reg_idx(j), d0);
        });
        wg_commit();
        if constexpr (cc < 7) {
          constexpr int sn = (SLOT1 >> (4 * cc + 4)) & 15;
          mbar_wait(sb + B_FULL + 8 * sn, ((USE1 >> (4 * cc + 4)) & 1) ^ (sn >> 1 == 1 ? fl : 0), budget);
        }
        wg_wait<0>();
        arrive_if_eq(sb + B_EMPTY + 8 * sl, lane0, ww * 32);
      });
      pin<16>(d);
      if (gate && (rank ? P_S5 : P_S4) == 8) nbar_arrive<NB_G4, 384>();
      PROFW(0, 20);
#pragma unroll
      for (int i = 0; i < 8; i++) pk[i] = pk[8 + i] = pack_bf16(d[4 * (i & 3) + ((i >> 1) & 2)], d[4 * (i & 3) + ((i >> 1) & 2) + 1]);
      continue;
    }
    float d[32];
    sfor<0, 16>([&](auto C) {
      constexpr int cc = C, sl = (cc + 4) % 5;
      if constexpr (cc == 0) mbar_wait(sb + B_FULL + 8 * sl, 0, budget);
      if constexpr (cc == P_G1) { if (gate) nbar_sync<NB_G1, 384>(); }
      if constexpr (cc == P_G2) { if (gate) nbar_sync<NB_G2, 384>(); }
      if constexpr (cc == P_NA) {
        PROFW(0, 18);
        nbar_sync<NB_WO, 384>();
      }
      if constexpr (cc == P_G4 || cc == P_G5) { if (gate && cc == (rank ? P_G5 : P_G4)) nbar_sync<NB_G4, 384>(); }
      wg_fence();
      sfor<0, 4>([&](auto I) {
        constexpr int i = I, j = cc * 4 + i;
        typedef Op<RING + sl * 8192 + i * 32, 16, 1024, 1, 0> OB;
        if constexpr (is_ss(j)) wg_ss64<j != 0, OpW<j>, OB>(d, da, d0);
        else wg_rs64<j != 0, OB>(d, is_lo(j) ? stg[0] : wr + 4 * reg_idx(j), d0);
      });
      wg_commit();
      if constexpr (cc == P_NA) PROFW(0, 19);
      if constexpr (cc < 15) {
        if constexpr (is_lo(cc * 4 + 4)) stage(stg[0], reg_idx(cc * 4 + 4));
        mbar_wait(sb + B_FULL + 8 * ((sl + 1) % 5), ((cc + 5) / 5 + (sl == 1 || sl == 2 ? LAG : 0)) & 1, budget);
      }
      wg_wait<0>();
      arrive_if_eq(sb + B_EMPTY + 8 * sl, lane0, ww * 32);
    });
    pin<32>(d);
    if (gate && (rank ? P_G5 : P_G4) == 16) nbar_arrive<NB_G4, 384>();
    PROFW(0, 20);
#pragma unroll
    for (int i = 0; i < 16; i++) pk[i] = pack_bf16(d[16 * (i >> 3) + 4 * (i & 3) + ((i >> 1) & 2)], d[16 * (i >> 3) + 4 * (i & 3) + ((i >> 1) & 2) + 1]);
  }
}

DEVI float softmax_row(float* v, uint32_t* p) {
  constexpr float SC = 0.08838834764831845f * 1.4426950408889634f;
  float m = fmaxf(fmaxf(fmaxf(fmaxf(v[0], v[1]), fmaxf(v[2], v[3])), fmaxf(fmaxf(v[4], v[5]), fmaxf(v[6], v[7]))), fmaxf(v[8], v[9]));
  m = fmaxf(m, __shfl_xor_sync(0xffffffffu, m, 1));
  m = fmaxf(m, __shfl_xor_sync(0xffffffffu, m, 2));
  const float ms = -m * SC, mh = fmaf(m, -SC, -1.f);
#pragma unroll
  for (int i = 0; i < 10; i++) asm("ex2.approx.ftz.f32 %0, %1;" : "=f"(v[i]) : "f"(fmaf(v[i], SC, i < 8 ? ms : mh)));
#pragma unroll
  for (int n = 0; n < 5; n++) p[n] = pack_bf16(v[2*n], v[2*n+1]);
  return fmaf(v[8] + v[9], 2.f, ((v[0] + v[1]) + (v[2] + v[3])) + ((v[4] + v[5]) + (v[6] + v[7])));
}

template<bool ATT>
DEVI void rec_attn(const uint32_t sb, int h, int rank, int w, const bf16* __restrict__ Wo, const bf16* __restrict__ mem0) {
  using namespace rec;
  const int lane0 = lane_reg();
  int budget = SPIN_BUDGET;
  constexpr int NT = ATT ? 5 : 6;
  uint32_t wl[16];
  if (!ATT) {
    LANE_NOW;
#pragma unroll
    for (int i = 0; i < 16; i++) {
      const int dh = 8 * (i >> 1) + 2 * c;
      const unsigned short* p = (const unsigned short*)Wo + (size_t)(h * DH + dh) * DM + 15 * 64 + 16 * w + 8 * (i & 1) + g;
      wl[i] = p[0] | (uint32_t)p[DM] << 16;
    }
  }
  cluster_sync();
  const uint32_t d0 = desc_base(sb);
  uint32_t pph = 0;
#pragma unroll 1
  for (int s = -1; s < NSTEP; s++) {
    asm volatile("" : "+r"(h), "+r"(rank), "+r"(w));
    const uint32_t sp = s & 1;
    const int t0 = ATT ? rank + 1 : 0;
    const bool more = s + 1 < NSTEP;
    if (s == 0) mbar_wait(sb + B_WO, 0, budget);
    float hold[10] = {0, 0, 0, 0, 0, 0, 0, 0, 0, 0};
    if (ATT && s >= 0) {
      float sc[20];
      LANE_NOW;
      mbar_wait(sb + B_QK, sp, budget);
      PROFW(0, 1);
      fence_proxy_async();
      wg_fence();
      sfor<0, 8>([&](auto K) { constexpr int k = K; wg_ss40<k != 0, Op<QB + k * 256, 128, RG, 0, 1>, Op<QB + 3 * RG + k * 256, 128, 2 * RG, 0, 1>>(sc, d0, d0); });
      wg_commit();
      if (P_G1 < 16 && more) nbar_arrive<NB_G1, 384>();
      wg_wait<0>();
      pin<20>(sc);
      if (w == 3 && more) nbar_arrive<NB_S, 64>();
      PROFW(1, 2);
      if (w == 0) {
        uint32_t p[5];
        float v[10];
#pragma unroll
        for (int i = 0; i < 10; i++) v[i] = sc[4 * (i >> 1) + (i & 1)];
        softmax_row(v, p);
        const uint32_t a = sb + lane * 4;
        sts32v(a + PM0, p[0]); sts32v(a + PM0 + 128, p[1]); sts32v(a + PM1, p[2]); sts32v(a + PM1 + 128, p[3]); sts32v(a + PM2, p[4]);
      }
      if (w || !more) mbar_wait(sb + B_V, sp, budget);
      if (w == 1 && more) e_expect_tx(sb + B_V, 10240);
      if (more) {
        float rs[4], ot[2][4];
        uint32_t one[4];
#pragma unroll
        for (int i = 0; i < 4; i++) one[i] = 0x3F803F80u + ((uint32_t)budget >> (31 - i));
        typedef Op<PM0, 128, 128, 0, 0> P0; typedef Op<PM1, 128, 128, 0, 0> P1; typedef Op<PM2, 0, 128, 0, 0> P2;
        fence_proxy_async();
        nbar_sync<NB_P, 128>();
        PROFW(0, 3);
        wg_fence();
        wg_rs8<0, P0>(rs, one, d0); wg_rs8<1, P1>(rs, one, d0); wg_rs8<1, P2>(rs, one, d0);
        wg_commit();
        sfor<0, 2>([&](auto T) {
          constexpr int t = T;
          wg_ss8<0, Op<QB + 8 * RG + t * 1024, 2 * RG, 128, 0, 0>, P0>(ot[t], d0, d0);
          wg_ss8<1, Op<QB + 12 * RG + t * 1024, RG, 128, 0, 0>, P1>(ot[t], d0, d0);
          wg_ss8<1, Op<QB + 14 * RG + t * 1024, 0, 128, 0, 0>, P2>(ot[t], d0, d0);
        });
        wg_commit();
        if (P_G2 < 16 && !P_G2L) nbar_arrive<NB_G2, 384>();
        const uint32_t oa = w * 256 + lane * 4, r1 = mapr(h, sb, rank ^ 1), r2 = mapr(h, sb, 2);
        mbar_wait(sb + B_SDONE, sp, budget);
        wg_wait<1>();
        pin<4>(rs);
        float i0, i1;
        asm volatile("rcp.approx.ftz.f32 %0, %1;" : "=f"(i0) : "f"(rs[0]));
        asm volatile("rcp.approx.ftz.f32 %0, %1;" : "=f"(i1) : "f"(rs[1]));
        wg_wait<0>();
        pin<4>(ot[0]); pin<4>(ot[1]);
        uint32_t x[4];
#pragma unroll
        for (int j = 0; j < 4; j++) {
          x[j] = pack_bf16(ot[j >> 1][2 * (j & 1)] * i0, ot[j >> 1][2 * (j & 1) + 1] * i1);
          sts32v(sb + OM + rank * OMS + oa + (j >> 1) * 1024 + (j & 1) * 128, x[j]);
        }
        fence_proxy_async();
#pragma unroll
        for (int j = 0; j < 8; j++) {
          const int i = P_OS ? j >> 1 : j & 3;
          if (P_OS ? j & 1 : j >> 2) st_async32(r1 + OM + rank * OMS + oa + (i >> 1) * 1024 + (i & 1) * 128, x[i], r1 + B_OM);
          else st_async32(r2 + OM2 + rank * OM2S + oa + (i >> 1) * 1024 + (i & 1) * 128, x[i], r2 + B_OM);
        }
        e_arrive(sb + B_OM);
        if (P_G2 < 16 && P_G2L) nbar_arrive<NB_G2, 384>();
        PROFW(0, 4);
      }
#pragma unroll
      for (int i = 0; i < 10; i++) hold[i] = w ? sc[4 * (i >> 1) + (i & 1)] : sc[4 * (i >> 1) + 2 + (i & 1)];
    }
    if (more && s >= 0) {
      LANE_NOW;
      char* const pw = (char*)g_part + (uint32_t)((t0 * 16 + w * 4 + (lane >> 3)) * 4096 + h * 128 + ((lane ^ h) & 7) * 16);
      mbar_wait(sb + B_OM, sp, budget);
      if (w == 0) nbar_arrive<NB_G, 128>();
      PROFW(1, 5);
      if (!ATT) fence_proxy_async();
      float acc[3][8];
      auto store = [&](auto J) {
        constexpr int j = J;
        float* d = acc[j % 3];
        pin<8>(d);
        uint32_t x[4];
#pragma unroll
        for (int i = 0; i < 4; i++) { const uint32_t m = (h >> 3) == i; x[i] = (pack_bf16(d[2*i], d[2*i+1]) & ~m) | (m & ~sp); }
        stg_rlx128(pw + j * (48 * 4096), x[0], x[1], x[2], x[3]);
        if constexpr (ATT && j == JA) nbar_arrive<NB_TR, 160>();
        if constexpr (j == 2) PROFW(3, 26);
      };
      sfor<0, NT>([&](auto J) {
        constexpr int j = J;
        if constexpr (ATT && j == JA) { mbar_wait(sb + B_WA, sp, budget); PROFW(2, 0); }
        wg_fence();
        sfor<0, 8>([&](auto K) {
          constexpr int k = K;
          typedef Op<(ATT ? OM : OM2) + k * 256, 128, ATT ? OMS : OM2S, 0, 1> OB;
          if constexpr (j == 5 && k < 4) wg_rs16<k ? 1 : 2, OB>(acc[j % 3], wl + 4 * k, d0);
          else wg_ss16<k ? 1 : j < 3 ? 0 : 2, Op<(j == JA ? WA : j < 5 ? WO + (j - (j > JA)) * 16384 : WH - 8192) + k * 2048, 16, 1024, 1, 1>, OB>(acc[j % 3], d0, d0);
        });
        wg_commit();
        if constexpr (j == 0) { if (w == 3) e_expect_tx(sb + B_OM, ATT ? 2048 : 4096); }
        if constexpr (j == NT - 1 && !P_WOL) nbar_arrive<NB_WO, 384>();
        if constexpr (j > 0 && j != P_WB + 1) { wg_wait<1>(); store(IC<j - 1>{}); }
        if constexpr (j == P_WB || j == NT - 1) { wg_wait<0>(); store(IC<j>{}); }
        if constexpr (j == P_WB) {
          const uint32_t t = clock32();
          if (ATT) {
            if (w == 3 && lane < 14) sts128(sb + PM1 + lane * 16, (lane >> 1) == 3 ? 0x3F803F80u : 0);
            if (w == 3 || P_MB) fence_proxy_async();
            nbar_sync<NB_P, 128>();
          } else if (P_MB) fence_proxy_async();
          spin_until(t, TUN(8, 100));
        }
      });
      if (P_WOL) { spin_until(clock32(), TUN(9, 0)); nbar_arrive<NB_WO, 384>(); }
    } else if (more) nbar_arrive<NB_WO, 384>();
    PROFW(0, 6);
    asm volatile("" : "+r"(h), "+r"(rank), "+r"(w));
#pragma unroll 1
    for (int pass = 0; ATT && pass < 2; pass++)
    if (pass != rank) {
      LANE_NOW;
      const int lim = 8 * (g >> 1) + (g & 1) + 2 * w - 8 * c;
      uint32_t p[5];
#pragma unroll
      for (int i = 0; i < 8; i++) hold[2+i] = i <= lim ? hold[2+i] : -INFINITY;
      const float psum = softmax_row(hold, p);
#pragma unroll
      for (int i = 0; i < 5; i++) hold[i] = __uint_as_float(p[i]);
      hold[5] = psum;
    } else if (more) {
      LANE_NOW;
      const int blk = rank * 32 + (h ^ 16);
      char* const mw = (char*)g_mem + (uint32_t)(sp * 32768 + blk * 512 + w * 128 + lane * 4);
      uint32_t v0 = 0;
      if (s == -1 || (s == LAG - 1 && (w & 1))) {
        const unsigned short* q = (const unsigned short*)mem0 + c * 2 * DM + blk * 16 + (w >> 1) * 8 + g;
        v0 = q[0] | (uint32_t)q[DM] << 16;
        if (v0 == 0) v0 = 0x8000u;
      }
      keep(mw);
      if (s >= 0) {
        const uint32_t ca = sb + WA + lane * 128 + (((2 * w) ^ lane) & 7) * 16 + (lane >> 3) * 4;
        const uint32_t sa = sb + OM + (((g >> 1) & 1) * 2 + (g >> 2)) * 128 + (2 * c + (w >> 1)) * 16 + (w & 1) * 8 + (g & 1) * 2;
        const bool g4l = P_G4L == 1 || (P_G4L == 2 && single(s));
        for (bool first = true; ; first = false) {
          float r[4];
          mbar_wait(sb + B_PART, pph, budget);
          PROFW(0, 11);
          pph ^= 1;
          wg_fence();
          sfor<0, 8>([&](auto K) { constexpr int k = K; wg_ss8<k != 0, Op<WA + k * 2048, 16, 1024, 1, 1>, Op<PM1 + (6 - (k & 6)) * 16, 0, 128, 0, 0>>(r, d0, d0); });
          wg_commit();
          if (!g4l && first) nbar_arrive<NB_G4, 384>();
          const uint32_t x0 = lds32v(ca), x1 = lds32v(ca + 4096), x2 = lds32v(ca + 8192), x3 = lds32v(ca + 12288);
          bool bad = __any_sync(0xffffffffu, (sp ? x0 | x1 | x2 | x3 : ~(x0 & x1 & x2 & x3)) & 1) && budget > 0;
          wg_wait<0>();
          pin<4>(r);
          uint32_t y = pack_bf16(r[0], r[2]);
          y |= (y & 0xffffu) ? 0 : 0x8000u;
          y |= (y >> 16) ? 0 : 0x80000000u;
          if (bad) y = 0;
          sts16(sa, y); sts16(sa + 4, y >> 16);
          nbar_sync<NB_P, 128>();
          y = lds32v(sb + OM + w * 128 + lane * 4);
          const bool ok = !__any_sync(0xffffffffu, y == 0);
          if (ok) stg_rlx32(mw, v0 ? v0 : y);
          if (g4l && first) nbar_arrive<NB_G4, 384>();
          if (ok) break;
          nbar_sync<NB_P, 128>();
          budget--;
          if (w == 0) { e_expect_tx(sb + B_PART, 16384); e_bulk_g2s(sb + WA, (const char*)g_part + blk * 16384, 16384, sb + B_PART); }
          __syncwarp();
        }
        nbar_sync<NB_P, 128>();
        if (w < 2) e_arrive_cl(mapr(h, sb + B_BFREE, w));
      } else stg_rlx32(mw, v0);
      stg_rlx32(mw + (sp ? -32768 : 32768), 0);
      PROFW(1, 8);
    }
    if (ATT && s >= 0) {
      const int seg = s - (rank ? LAG : 0);
      const bool act = (unsigned)seg < NSEG;
      LANE_NOW;
      uint32_t a[12];
#pragma unroll
      for (int i = 0; i < 12; i++) a[i] = __float_as_uint(hold[i < 10 ? i >> 1 : 4]) + ((uint32_t)budget >> (31 - (i & 3)));
      float o[32], inv, psum = hold[5];
      char* const ob = (char*)g_o[rank] + ((size_t)(seg * 32 + 8 * (g >> 1) + (g & 1) + 2 * w) * (NH * DH) + h * DH + c * 8) * 2;
      sfor<0, 2>([&](auto HF) {
        constexpr int hf = HF;
        wg_fence();
        wg_rs64<hf * 2, Op<QB + 8 * RG + hf * 1024, 2 * RG, 128, 0, 0>>(o, a, d0);
        wg_rs64<1, Op<QB + 12 * RG + hf * 1024, RG, 128, 0, 0>>(o, a + 4, d0);
        wg_rs64<1, Op<QB + 14 * RG + hf * 1024, 0, 128, 0, 0>>(o, a + 8, d0);
        wg_commit();
        if constexpr (hf == 0) {
          psum += __shfl_xor_sync(0xffffffffu, psum, 1);
          psum += __shfl_xor_sync(0xffffffffu, psum, 2);
          asm("rcp.approx.ftz.f32 %0, %1;" : "=f"(inv) : "f"(psum));
        }
        wg_wait<0>();
        pin<32>(o);
        if constexpr (hf == 1) { if (w == 2 && more) e_arrive_cl(mapr(h, sb + B_BFREE, 2)); }
        if (act) {
#pragma unroll
          for (int i = 0; i < 2; i++)
            stg128(ob + (hf * 2 + i) * 64, pack_bf16(o[16*i] * inv, o[16*i+1] * inv), pack_bf16(o[16*i+4] * inv, o[16*i+5] * inv),
                   pack_bf16(o[16*i+8] * inv, o[16*i+9] * inv), pack_bf16(o[16*i+12] * inv, o[16*i+13] * inv));
        }
      });
      PROFW(0, 7);
      if (act && (seg & 3) == 3) {
        nbar_sync<NB_P, 128>();
        if (w == 0) e_flag_add(g_fl.dep + grp(0, rank, seg >> 2), 4);
      }
    } else if (!ATT && w == 3) {
      if (s + 4 < NSEG) e_prefetch(g_xn[0] + (size_t)((s + 4) * 32 + h) * DM, 2048);
    }
  }
  cluster_sync();
}

DEVI void rec_load(const uint32_t sb, const int h, const int rank, const int w, const CUtensorMap* mX, const CUtensorMap* mWo) {
  using namespace rec;
  const int lane0 = lane_reg(), mq = (w + 3) & 3;
  int budget = SPIN_BUDGET;
  if (w == 0) flag_wait(g_fl.xn[0][0], 96, budget);
  SPROF(3);
  bool late = false;
  cluster_sync();
  if (w == 0) { if (lane0 < 4) mbar_arrive(sb + B_FULL + 8 * lane0); __syncwarp(); }
  if (w == 3) {
    mbar_wait(sb + B_W2, 0, budget);
    e_expect_tx(sb + B_WO, rank == 2 ? 65536 + 16384 + 8192 : 65536);
    const int t0 = (rank + 1) % 3;
    if (lane0 < 8) tma_load_2d(sb + WO + lane0 * 8192, mWo, (3 * ((lane0 >> 1) + (lane0 >> 1 >= JA)) + t0) * 64, h * DH + (lane0 & 1) * 64, sb + B_WO);
    else if (rank < 2 && lane0 < 10) tma_prefetch_2d(mWo, (3 * JA + t0) * 64, h * DH + (lane0 & 1) * 64);
    else if (rank == 2 && lane0 < 11) tma_load_2d(lane0 < 10 ? sb + WA + (lane0 - 8) * 8192 : sb + WH, mWo, lane0 < 10 ? 3 * JA * 64 : 15 * 64, h * DH + (lane0 > 8) * 64, sb + B_WO);
    __syncwarp();
  }
  uint32_t lph = 0;
#pragma unroll 1
  for (int s = -1; s < NSTEP - 1; s++) {
    if (w == 0) {
      if (late) flag_wait(g_fl.xn[1][(s + 1 - LAG) >> 2], 128, budget);
      if (single(s)) {
#pragma unroll 1
        for (int i = 0; i < 8; i++) {
          const int k = i < 5 ? (0x21430 >> (4 * i)) & 15 : i;
          const int sl = (SLOT1 >> (4 * k)) & 15;
          mbar_wait(sb + B_EMPTY + 8 * sl, (((USE1 >> (4 * k)) ^ (sl >> 1 == 1 ? flip(s) : 0)) & 1) ^ 1, budget);
          e_expect_tx(sb + B_FULL + 8 * sl, 8192);
          e_tma_3d(sb + RING + sl * 8192, mX + 1, 0, (s + 1 + (s < LAG ? 0 : NSTEP)) * 32, k * 2, sb + B_FULL + 8 * sl);
        }
      } else {
        int sl = 4, ph = 1;
#pragma unroll 1
        for (int i = 0; i < 16; i++) {
          mbar_wait(sb + B_EMPTY + 8 * sl, ph ^ (sl >> 1 & LAG & 1), budget);
          e_expect_tx(sb + B_FULL + 8 * sl, 8192);
          e_tma_3d(sb + RING + sl * 8192, mX, i * 64, (s + 1) * 32, 0, sb + B_FULL + 8 * sl);
          if (++sl == 5) { sl = 0; ph ^= 1; }
        }
      }
      nbar_arrive<NB_X, 128>();
      const int sn = s + 2 - LAG;
      late = (sn & 3) == 0 && (unsigned)sn < NSEG && ld_acquire(g_fl.xn[1][sn >> 2]) < 128;
      asm volatile("fence.proxy.async.global;" ::: "memory");
    }
    uint32_t t = gtime();
    if (s >= 0) {
      uint2 a;
      if (w == 2 && rank < 2) {
        nbar_sync<NB_S, 64>();
        e_expect_tx(sb + B_WA, 16384);
        e_tma_2d(sb + WA, mWo, (3 * JA + 1 + rank) * 64, h * DH, sb + B_WA);
        e_tma_2d(sb + WA + 8192, mWo, (3 * JA + 1 + rank) * 64, h * DH + 64, sb + B_WA);
        e_arrive_cl(mapr(h, sb + B_SDONE, rank ^ 1));
        stg_rlx32(&g_ann[s & 1][lane0][h * 2 + rank], (gtime() & ~31u) | ((s + 1) & 31));
        e_expect_tx(sb + B_QK, 10240);
      }
      if (w) nbar_sync<NB_G, 128>();
      do { a = ldg_rlx64(&g_ann[s & 1][h][lane0 * 2]); } while (__any_sync(0xffffffffu, ((a.x ^ (s + 1)) | (a.y ^ (s + 1))) & 31) && --budget > 0);
      t += __reduce_max_sync(0xffffffffu, max((int)(a.x - t), (int)(a.y - t)));
      t &= ~31u;
      PROFW(1, 12);
      if (w == 1 && rank < 2) {
        nbar_sync<NB_TR, 160>();
        e_expect_tx(sb + B_PART, 16384);
        wait_time(t + (single(s) ? (rank ? TUN(11, 1600) : TUN(10, 1200)) : rank ? TUN(1, 1700) : TUN(0, 1300)), budget);
        e_bulk_g2s(sb + WA, (const char*)g_part + (rank * 32 + (h ^ 16)) * 16384, 16384, sb + B_PART);
        PROFW(1, 21);
      }
      t += single(s) ? (mq == 0 ? TUN(12, 2050) : mq == 1 ? TUN(13, 2250) : mq == 2 ? TUN(14, 2500) : TUN(15, 2750))
                     : (mq == 0 ? TUN(2, 2250) : mq == 1 ? TUN(3, 2450) : mq == 2 ? TUN(4, 2700) : TUN(5, 2950));
    }
    if (w) nbar_sync<NB_X, 128>();
    mbar_wait(sb + B_EMPTY + 8 * mq, mq >= 2 ? flip(s + 1) ^ 1 : 1, budget);
    PROFW(1, 9);
    uint32_t bar = sb + (P_SPEC && mq == 0 ? B_ML0 : B_MLAND + 8 * mq), redo = 0;
    e_expect_tx(bar, 8192);
    wait_time(t, budget);
    PROFW(1, 22); PROFW(3, 23);
    while (true) {
      e_bulk_g2s(sb + RING + mq * 8192, (const char*)g_mem + (s & 1) * 32768 + mq * 8192, 8192, bar);
      const uint32_t a = sb + RING + mq * 8192 + lane0 * 32 + (lane0 >> 2) * 4;
      if (bar == sb + B_ML0) mbar_wait(bar, (s + 1) & 1, budget);
      else { mbar_wait(bar, lph, budget); lph ^= 1; }
      PROFW(1, 24);
      uint32_t mn = 0xffffffffu;
#pragma unroll
      for (int i = 0; i < 8; i++) mn = min(mn, lds32v(a + i * 1024));
      if (!__any_sync(0xffffffffu, mn == 0) || --budget <= 0) break;
      bar = sb + B_MLAND + 8 * mq; redo = 1;
      e_expect_tx(bar, 8192);
    }
    if (mq == 0) sts32v(sb + REDO, redo);
    e_arrive(sb + B_FULL + 8 * mq);
    PROFW(1, 10); PROFW(2, 13); PROFW(3, 14); PROFW(0, 15);
  }
}

DEVI void ln_row(const uint4* u, bf16* dst, int lane) {
  const uint32_t* x = (const uint32_t*)u;
  float mean = 0, q = 0;
#pragma unroll
  for (int i = 0; i < 16; i++) mean += bf_lo(x[i]) + bf_hi(x[i]);
  mean *= 1.f / 32;
#pragma unroll
  for (int i = 0; i < 16; i++) { const float a = bf_lo(x[i]) - mean, b = bf_hi(x[i]) - mean; q = fmaf(a, a, fmaf(b, b, q)); }
#pragma unroll
  for (int o = 1; o < 32; o *= 2) {
    const float m2 = __shfl_xor_sync(0xffffffffu, mean, o), q2 = __shfl_xor_sync(0xffffffffu, q, o), dl = m2 - mean;
    q = fmaf(dl * dl, 16.f * o, q + q2);
    mean = 0.5f * (mean + m2);
  }
  const float rs = rsqrtf(q * (1.f / DM) + 1e-5f), mr = -mean * rs;
#pragma unroll
  for (int i = 0; i < 4; i++) {
    uint32_t y[4];
#pragma unroll
    for (int k = 0; k < 4; k++) y[k] = pack_bf16(fmaf(bf_lo(x[4*i+k]), rs, mr), fmaf(bf_hi(x[4*i+k]), rs, mr));
    stg128((uint4*)dst + i * 32 + lane, y[0], y[1], y[2], y[3]);
  }
}

struct RecMaps { CUtensorMap w[3], wo, x[2]; };
__global__ void __cluster_dims__(R_CL, 1, 1) __launch_bounds__(512, 1)
rec_kernel(const __grid_constant__ RecMaps M, const bf16* __restrict__ Wo, const bf16* __restrict__ mem0, const bf16* __restrict__ x, uint32_t zero) {
  using namespace rec;
  extern __shared__ __align__(1024) uint8_t smem[];
  const uint32_t sb = smem_u32(smem);
  const int tid = threadIdx.x, warp = __shfl_sync(0xffffffffu, tid >> 5, 0), wg = warp >> 2, lane = tid & 31;
  const int h = blockIdx.x / 3, rank = blockIdx.x % 3;
  if (warp >= 4) {
    const bool ln = warp >= 5 && blockIdx.x * 11 + warp - 5 < SEQ / 2;
    const size_t lo = (size_t)(blockIdx.x * 11 + warp - 5) * (2 * DM);
    uint4 u[8];
    if (ln) {
#pragma unroll
      for (int i = 0; i < 8; i++) u[i] = ldg_rlx128((const uint4*)(x + lo) + i * 32 + lane);
    }
    const uint4 z = make_uint4(0, 0, 0, 0);
    const int t = blockIdx.x * 384 + tid - 128;
    constexpr int N = (sizeof(Flags) - sizeof(g_fl.xn)) / 16;
    g_part[t] = z;
    if (t < 28672) g_part[96 * 384 + t] = z;
    else if (t < 32768) g_mem[0][t - 28672] = ((uint4*)g_stat[4])[t - 28672] = z;
    else if (t < 33792) ((uint4*)g_ann)[t - 32768] = z;
    else if (t < 33792 + N) ((uint4*)g_fl.dep)[t - 33792] = z;
    __syncwarp();
    if (ln) { ln_row(u, g_xn[0] + lo, lane); ln_row(u + 4, g_xn[0] + lo + DM, lane); }
    nbar_sync<NB_WO, 384>();
    if (warp == 4) {
      e_flag_add(g_fl.xn[0][0]);
      asm volatile("griddepcontrol.launch_dependents;" ::: "memory");
    }
  } else if (warp == 0) {
    if (lane < 20) mbar_init(sb + BARS + 8 * lane, (lane >= 5 && lane < 10) || lane == 19 ? 2 : lane == 14 ? 9 : lane == 16 && rank < 2 ? 5 : 1);
    else if (lane < 23) mbar_init(sb + B_W1 + 8 * (lane - 20), 1);
    else if (lane < 25) mbar_init(sb + B_PART + 8 * (lane - 23), 1);
    fence_mbar_init();
    __syncwarp();
    e_expect_tx(sb + B_W1, NRS * 4096); e_expect_tx(sb + B_W2, NSS * 4096);
    e_expect_tx(sb + B_QK, 10240); e_expect_tx(sb + B_V, 10240); e_expect_tx(sb + B_OM, rank < 2 ? 2048 : 4096);
    if (lane < X_ST && !is_ss(lane >> 1)) tma_load_2d(sb + stage_at(lane & 1, reg_idx(lane >> 1)), &M.w[rank], h * DH + (lane & 1) * 64, (lane >> 1) * 16, sb + B_W1);
    __syncwarp();
  }
  __syncthreads();
  if (warp < 4) {
    for (int i = tid; i < 256; i += 128) {
      const int j = (i >> 1) & 63, t = i & 1, r = reg_idx(j);
      if (is_ss(j) != i >> 7 || i < X_ST) continue;
      if (!is_ss(j)) tma_load_2d(sb + stage_at(t, r), &M.w[rank], h * DH + t * 64, j * 16, sb + B_W1);
      else if (ss_before(j) < NSS - RB) tma_load_2d(sb + WS + (t * NSS + ss_before(j)) * 2048, &M.w[rank], h * DH + t * 64, j * 16, sb + B_W2);
      else tma_prefetch_2d(&M.w[rank], h * DH + t * 64, j * 16);
    }
    __syncwarp();
  }
  if (wg == 3) {
    reg_dec<24>();
    rec_load(sb, h, rank, warp & 3, M.x, &M.wo);
    cluster_sync();
  } else if (wg == 2) {
    reg_dec<72>();
    if (rank < 2) rec_attn<true>(sb, h, rank, warp & 3, Wo, mem0);
    else rec_attn<false>(sb, h, rank, warp & 3, Wo, mem0);
  } else {
    reg_inc<208>();
    rec_proj(sb, h, rank, warp, &M.w[rank], zero);
    cluster_sync();
  }
}

namespace gm {
constexpr int STAGES = 6, STAGE_BYTES = 32768;
constexpr uint32_t SO = STAGES * STAGE_BYTES, B_FULL = SO + 32768, B_TRIG = B_FULL + 56, B_EMPTY = B_FULL + 64, B_JOB = B_FULL + 128,
                   B_MSG = B_FULL + 144, B_XF = B_FULL + 160, B_SF = B_FULL + 176, JOB = B_FULL + 192, MSG = JOB + 8, SMEM = B_FULL + 256;
constexpr int T_O = 0, T_GU = 1, T_D = 2, T_END = 3;
#define G_LOOK 8
#define G_FILL 7
#define G_SLEEP 100
#define G_SLEEP2 500
#define G_SLEEP3 100
#define G_DF 2
#define G_FL 10
#define G_DE 0
#define G_BOOT 3
#define G_DS 14
DEVI bool is_split(int ty, int l, int cb) { return ty == T_O || (ty == T_D && (!l || cb >= G_DS)); }
#define G_ROLES 16, 17, 8, 9, 10, 0, 1, 2, 3, 4, 5, 6, 7, 11, 12, 13, 14, 15
constexpr uint64_t pack_roles(int i0, int i1) { constexpr int r[18] = {G_ROLES}; uint64_t v = 0; for (int i = i0; i < i1; i++) v |= (uint64_t)r[i] << (5 * (i - i0)); return v; }
constexpr uint64_t ROLE0 = pack_roles(0, 12), ROLE1 = pack_roles(12, 18);
struct Pipe { int s, ph; DEVI void next() { if (++s == STAGES) { s = 0; ph ^= 1; } } };
}
struct GemmMaps { CUtensorMap o, wo, x, x1, x1s, xm, xms, xn, wg, wu, h, hs, wd, x2, out, outs; };

DEVI float geglu(float g, float u) {
  const float z = g * (0.7978845608028654f + 0.035677408136300125f * g * g);
  float t; asm("tanh.approx.f32 %0, %1;" : "=f"(t) : "f"(z));
  const float hg = 0.5f * g;
  return fmaf(hg, t, hg) * u;
}
DEVI int h_ready(int v) { const int t = v ^ 0x10141014; return t & 0xff0000ff ? 0 : t & 0xff00 ? 20 : t ? 36 : 56; }
DEVI int a_ready(int ty, int l, int cb) {
  int v;
  asm volatile("ld.acquire.gpu.global.s32 %0, [%1];" : "=r"(v) : "l"(g_fl.dep + grp(ty, l, cb) + (threadIdx.x & 1)) : "memory");
  v = __shfl_sync(0xffffffffu, v, 0);
  asm volatile("fence.proxy.async.global;" ::: "memory");
  return ty == gm::T_D ? h_ready(v) : v >= (ty == gm::T_O && l ? 256 : 128) ? 64 : 0;
}

__global__ void __cluster_dims__(2, 1, 1) __launch_bounds__(512, 1) gemm_kernel(const __grid_constant__ GemmMaps M) {
  using namespace gm;
  extern __shared__ __align__(1024) uint8_t smem[];
  const uint32_t sb = smem_u32(smem);
  const int tid = threadIdx.x, wid = __shfl_sync(0xffffffffu, tid >> 5, 0), wg = wid >> 2, warp = wid & 3;
  int budget = SPIN_BUDGET;
  const int rank = blockIdx.x & 1;
  const uint32_t peer = mapa(sb, rank ^ 1);
  if (tid < 24) mbar_init(sb + B_FULL + 8 * tid, tid >> 3 == 1 ? 2 : 1);
  fence_mbar_init();
  if (wid == 1 && tid < 32 + sizeof(GemmMaps) / 128) asm volatile("prefetch.tensormap [%0];" :: "l"(&M.o + (tid - 32)) : "memory");
  __syncthreads();
  cluster_sync();
  const int cta = blockIdx.x, lane = lane_reg();
  if (wg >= 2) {
    reg_dec<72>();
    if (wid == 8 || wid == 10) {
      Pipe p; p.s = 0; p.ph = 1;
      for (int n = 0; ; n++) {
        if (wid == 8) e_expect_tx(sb + B_MSG + 8 * (n & 1), 4);
        mbar_wait(sb + B_MSG + 8 * (n & 1), (n >> 1) & 1, budget);
        const int msg = __shfl_sync(0xffffffffu, lds32v(sb + MSG + 4 * (n & 1)), 0);
        const int ty = (msg >> 11) & 3, l = (msg >> 10) & 1;
        const bool shb = ty == T_GU && l, spl = is_split(ty, l, (msg >> 6) & 15);
        const int cb = ((msg >> 6) & 15) + (shb ? rank : 0), j = (msg & 63) + (ty == T_END || shb ? 0 : rank);
        const int ke = ty == T_O ? 64 : ty == T_GU ? 16 : 56, k0 = spl ? rank : 0, dk = spl ? 2 : 1;
        const int c0 = ty == T_GU ? j * 64 : spl ? (j >> 1) * 128 : j * 128, c1 = ty == T_GU ? c0 : c0 + 64;
        mbar_wait(sb + B_EMPTY + 8 * p.s, p.ph, budget);
        trap_if_spent(budget);
        auto stages = [&](auto f) {
#pragma unroll 1
          for (int k = k0; k < ke; k += dk) {
            mbar_wait(sb + B_EMPTY + 8 * p.s, p.ph, budget);
            f(k, sb + p.s * STAGE_BYTES, sb + B_FULL + 8 * p.s);
            p.next();
          }
        };
        if (wid == 8) {
          const int job = ty << 11 | l << 10 | cb << 6 | j;
          sts32v(sb + JOB + 4 * (n & 1), job | p.s << 16 | (p.ph ^ 1) << 20);
          e_arrive(sb + B_JOB + 8 * (n & 1));
          if (ty == T_END) break;
          if (ty != T_GU) { e_expect_tx(sb + B_FULL + 8 * p.s, spl ? 16384 : STAGE_BYTES); p.next(); }
          const CUtensorMap* const m0 = ty == T_D ? &M.wd : shb && rank ? &M.wu : &M.wg, * const m1 = ty == T_D ? &M.wd : &M.wu;
          if (ty == T_O) stages([&](int k, uint32_t a, uint32_t fb) { e_expect_tx(fb, STAGE_BYTES); e_tma_5d(a + 16384, &M.wo, c0, k * 2, fb); e_tma_5d(a + 24576, &M.wo, c1, k * 2, fb); });
          else if (shb) stages([&](int k, uint32_t a, uint32_t fb) { e_expect_tx(fb, STAGE_BYTES); e_tma_2d_mc(a + 16384 + rank * 8192, m0, c0, k * 64, fb); });
          else stages([&](int k, uint32_t a, uint32_t fb) { e_expect_tx(fb, STAGE_BYTES); e_tma_2d(a + 16384, m0, c0, k * 64, fb); e_tma_2d(a + 24576, m1, c1, k * 64, fb); });
        } else {
          if (ty == T_END) break;
          const int row = l * SEQ + cb * 128, kt = ke + k0 - G_LOOK * dk;
          const uint64_t polA = ty != T_GU ? EVICT_FIRST : EVICT_NORMAL;
          int rdy = msg >> 16;
          auto need = [&](int k) {
            if (k == kt) e_arrive(sb + B_TRIG);
            while (k >= rdy && k >= (rdy = a_ready(ty, l, cb))) { __nanosleep(G_SLEEP); trap_if_spent(--budget); }
          };
          if (ty != T_GU) {
            need(0);
            const uint32_t a = sb + p.s * STAGE_BYTES, fb = sb + B_FULL + 8 * p.s;
            const CUtensorMap* const m = ty == T_D ? (spl ? &M.x1 : &M.x1s) : l ? &M.x2 : &M.x;
            const int r = (ty == T_D ? row : cb * 128) + (spl ? rank * 64 : 0);
            e_tma_2d(a, m, c0, r, fb, polA); e_tma_2d(a + 16384, m, c1, r, fb, polA);
            p.next();
          }
          if (shb || spl) {
            const CUtensorMap* const ma = ty == T_O ? &M.o : ty == T_GU ? &M.xms : &M.hs;
            stages([&](int k, uint32_t a, uint32_t fb) { need(k); e_tma_2d(a, ma, k * 64, row, fb, polA); });
          } else {
            const CUtensorMap* const ma = ty == T_GU ? &M.xm : &M.h;
            stages([&](int k, uint32_t a, uint32_t fb) { need(k); e_tma_2d_mc(a + rank * 8192, ma, k * 64, row + rank * 64, fb, polA); });
          }
        }
      }
    } else if (wid == 9 && rank == 0) {
      uint32_t sm; asm volatile("mov.u32 %0, %%smid;" : "=r"(sm));
      const bool crowd = sm >= 124 || sm < 50;
      int d0, d1, t0, t1, pair = e_ticket(g_fl.ticket, crowd ? 1 : 256);
      auto peek = [&]() {
        d0 = ld_relaxed(g_fl.dep + lane); d1 = ld_relaxed(g_fl.dep + 32 + lane);
        t0 = ld_relaxed(g_fl.taken + lane); t1 = ld_relaxed(g_fl.taken + 32 + lane);
      };
      peek();
      {
        const int t = bcast(pair), a = t & 255, b = t >> 8, i = crowd ? a : 17 - b;
        pair = a + b >= 18 ? a + b : (int)((i < 12 ? ROLE0 >> (5 * i) : ROLE1 >> (5 * i - 60)) & 31);
      }
      int k1 = pair < 18 ? 0 : 48, skip = pair - 18;
      bool late = false;
      for (int n = 0, ty = 0; ty != T_END; n++) {
        mbar_wait(sb + B_TRIG, (n & 1) ^ 1, budget);
        int l, cb, j, rdy = 64;
        while (true) {
          const int ph = k1 % 3;
          const bool gap = pair < 8 ? ph == 1 : pair >= 16 && ph == 2;
          if (k1 < 48) {
            cb = k1++ / 3;
            if (gap && (late || !(G_FILL & (pair < 8 ? 1 : 2)))) continue;
            if (!gap) {
              l = 0;
              ty = pair < 8 ? (ph ? T_GU : T_O) : ph == 2 ? T_D : T_GU;
              j = 2 * (pair < 8 ? (ph ? pair + 10 : pair) : ph == 1 ? pair + 10 : pair - 8);
              rdy = a_ready(ty, 0, cb);
              if (ph == 0) late = rdy != 0;
              break;
            }
          }
          if (skip < 0) peek();
          const bool l0 = t0 < (lane < 16 ? 8 : lane & 1 ? 0 : 56), l1 = lane < 16 && t1 < (lane < G_DS ? 4 : 8);
          const uint32_t rd = __ballot_sync(0xffffffffu, d0 >= (lane < 16 ? 256 : 128));
          uint32_t ok0 = __ballot_sync(0xffffffffu, l0) & rd & (rd >> 1 | 0xffff), ok1 = __ballot_sync(0xffffffffu, l1 && h_ready(d1) > 0);
          if (gap) { ok1 = 0; if (pair < 16) ok0 &= 0xffff0000u | G_BOOT; }
          ty = T_END; l = 1; cb = j = 0;
          if (!gap && !__any_sync(0xffffffffu, l0 || l1)) break;
          if (ok1 & ((1u << G_DS) - 1)) ok1 &= (1u << G_DS) - 1;
          const uint32_t dfirst = ok1 & __ballot_sync(0xffffffffu, lane < G_DF && d1 == 0x10141014);
          if (dfirst && !(ok0 & 0xffff)) { ok0 = 0; ok1 = dfirst; }
          else if (__any_sync(0xffffffffu, l0)) ok1 &= (1u << G_DE) - 1;
          else if (!ok1 && !gap) ok1 = __ballot_sync(0xffffffffu, l1);
          uint32_t m = ok0 ? ok0 : ok1;
          if (!m && !gap) __nanosleep(100);
          while (m) {
            const int nth = ok0 ? 0 : pair % __popc(m);
            const int b = __ffs(__ballot_sync(0xffffffffu, __popc(m << (31 - lane)) > nth)) - 1, gn = b + (ok0 ? 0 : 32);
            const int sz = gn < 16 ? 8 : gn < 32 ? 56 : gn < 32 + G_DS ? 4 : 8;
            m &= ~(1u << b);
            if (skip >= 0 && m && (skip -= sz - __shfl_sync(0xffffffffu, ok0 ? t0 : t1, b)) >= 0) continue;
            int t = e_ticket(g_fl.taken + gn);
            rdy = a_ready(gn >> 4, 1, gn & 15);
            t = bcast(t);
            if (t < sz) { ty = gn >> 4; cb = gn & 15; j = sz == 56 ? t : 2 * t; break; }
          }
          skip = -1;
          if (ty != T_END) break;
          trap_if_spent(--budget);
        }
        const int msg = rdy << 16 | ty << 11 | l << 10 | cb << 6 | j;
        e_st_async32(peer + MSG + 4 * (n & 1), msg, peer + B_MSG + 8 * (n & 1));
        e_st_async32(sb + MSG + 4 * (n & 1), msg, sb + B_MSG + 8 * (n & 1));
      }
    } else if (wg == 3) {
      bool open = lane < G_FL && ld_relaxed(g_fl.rows + lane) < 128;
      while (__any_sync(0xffffffffu, open)) {
        int v = 0;
        if (open) asm volatile("ld.acquire.gpu.global.s32 %0, [%1];" : "=r"(v) : "l"(g_fl.part + lane) : "memory");
        const uint32_t ok = __ballot_sync(0xffffffffu, open && v >= 128);
        if (!ok) {
          if (--budget <= 0) break;
          __nanosleep(G_SLEEP2);
          continue;
        }
        const int cb = __ffs(__ballot_sync(0xffffffffu, __popc(ok << (31 - lane)) > (cta >> 5) % __popc(ok))) - 1;
        const int r = bcast(e_ticket(g_fl.rows + cb));
        if (r >= 128) { open = open && lane != cb; continue; }
        uint4 u[4];
#pragma unroll
        for (int i = 0; i < 4; i++) u[i] = ldg_rlx128((const uint4*)(g_x1[1] + (size_t)(cb * 128 + r) * DM) + i * 32 + lane);
        ln_row(u, g_xm[1] + (size_t)(cb * 128 + r) * DM, lane);
        __syncwarp();
        e_flag_add(g_fl.dep + grp(T_GU, 1, cb));
      }
      if (cta == 0 && wid == 12) {
        asm volatile("griddepcontrol.wait;" ::: "memory");
        g_fl.xn[lane >> 4][lane & 15][0] = 0;
      }
    }
    cluster_sync();
  } else {
    reg_inc<184>();
    const bool lead = warp == 0;
    const uint32_t eb = (warp == 1 ? peer : sb) + B_EMPTY;
    const int rl = warp < 2 ? 0 : -1;
    const uint32_t so = sb + SO + wg * 16384;
    const int r0 = warp * 16 + (lane & 7) + ((lane >> 3) & 1) * 8;
    const uint32_t sw = r0 * 128 + (((lane >> 4) ^ (r0 & 7)) << 4);
    int xph = 0;
    for (int n = wg; ; n += 2) {
      float d0[64], d1[64];
      mbar_wait(sb + B_JOB + 8 * wg, (n >> 1) & 1, budget);
      fault_if_spent(budget);
      const int job = __shfl_sync(0xffffffffu, lds32v(sb + JOB + 4 * wg), 0);
      const int ty = (job >> 11) & 3, l = (job >> 10) & 1, cb = (job >> 6) & 15, j = job & 63;
      if (ty == T_END) {
        if (n > 0) nbar_sync_r(1 + wg, 256);
        if (lead && !(job & 1)) { sts32v(sb + JOB + 4 * (wg ^ 1), job | 1); e_arrive(sb + B_JOB + 8 * (wg ^ 1)); }
        if (!(job & 1)) nbar_arrive_r(1 + (wg ^ 1), 256);
        break;
      }
      Pipe q; q.s = (job >> 16) & 15; q.ph = job >> 20;
      const bool spl = is_split(ty, l, cb);
      if (ty != T_GU) mbar_wait(sb + B_FULL + 8 * q.s, q.ph, budget);
#pragma unroll
      for (int m = 0; m < 2; m++) {
        float* d = m ? d1 : d0;
        if (ty != T_GU && !(m && spl)) {
#pragma unroll
          for (int c = 0; c < 8; c++) {
            uint32_t r[4];
            ldsm4(sb + q.s * STAGE_BYTES + (c >> 2) * 16384 + m * 8192 + (sw ^ ((c & 3) << 5)), r[0], r[1], r[2], r[3]);
#pragma unroll
            for (int i = 0; i < 4; i++) { d[8*c+2*i] = bf_lo(r[i]); d[8*c+2*i+1] = bf_hi(r[i]); }
          }
        } else {
#pragma unroll
          for (int i = 0; i < 64; i++) d[i] = 0.f;
        }
      }
      if (ty != T_GU) {
        fence_proxy_async();
        nbar_sync_r(3 + wg, 128);
        arrive_cl_if_eq(eb + 8 * q.s, lane, rl);
        q.next();
      }
      pin<64>(d0); pin<64>(d1);
      if (n > 0) nbar_sync_r(1 + wg, 256);
      const int nk = ty == T_O ? 32 : ty == T_GU ? 16 : spl ? 28 : 56;
      const uint32_t ro = spl ? rank * 512 : 0;
      int prev = 0;
      for (int i = 0; i < nk; i++) {
        mbar_wait(sb + B_FULL + 8 * q.s, q.ph, budget);
        const uint32_t da = desc_base(sb) + q.s * (STAGE_BYTES / 16);
        wg_fence();
        sfor<0, 4>([&](auto K) {
          constexpr int k = K;
          typedef Op<16384 + k * 2048, 8192, 1024, 1, 1> OB;
          wg_ss128<1, Op<k * 32, 16, 1024, 1, 0>, OB>(d0, da + ro, da);
          wg_ss128<1, Op<8192 + k * 32, 16, 1024, 1, 0>, OB>(d1, da - ro, da);
        });
        wg_commit();
        wg_wait<1>();
        arrive_cl_if_eq(eb + 8 * prev, lane, i ? rl : -1);
        prev = q.s;
        q.next();
      }
      nbar_arrive_r(1 + (wg ^ 1), 256);
      wg_wait<0>();
      pin<64>(d0); pin<64>(d1);
      arrive_cl_if_eq(eb + 8 * prev, lane, rl);
      if (spl) {
        const uint32_t xa = SO + wg * 16384 + warp * 512 + lane * 16;
        if (lead) e_expect_tx(sb + B_XF + 8 * wg, 16384);
        mbar_wait(sb + B_SF + 8 * wg, ((n >> 1) & 1) ^ 1, budget);
#pragma unroll
        for (int i = 0; i < 8; i++) {
          const float* d = d1 + 8 * i;
          st_async128(peer + xa + i * 2048, pack_bf16(d[0], d[1]), pack_bf16(d[2], d[3]), pack_bf16(d[4], d[5]), pack_bf16(d[6], d[7]), peer + B_XF + 8 * wg);
        }
        mbar_wait(sb + B_XF + 8 * wg, xph, budget);
        xph ^= 1;
        uint32_t y[32];
#pragma unroll
        for (int i = 0; i < 8; i++) {
          const float* d = d0 + 8 * i;
          const uint4 v = lds128(sb + xa + i * 2048);
          y[4*i] = pack_bf16(d[0] + bf_lo(v.x), d[1] + bf_hi(v.x)); y[4*i+1] = pack_bf16(d[2] + bf_lo(v.y), d[3] + bf_hi(v.y));
          y[4*i+2] = pack_bf16(d[4] + bf_lo(v.z), d[5] + bf_hi(v.z)); y[4*i+3] = pack_bf16(d[6] + bf_lo(v.w), d[7] + bf_hi(v.w));
        }
        const bool fuse = !l || (ty == T_O && cb >= G_FL);
        float2* const st = &g_stat[l ? 4 + (cb & 7) : ty + (cb & 1)][0][rank * 64 + warp * 16 + (lane >> 2) * 2];
        if (fuse) {
          float mn[2], sq[2];
#pragma unroll
          for (int z = 0; z < 2; z++) {
            float m = 0, s2 = 0;
#pragma unroll
            for (int i = 0; i < 16; i++) m += bf_lo(y[2*i+z]) + bf_hi(y[2*i+z]);
            m += __shfl_xor_sync(0xffffffffu, m, 1); m += __shfl_xor_sync(0xffffffffu, m, 2);
            m *= 1.f / 128;
#pragma unroll
            for (int i = 0; i < 16; i++) { const float a = bf_lo(y[2*i+z]) - m, b = bf_hi(y[2*i+z]) - m; s2 = fmaf(a, a, fmaf(b, b, s2)); }
            s2 += __shfl_xor_sync(0xffffffffu, s2, 1); s2 += __shfl_xor_sync(0xffffffffu, s2, 2);
            mn[z] = m; sq[z] = s2;
          }
          if ((lane & 3) == 0) stg_rlx128(st + (j >> 1) * 128, __float_as_uint(mn[0]), (__float_as_uint(sq[0]) & ~31u) | (cb + 1), __float_as_uint(mn[1]), __float_as_uint(sq[1]));
          __syncwarp();
        }
        const int row = (ty == T_O ? l * SEQ : 0) + cb * 128 + rank * 64;
        auto put = [&](const CUtensorMap* mo, auto f) {
          nbar_sync_r(3 + wg, 128);
#pragma unroll
          for (int c = 0; c < 8; c++) stsm4(so + (c >> 2) * 8192 + (sw ^ ((c & 3) << 5)), f(4*c), f(4*c+1), f(4*c+2), f(4*c+3));
          fence_proxy_async();
          nbar_sync_r(3 + wg, 128);
          if (lead) { e_tma_store_2d(mo, so, (j >> 1) * 128, row); e_tma_store_2d(mo, so + 8192, (j >> 1) * 128 + 64, row); bulk_commit(); }
        };
        if (fuse) {
          uint4 u[2];
          while (true) {
            __nanosleep(G_SLEEP3);
            u[0] = ldg_rlx128(st + (lane & 3) * 256); u[1] = ldg_rlx128(st + (lane & 3) * 256 + 128);
            if (!__any_sync(0xffffffffu, ((u[0].y ^ (cb + 1)) | (u[1].y ^ (cb + 1))) & 31) || --budget <= 0) break;
          }
          float rs[2], mr[2];
#pragma unroll
          for (int z = 0; z < 2; z++) {
            const float ma = __uint_as_float(z ? u[0].z : u[0].x), mb = __uint_as_float(z ? u[1].z : u[1].x);
            float m = ma + mb;
            m += __shfl_xor_sync(0xffffffffu, m, 1); m += __shfl_xor_sync(0xffffffffu, m, 2);
            m *= 0.125f;
            float s2 = __uint_as_float(z ? u[0].w : u[0].y & ~31u) + __uint_as_float(z ? u[1].w : u[1].y & ~31u) + 128.f * ((ma - m) * (ma - m) + (mb - m) * (mb - m));
            s2 += __shfl_xor_sync(0xffffffffu, s2, 1); s2 += __shfl_xor_sync(0xffffffffu, s2, 2);
            rs[z] = rsqrtf(s2 * (1.f / DM) + 1e-5f); mr[z] = -m * rs[z];
          }
          put(ty == T_O ? &M.xm : &M.xn, [&](int i) { return pack_bf16(fmaf(bf_lo(y[i]), rs[i & 1], mr[i & 1]), fmaf(bf_hi(y[i]), rs[i & 1], mr[i & 1])); });
          if (lead) {
            bulk_wait<0>();
            e_flag_add_bulk(ty == T_D ? g_fl.xn[1][cb] : g_fl.dep + grp(T_GU, l, cb), 8);
          }
        }
        put(ty == T_O ? &M.x1 : l ? &M.out : &M.x2, [&](int i) { return y[i]; });
      } else {
        if (ty == T_GU) {
#pragma unroll
          for (int i = 0; i < 32; i++) { d0[i] = geglu(d0[i], d0[32 + i]); d1[i] = geglu(d1[i], d1[32 + i]); }
        }
#pragma unroll
        for (int hf = 0; hf < 2; hf++) {
          if (hf) {
            if (ty == T_GU) break;
            if (lead) bulk_wait_read<0>();
            nbar_sync_r(3 + wg, 128);
          }
#pragma unroll
          for (int m = 0; m < 2; m++)
#pragma unroll
            for (int c = 0; c < 4; c++) {
              const float* d = (m ? d1 : d0) + 32 * hf + 8 * c;
              stsm4(so + m * 8192 + (sw ^ (c << 5)), pack_bf16(d[0], d[1]), pack_bf16(d[2], d[3]), pack_bf16(d[4], d[5]), pack_bf16(d[6], d[7]));
            }
          fence_proxy_async();
          nbar_sync_r(3 + wg, 128);
          if (lead) {
            if (ty == T_GU) e_tma_store_2d(&M.hs, so, j * 64, l * SEQ + cb * 128); else e_tma_store_2d(&M.outs, so, j * 128 + hf * 64, cb * 128);
            bulk_commit();
          }
        }
      }
      if (lead) {
        bulk_wait<0>();
        e_arrive_cl(peer + B_SF + 8 * wg);
        if (ty == T_GU) e_flag_add_bulk(g_fl.dep + grp(T_D, l, cb), j < 20 ? 1 : j < 36 ? 1 << 8 : 1 << 16);
        else if (ty == T_O) { e_flag_add_bulk(g_fl.dep + grp(T_D, l, cb), 1 << 24); if (l && cb < G_FL) e_flag_add_bulk(g_fl.part + cb, 8); }
        else if (!l) e_flag_add_bulk(g_fl.dep + grp(T_O, 1, cb), 8);
      }
    }
    cluster_sync();
  }
}

typedef CUresult (*PFN_encodeTiled)(CUtensorMap*, CUtensorMapDataType, cuuint32_t, void*, const cuuint64_t*, const cuuint64_t*,
                                    const cuuint32_t*, const cuuint32_t*, CUtensorMapInterleave, CUtensorMapSwizzle,
                                    CUtensorMapL2promotion, CUtensorMapFloatOOBfill);
static PFN_encodeTiled g_encode = nullptr;
static int g_sms = 0;
static CUtensorMap encode(const void* ptr, int rank, const cuuint64_t* dims, const cuuint64_t* strides, const cuuint32_t* box) {
  CUtensorMap m;
  const cuuint32_t es[5] = {1, 1, 1, 1, 1};
  g_encode(&m, CU_TENSOR_MAP_DATA_TYPE_BFLOAT16, rank, (void*)ptr, dims, strides, box, es, CU_TENSOR_MAP_INTERLEAVE_NONE,
           CU_TENSOR_MAP_SWIZZLE_128B, CU_TENSOR_MAP_L2_PROMOTION_L2_256B, CU_TENSOR_MAP_FLOAT_OOB_FILL_NONE);
  return m;
}
static CUtensorMap make_map(const void* ptr, uint64_t rows, uint64_t cols, uint32_t box_rows) {
  const cuuint64_t dims[2] = {cols, rows}, strides[1] = {cols * 2};
  const cuuint32_t box[2] = {64, box_rows};
  return encode(ptr, 2, dims, strides, box);
}
static CUtensorMap make_map_x(const void* ptr) {
  const cuuint64_t dims[3] = {DM, NSTEP * 32, 2}, strides[2] = {DM * 2, (cuuint64_t)NSTEP * 32 * DM * 2};
  const cuuint32_t box[3] = {64, 32, 2};
  return encode(ptr, 3, dims, strides, box);
}
static CUtensorMap make_map_x1(const void* ptr) {
  const cuuint64_t dims[3] = {64, 2 * NSTEP * 32, DM / 64}, strides[2] = {DM * 2, 128};
  const cuuint32_t box[3] = {64, 32, 2};
  return encode(ptr, 3, dims, strides, box);
}
static CUtensorMap make_map_wo(const void* ptr) {
  const cuuint64_t dims[5] = {DM, 2, 4, 4, NH * DH / 32}, strides[4] = {DM * 2, 8 * DM * 2, 2 * DM * 2, 32 * DM * 2};
  const cuuint32_t box[5] = {64, 2, 4, 4, 2};
  return encode(ptr, 5, dims, strides, box);
}

extern "C" void kernel_launch(void* const* d_in, const int* in_sizes, int n_in, void* d_out, int out_size) {
  const bf16 *x = (const bf16*)d_in[0], *mem0 = (const bf16*)d_in[1], *Wo = (const bf16*)d_in[5];
  if (!g_encode) {
    void* p = nullptr; cudaDriverEntryPointQueryResult q;
    cudaGetDriverEntryPoint("cuTensorMapEncodeTiled", &p, cudaEnableDefault, &q);
    g_encode = (PFN_encodeTiled)p;
    int dev = 0;
    cudaGetDevice(&dev);
    cudaDeviceGetAttribute(&g_sms, cudaDevAttrMultiProcessorCount, dev);
    cudaFuncSetAttribute(rec_kernel, cudaFuncAttributeMaxDynamicSharedMemorySize, rec::SMEM);
    cudaFuncSetAttribute(gemm_kernel, cudaFuncAttributeMaxDynamicSharedMemorySize, gm::SMEM);
  }
  void *xn, *o, *x1, *xm, *x2, *hh;
  cudaGetSymbolAddress(&xn, g_xn); cudaGetSymbolAddress(&o, g_o); cudaGetSymbolAddress(&x1, g_x1);
  cudaGetSymbolAddress(&xm, g_xm); cudaGetSymbolAddress(&x2, g_x2); cudaGetSymbolAddress(&hh, g_h);
  RecMaps R;
  for (int i = 0; i < 3; i++) R.w[i] = make_map(d_in[2 + i], DM, NH * DH, 16);
  R.wo = make_map(Wo, NH * DH, DM, 64); R.x[0] = make_map_x(xn); R.x[1] = make_map_x1(xn);
  rec_kernel<<<96, 512, rec::SMEM>>>(R, Wo, mem0, x, 0);
  GemmMaps G;
  G.o = make_map(o, 2 * SEQ, NH * DH, 128); G.wo = make_map_wo(Wo);
  G.x1 = make_map(x1, 2 * SEQ, DM, 64); G.x1s = make_map(x1, 2 * SEQ, DM, 128);
  G.xn = make_map((bf16*)xn + (NSTEP + LAG) * 32 * DM, SEQ, DM, 64);
  G.xm = make_map(xm, 2 * SEQ, DM, 64); G.xms = make_map(xm, 2 * SEQ, DM, 128);
  G.wg = make_map(d_in[8], DM, DF, 64); G.wu = make_map(d_in[9], DM, DF, 64); G.wd = make_map(d_in[10], DF, DM, 64);
  G.h = make_map(hh, 2 * SEQ, DF, 64); G.hs = make_map(hh, 2 * SEQ, DF, 128);
  G.x = make_map(x, SEQ, DM, 64); G.x2 = make_map(x2, SEQ, DM, 64); G.out = make_map(d_out, SEQ, DM, 64); G.outs = make_map(d_out, SEQ, DM, 128);
  cudaLaunchConfig_t cfg = {};
  cfg.gridDim = dim3(g_sms & ~1); cfg.blockDim = dim3(512); cfg.dynamicSmemBytes = gm::SMEM; cfg.stream = cudaStreamPerThread;
  cudaLaunchAttribute at;
  at.id = cudaLaunchAttributeProgrammaticStreamSerialization; at.val.programmaticStreamSerializationAllowed = 1;
  cfg.attrs = &at; cfg.numAttrs = 1;
  cudaLaunchKernelEx(&cfg, gemm_kernel, G);
}
```

```cpp
#include <cuda_runtime.h>
#include <cuda_bf16.h>
#include <cuda.h>
#include <stdint.h>

#define DEVI __device__ __forceinline__
typedef __nv_bfloat16 bf16;

#define LAG 14
constexpr int SEQ = 2048, DM = 1024, NH = 32, DH = 128, DF = 3584, NSEG = 64, NSTEP = NSEG + LAG;

__device__ __align__(1024) bf16 g_xn[2][NSTEP * 32 * DM];
__device__ __align__(1024) bf16 g_o[2][SEQ * NH * DH];
__device__ __align__(1024) bf16 g_x1[2][SEQ * DM];
__device__ __align__(1024) bf16 g_xm[2][SEQ * DM];
__device__ __align__(1024) bf16 g_x2[SEQ * DM];
__device__ __align__(1024) bf16 g_h[2][SEQ * DF];
__device__ __align__(1024) uint4 g_part[256 * 32 * 8];
__device__ __align__(1024) uint32_t g_ann[2][32][64];
__device__ __align__(1024) uint4 g_mem[2][2048];
__device__ __align__(128) float2 g_stat[12][8][128];
__host__ __device__ constexpr int grp(int type, int layer, int blk) { return layer ? 16 * type + blk : 64 + (16 * type + blk) * 32; }
struct Flags {
  int xn[2][16][32];
  int dep[64 + 48 * 32];
  int taken[64];
  int rows[32];
  int part[32];
  int ticket[32];
};
__device__ __align__(128) Flags g_fl;

DEVI uint32_t smem_u32(const void* p) { return (uint32_t)__cvta_generic_to_shared(p); }
DEVI void mbar_init(uint32_t bar, uint32_t cnt) { asm volatile("mbarrier.init.shared::cta.b64 [%0], %1;" :: "r"(bar), "r"(cnt) : "memory"); }
DEVI void mbar_expect_tx(uint32_t bar, uint32_t bytes) { asm volatile("mbarrier.arrive.expect_tx.shared::cta.b64 _, [%0], %1;" :: "r"(bar), "r"(bytes) : "memory"); }
DEVI void mbar_arrive(uint32_t bar) { asm volatile("mbarrier.arrive.shared::cta.b64 _, [%0];" :: "r"(bar) : "memory"); }
DEVI bool mbar_try(uint32_t bar, uint32_t parity) {
  uint32_t p;
  asm volatile("{.reg .pred p; mbarrier.try_wait.parity.shared::cta.b64 p, [%1], %2; selp.u32 %0, 1, 0, p;}" : "=r"(p) : "r"(bar), "r"(parity) : "memory");
  return p;
}
DEVI bool mbar_test(uint32_t bar, uint32_t parity) {
  uint32_t p;
  asm volatile("{.reg .pred p; mbarrier.test_wait.parity.shared::cta.b64 p, [%1], %2; selp.u32 %0, 1, 0, p;}" : "=r"(p) : "r"(bar), "r"(parity) : "memory");
  return p;
}
constexpr int SPIN_BUDGET = 1 << 20;
DEVI void mbar_wait(uint32_t bar, uint32_t parity, int& budget) {
  while (!mbar_try(bar, parity)) { if (--budget < 0) break; }
}
DEVI void trap_if_spent(int budget) { asm volatile("{.reg .pred p; setp.le.s32 p, %0, 0; @p trap;}" :: "r"(budget) : "memory"); }
DEVI void fault_if_spent(int budget) { asm volatile("{.reg .pred p; setp.le.s32 p, %0, 0; @p st.global.u32 [%1], 0;}" :: "r"(budget), "l"(0ull) : "memory"); }
DEVI uint32_t mapa(uint32_t addr, uint32_t rank) { uint32_t r; asm("mapa.shared::cluster.u32 %0, %1, %2;" : "=r"(r) : "r"(addr), "r"(rank)); return r; }
DEVI void cluster_sync() { asm volatile("barrier.cluster.arrive.relaxed.aligned; barrier.cluster.wait.aligned;" ::: "memory"); }
DEVI void fence_mbar_init() { asm volatile("fence.mbarrier_init.release.cluster;" ::: "memory"); }
DEVI void fence_proxy_async() { asm volatile("fence.proxy.async.shared::cta;" ::: "memory"); }
DEVI void tma_load_2d(uint32_t dst, const CUtensorMap* m, int c0, int c1, uint32_t bar) {
  asm volatile("cp.async.bulk.tensor.2d.shared::cluster.global.mbarrier::complete_tx::bytes [%0], [%1, {%3, %4}], [%2];"
    :: "r"(dst), "l"(m), "r"(bar), "r"(c0), "r"(c1) : "memory");
}
DEVI void tma_load_5d(uint32_t dst, const CUtensorMap* m, int c0, int c4, uint32_t bar) {
  asm volatile("cp.async.bulk.tensor.5d.shared::cluster.global.mbarrier::complete_tx::bytes [%0], [%1, {%3, %5, %5, %5, %4}], [%2];"
    :: "r"(dst), "l"(m), "r"(bar), "r"(c0), "r"(c4), "r"(0) : "memory");
}
DEVI void tma_prefetch_2d(const CUtensorMap* m, int c0, int c1) {
  asm volatile("cp.async.bulk.prefetch.tensor.2d.L2.global [%0, {%1, %2}];" :: "l"(m), "r"(c0), "r"(c1) : "memory");
}
DEVI void tma_prefetch_5d(const CUtensorMap* m, int c0, int c4) {
  asm volatile("cp.async.bulk.prefetch.tensor.5d.L2.global [%0, {%1, %3, %3, %3, %2}];" :: "l"(m), "r"(c0), "r"(c4), "r"(0) : "memory");
}
#define ELECT "{.reg .pred p; elect.sync _|p, 0xffffffff;\n @p "
DEVI void e_expect_tx(uint32_t bar, uint32_t bytes) { asm volatile(ELECT "mbarrier.arrive.expect_tx.shared::cta.b64 _, [%0], %1;}" :: "r"(bar), "r"(bytes) : "memory"); }
DEVI void e_arrive(uint32_t bar) { asm volatile(ELECT "mbarrier.arrive.shared::cta.b64 _, [%0];}" :: "r"(bar) : "memory"); }
DEVI void e_arrive_cl(uint32_t bar) { asm volatile(ELECT "mbarrier.arrive.shared::cluster.b64 _, [%0];}" :: "r"(bar) : "memory"); }
constexpr uint64_t EVICT_NORMAL = 0x1000000000000000ull, EVICT_FIRST = 0x12F0000000000000ull;
DEVI void e_tma_2d(uint32_t dst, const CUtensorMap* m, int c0, int c1, uint32_t bar, uint64_t pol = EVICT_NORMAL) {
  asm volatile(ELECT "cp.async.bulk.tensor.2d.shared::cluster.global.mbarrier::complete_tx::bytes.L2::cache_hint [%0], [%1, {%3, %4}], [%2], %5;}"
    :: "r"(dst), "l"(m), "r"(bar), "r"(c0), "r"(c1), "l"(pol) : "memory");
}
DEVI void e_tma_2d_mc(uint32_t dst, const CUtensorMap* m, int c0, int c1, uint32_t bar, uint64_t pol = EVICT_NORMAL) {
  asm volatile(ELECT "cp.async.bulk.tensor.2d.shared::cluster.global.mbarrier::complete_tx::bytes.multicast::cluster.L2::cache_hint [%0], [%1, {%3, %4}], [%2], %5, %6;}"
    :: "r"(dst), "l"(m), "r"(bar), "r"(c0), "r"(c1), "h"((unsigned short)3), "l"(pol) : "memory");
}
DEVI void e_st_async32(uint32_t a, uint32_t x, uint32_t bar) {
  asm volatile(ELECT "st.async.weak.shared::cluster.mbarrier::complete_tx::bytes.b32 [%0], %1, [%2];}" :: "r"(a), "r"(x), "r"(bar) : "memory");
}
DEVI void e_tma_store_2d(const CUtensorMap* m, uint32_t src, int c0, int c1) {
  asm volatile(ELECT "cp.async.bulk.tensor.2d.global.shared::cta.bulk_group [%0, {%2, %3}], [%1];}" :: "l"(m), "r"(src), "r"(c0), "r"(c1) : "memory");
}
DEVI void e_flag_add(int* p, int v = 1) {
  asm volatile("{.reg .pred p; elect.sync _|p, 0xffffffff;\n fence.proxy.async.global; @p red.release.gpu.global.add.s32 [%0], %1;}" :: "l"(p), "r"(v) : "memory");
}
DEVI void e_flag_add_bulk(int* p, int v) {
  asm volatile(ELECT "red.relaxed.gpu.global.add.s32 [%0], %1;}" :: "l"(p), "r"(v) : "memory");
}
DEVI int e_ticket(int* p, int n = 1) { int v = 0; asm volatile(ELECT "atom.relaxed.gpu.global.add.s32 %0, [%1], %2;}" : "+r"(v) : "l"(p), "r"(n) : "memory"); __syncwarp(); return v; }
DEVI int bcast(int v) { return __reduce_max_sync(0xffffffffu, v); }
DEVI int ld_relaxed(const int* p) { int v; asm volatile("ld.relaxed.gpu.global.s32 %0, [%1];" : "=r"(v) : "l"(p) : "memory"); return v; }
DEVI int ld_acquire(const int* p) { int v; asm volatile("ld.acquire.gpu.global.s32 %0, [%1];" : "=r"(v) : "l"(p) : "memory"); return __shfl_sync(0xffffffffu, v, 0); }
DEVI void e_tma_3d(uint32_t dst, const CUtensorMap* m, int c0, int c1, int c2, uint32_t bar) {
  asm volatile(ELECT "cp.async.bulk.tensor.3d.shared::cluster.global.mbarrier::complete_tx::bytes [%0], [%1, {%3, %4, %5}], [%2];}"
    :: "r"(dst), "l"(m), "r"(bar), "r"(c0), "r"(c1), "r"(c2) : "memory");
}
DEVI void e_tma_5d(uint32_t dst, const CUtensorMap* m, int c0, int c4, uint32_t bar) {
  asm volatile(ELECT "cp.async.bulk.tensor.5d.shared::cluster.global.mbarrier::complete_tx::bytes [%0], [%1, {%3, %5, %5, %5, %4}], [%2];}"
    :: "r"(dst), "l"(m), "r"(bar), "r"(c0), "r"(c4), "r"(0) : "memory");
}
DEVI void e_bulk_g2s(uint32_t dst, const void* src, uint32_t bytes, uint32_t bar) {
  asm volatile(ELECT "cp.async.bulk.shared::cluster.global.mbarrier::complete_tx::bytes [%0], [%1], %2, [%3];}" :: "r"(dst), "l"(src), "r"(bytes), "r"(bar) : "memory");
}
DEVI void e_prefetch(const void* src, uint32_t bytes) {
  asm volatile(ELECT "cp.async.bulk.prefetch.L2.global [%0], %1;}" :: "l"(src), "r"(bytes) : "memory");
}
DEVI void bulk_commit() { asm volatile("cp.async.bulk.commit_group;" ::: "memory"); }
template<int N> DEVI void bulk_wait_read() { asm volatile("cp.async.bulk.wait_group.read %0;" :: "n"(N) : "memory"); }
template<int N> DEVI void bulk_wait() { asm volatile("cp.async.bulk.wait_group %0;" :: "n"(N) : "memory"); }
template<int ID, int N> DEVI void nbar_sync() { asm volatile("bar.sync %0, %1;" :: "n"(ID), "n"(N) : "memory"); }
template<int ID, int N> DEVI void nbar_arrive() { asm volatile("bar.arrive %0, %1;" :: "n"(ID), "n"(N) : "memory"); }
DEVI void nbar_sync_r(int id, int n) { asm volatile("bar.sync %0, %1;" :: "r"(id), "r"(n) : "memory"); }
DEVI void nbar_arrive_r(int id, int n) { asm volatile("bar.arrive %0, %1;" :: "r"(id), "r"(n) : "memory"); }
template<int R> DEVI void reg_inc() { asm volatile("setmaxnreg.inc.sync.aligned.u32 %0;" :: "n"(R)); }
template<int R> DEVI void reg_dec() { asm volatile("setmaxnreg.dec.sync.aligned.u32 %0;" :: "n"(R)); }
DEVI void wg_fence() { asm volatile("wgmma.fence.sync.aligned;" ::: "memory"); }
DEVI void wg_commit() { asm volatile("wgmma.commit_group.sync.aligned;" ::: "memory"); }
template<int N> DEVI void wg_wait() { asm volatile("wgmma.wait_group.sync.aligned %0;" :: "n"(N) : "memory"); }
DEVI uint32_t pack_bf16(float lo, float hi) { uint32_t r; asm("cvt.rn.bf16x2.f32 %0, %1, %2;" : "=r"(r) : "f"(hi), "f"(lo)); return r; }
DEVI float bf_lo(uint32_t v) { return __uint_as_float(v << 16); }
DEVI float bf_hi(uint32_t v) { return __uint_as_float(v & 0xffff0000u); }
DEVI uint32_t movmat(uint32_t a) { uint32_t r; asm volatile("movmatrix.sync.aligned.m8n8.trans.b16 %0, %1;" : "=r"(r) : "r"(a)); return r; }
DEVI void ldsm4(uint32_t addr, uint32_t& r0, uint32_t& r1, uint32_t& r2, uint32_t& r3) {
  asm volatile("ldmatrix.sync.aligned.m8n8.x4.shared.b16 {%0,%1,%2,%3}, [%4];" : "=r"(r0), "=r"(r1), "=r"(r2), "=r"(r3) : "r"(addr) : "memory");
}
DEVI void ldsm4t(uint32_t addr, uint32_t& r0, uint32_t& r1, uint32_t& r2, uint32_t& r3) {
  asm volatile("ldmatrix.sync.aligned.m8n8.x4.trans.shared.b16 {%0,%1,%2,%3}, [%4];" : "=r"(r0), "=r"(r1), "=r"(r2), "=r"(r3) : "r"(addr) : "memory");
}
DEVI void stsm4(uint32_t addr, uint32_t r0, uint32_t r1, uint32_t r2, uint32_t r3) {
  asm volatile("stmatrix.sync.aligned.m8n8.x4.shared.b16 [%0], {%1,%2,%3,%4};" :: "r"(addr), "r"(r0), "r"(r1), "r"(r2), "r"(r3) : "memory");
}
DEVI uint4 lds128(uint32_t a) { uint4 v; asm volatile("ld.shared.v4.u32 {%0,%1,%2,%3}, [%4];" : "=r"(v.x), "=r"(v.y), "=r"(v.z), "=r"(v.w) : "r"(a) : "memory"); return v; }
DEVI uint32_t lds32v(uint32_t a) { uint32_t v; asm volatile("ld.volatile.shared.u32 %0, [%1];" : "=r"(v) : "r"(a) : "memory"); return v; }
DEVI void sts32v(uint32_t a, uint32_t v) { asm volatile("st.volatile.shared.u32 [%0], %1;" :: "r"(a), "r"(v) : "memory"); }
DEVI void st_async128(uint32_t a, uint32_t x, uint32_t y, uint32_t z, uint32_t w, uint32_t bar) {
  asm volatile("st.async.weak.shared::cluster.mbarrier::complete_tx::bytes.v4.b32 [%0], {%1,%2,%3,%4}, [%5];" :: "r"(a), "r"(x), "r"(y), "r"(z), "r"(w), "r"(bar) : "memory");
}
DEVI void st_async32(uint32_t a, uint32_t x, uint32_t bar) {
  asm volatile("st.async.weak.shared::cluster.mbarrier::complete_tx::bytes.b32 [%0], %1, [%2];" :: "r"(a), "r"(x), "r"(bar) : "memory");
}
DEVI void st_cl128(bool own, uint32_t a, uint32_t x, uint32_t y, uint32_t z, uint32_t w, uint32_t bar) {
  asm volatile("{.reg .pred p; setp.ne.u32 p, %6, 0; @p st.shared.v4.b32 [%0], {%1,%2,%3,%4};\n"
               "@!p st.async.weak.shared::cluster.mbarrier::complete_tx::bytes.v4.b32 [%0], {%1,%2,%3,%4}, [%5];}"
               :: "r"(a), "r"(x), "r"(y), "r"(z), "r"(w), "r"(bar), "r"((uint32_t)own) : "memory");
}
DEVI void st_cl32(bool own, uint32_t a, uint32_t x, uint32_t bar) {
  asm volatile("{.reg .pred p; setp.ne.u32 p, %3, 0; @p st.shared.b32 [%0], %1;\n"
               "@!p st.async.weak.shared::cluster.mbarrier::complete_tx::bytes.b32 [%0], %1, [%2];}" :: "r"(a), "r"(x), "r"(bar), "r"((uint32_t)own) : "memory");
}
DEVI uint4 ldg_rlx128(const void* p) {
  uint4 v;
  asm volatile("ld.relaxed.gpu.global.v4.b32 {%0,%1,%2,%3}, [%4];" : "=r"(v.x), "=r"(v.y), "=r"(v.z), "=r"(v.w) : "l"(p) : "memory");
  return v;
}
DEVI void stg_rlx128(void* p, uint32_t x, uint32_t y, uint32_t z, uint32_t w) {
  asm volatile("st.relaxed.gpu.global.v4.b32 [%0], {%1,%2,%3,%4};" :: "l"(p), "r"(x), "r"(y), "r"(z), "r"(w) : "memory");
}
DEVI void stg128(void* p, uint32_t x, uint32_t y, uint32_t z, uint32_t w) {
  asm volatile("st.global.v4.b32 [%0], {%1,%2,%3,%4};" :: "l"(p), "r"(x), "r"(y), "r"(z), "r"(w) : "memory");
}
DEVI void stg_rlx64(void* p, uint32_t x, uint32_t y) { asm volatile("st.relaxed.gpu.global.v2.b32 [%0], {%1,%2};" :: "l"(p), "r"(x), "r"(y) : "memory"); }
DEVI void stg_rlx32(void* p, uint32_t x) { asm volatile("st.relaxed.gpu.global.b32 [%0], %1;" :: "l"(p), "r"(x) : "memory"); }
DEVI uint32_t clock32() { uint32_t c; asm volatile("mov.u32 %0, %%clock;" : "=r"(c) :: "memory"); return c; }
DEVI uint32_t gtime() { uint32_t c; asm volatile("mov.u32 %0, %%globaltimer_lo;" : "=r"(c) :: "memory"); return c; }
DEVI void wait_time(uint32_t t, int& budget) { while ((int)(gtime() - t) < 0 && --budget > 0) {} }
DEVI uint2 ldg_rlx64(const void* p) { uint2 v; asm volatile("ld.relaxed.gpu.global.v2.b32 {%0,%1}, [%2];" : "=r"(v.x), "=r"(v.y) : "l"(p) : "memory"); return v; }
DEVI void sts16(uint32_t a, uint32_t x) { asm volatile("st.shared.b16 [%0], %1;" :: "r"(a), "h"((unsigned short)x) : "memory"); }
DEVI void sts128(uint32_t a, uint32_t x) { asm volatile("st.shared.v4.b32 [%0], {%1,%1,%1,%1};" :: "r"(a), "r"(x) : "memory"); }
DEVI void arrive_if_eq(uint32_t bar, int a, int b) { asm volatile("{.reg .pred p; setp.eq.s32 p, %1, %2; @p mbarrier.arrive.shared::cta.b64 _, [%0];}" :: "r"(bar), "r"(a), "r"(b) : "memory"); }
DEVI void arrive_cl_if_eq(uint32_t bar, int a, int b) { asm volatile("{.reg .pred p; setp.eq.s32 p, %1, %2; @p mbarrier.arrive.shared::cluster.b64 _, [%0];}" :: "r"(bar), "r"(a), "r"(b) : "memory"); }
template<int ID, int N> DEVI bool nbar_or(bool x) {
  uint32_t r;
  asm volatile("{.reg .pred p, q; setp.ne.u32 p, %1, 0; bar.red.or.pred q, %2, %3, p; selp.u32 %0, 1, 0, q;}" : "=r"(r) : "r"((uint32_t)x), "n"(ID), "n"(N) : "memory");
  return __any_sync(0xffffffffu, r);
}
DEVI void spin_until(uint32_t t0, int d) { while ((int)(clock32() - t0) < d) {} }
DEVI void flag_wait(const int* p, int n, int& budget) {
  while (ld_acquire(p) < n && --budget > 0) __nanosleep(128);
  asm volatile("fence.proxy.async.global;" ::: "memory");
}

#define F4(C, o)  C(d[o+0]), C(d[o+1]), C(d[o+2]), C(d[o+3])
#define F8(C, o)  F4(C, o), F4(C, o+4)
#define F32(C, o) F8(C, o), F8(C, o+8), F8(C, o+16), F8(C, o+24)
#define R4  "{%0,%1,%2,%3}"
#define R8  "{%0,%1,%2,%3,%4,%5,%6,%7}"
#define R16 "{%0,%1,%2,%3,%4,%5,%6,%7,%8,%9,%10,%11,%12,%13,%14,%15}"
#define R20 "{%0,%1,%2,%3,%4,%5,%6,%7,%8,%9,%10,%11,%12,%13,%14,%15,%16,%17,%18,%19}"
#define R32 "{%0,%1,%2,%3,%4,%5,%6,%7,%8,%9,%10,%11,%12,%13,%14,%15,%16,%17,%18,%19,%20,%21,%22,%23,%24,%25,%26,%27,%28,%29,%30,%31}"
#define R64 "{%0,%1,%2,%3,%4,%5,%6,%7,%8,%9,%10,%11,%12,%13,%14,%15,%16,%17,%18,%19,%20,%21,%22,%23,%24,%25,%26,%27,%28,%29,%30,%31," \
  "%32,%33,%34,%35,%36,%37,%38,%39,%40,%41,%42,%43,%44,%45,%46,%47,%48,%49,%50,%51,%52,%53,%54,%55,%56,%57,%58,%59,%60,%61,%62,%63}"
template<uint32_t OFF, uint32_t LBO, uint32_t SBO, uint32_t SW, int T> struct Op {
  static constexpr uint32_t lo = (OFF >> 4) | ((LBO >> 4) << 16), hi = (SBO >> 4) | (SW << 30);
  static constexpr int t = T;
};
DEVI uint32_t desc_base(uint32_t addr) { return (addr & 0x3FFFF) >> 4; }
#define RS_ASM(SHAPE, REGS, A0, A1, A2, A3, B, LO, HI, T, SD) \
  "{.reg .b64 tb; .reg .b32 lb; add.u32 lb, " B ", " LO "; mov.b64 tb, {lb, " HI "};\n" \
  "wgmma.mma_async.sync.aligned." SHAPE ".f32.bf16.bf16 " REGS ", {" A0 "," A1 "," A2 "," A3 "}, tb, " SD ", 1, 1, " T ";}"
#define WG_RS(NAME, SHAPE, REGS, LIST, ...) \
  template<int ACC, class OB> DEVI void NAME(float* d, const uint32_t* a, uint32_t b) { \
    if (ACC) asm volatile(RS_ASM(SHAPE, REGS, __VA_ARGS__) \
      : LIST("+f") : "r"(a[0]), "r"(a[1]), "r"(a[2]), "r"(a[3]), "r"(b), "n"(OB::lo), "n"(OB::hi), "n"(OB::t), "n"(ACC & 1)); \
    else asm volatile(RS_ASM(SHAPE, REGS, __VA_ARGS__) \
      : LIST("=f") : "r"(a[0]), "r"(a[1]), "r"(a[2]), "r"(a[3]), "r"(b), "n"(OB::lo), "n"(OB::hi), "n"(OB::t), "n"(0)); \
  }
#define SS_ASM(SHAPE, REGS, A, B, LA, HA, TA, LB, HB, TB, SD) \
  "{.reg .b64 ta, tb; .reg .b32 la, lb; add.u32 la, " A ", " LA "; mov.b64 ta, {la, " HA "}; add.u32 lb, " B ", " LB "; mov.b64 tb, {lb, " HB "};\n" \
  "wgmma.mma_async.sync.aligned." SHAPE ".f32.bf16.bf16 " REGS ", ta, tb, " SD ", 1, 1, " TA ", " TB ";}"
#define WG_SS(NAME, SHAPE, REGS, LIST, ...) \
  template<int ACC, class OA, class OB> DEVI void NAME(float* d, uint32_t a, uint32_t b) { \
    if (ACC) asm volatile(SS_ASM(SHAPE, REGS, __VA_ARGS__) \
      : LIST("+f") : "r"(a), "r"(b), "n"(OA::lo), "n"(OA::hi), "n"(OA::t), "n"(OB::lo), "n"(OB::hi), "n"(OB::t), "n"(ACC & 1)); \
    else asm volatile(SS_ASM(SHAPE, REGS, __VA_ARGS__) \
      : LIST("=f") : "r"(a), "r"(b), "n"(OA::lo), "n"(OA::hi), "n"(OA::t), "n"(OB::lo), "n"(OB::hi), "n"(OB::t), "n"(0)); \
  }
#define L4(C)  F4(C, 0)
#define L8(C)  F8(C, 0)
#define L16(C) F8(C, 0), F8(C, 8)
#define L20(C) F8(C, 0), F8(C, 8), F4(C, 16)
#define L32(C) F32(C, 0)
WG_RS(wg_rs8, "m64n8k16", R4, L4, "%4", "%5", "%6", "%7", "%8", "%9", "%10", "%11", "%12")
WG_RS(wg_rs16, "m64n16k16", R8, L8, "%8", "%9", "%10", "%11", "%12", "%13", "%14", "%15", "%16")
WG_RS(wg_rs32, "m64n32k16", R16, L16, "%16", "%17", "%18", "%19", "%20", "%21", "%22", "%23", "%24")
WG_SS(wg_ss32, "m64n32k16", R16, L16, "%16", "%17", "%18", "%19", "%20", "%21", "%22", "%23", "%24")
WG_RS(wg_rs64, "m64n64k16", R32, L32, "%32", "%33", "%34", "%35", "%36", "%37", "%38", "%39", "%40")
WG_SS(wg_ss8, "m64n8k16", R4, L4, "%4", "%5", "%6", "%7", "%8", "%9", "%10", "%11", "%12")
WG_SS(wg_ss16, "m64n16k16", R8, L8, "%8", "%9", "%10", "%11", "%12", "%13", "%14", "%15", "%16")
WG_SS(wg_ss40, "m64n40k16", R20, L20, "%20", "%21", "%22", "%23", "%24", "%25", "%26", "%27", "%28")
WG_SS(wg_ss64, "m64n64k16", R32, L32, "%32", "%33", "%34", "%35", "%36", "%37", "%38", "%39", "%40")
#define L64(C) F32(C, 0), F32(C, 32)
WG_SS(wg_ss128, "m64n128k16", R64, L64, "%64", "%65", "%66", "%67", "%68", "%69", "%70", "%71", "%72")
template<int I> struct IC { __host__ __device__ constexpr operator int() const { return I; } };
template<int I, int N, class F> DEVI void sfor(F&& f) {
  if constexpr (I < N) { f(IC<I>{}); sfor<I + 1, N>(f); }
}

#define R_CL 6
namespace rec {
constexpr int NHI = 36, NLO = 5, NRS = NHI + NLO, NSS = 64 - NRS;
constexpr uint32_t WS = 0;
constexpr uint32_t WO = 2 * NSS * 2048;
constexpr uint32_t RING = WO + 65536;
constexpr uint32_t QB = RING + 40960, RG = 2080, POSQ = 0x64210, POSK = 0xB9753, POSV = 0xEDCA8;
#define JA 2
constexpr uint32_t WA = QB;
constexpr uint32_t OM = QB + 9 * RG, OMS = 2 * RG;
constexpr uint32_t OM2 = QB + 16384, OM2S = 2048;
constexpr uint32_t WH = QB + 20480;
constexpr uint32_t B_PART = QB + 15 * RG - 32, B_ML0 = B_PART + 8, REDO = B_PART + 16;
constexpr uint32_t PM0 = QB + 16384, PM1 = QB + 15 * RG, PM2 = PM1 + 256;
constexpr uint32_t BARS = PM2 + 128;
constexpr uint32_t B_FULL = BARS, B_EMPTY = BARS + 40, B_MLAND = BARS + 80, B_QK = BARS + 112, B_V = BARS + 120, B_OM = BARS + 128,
                   B_WA = BARS + 136, B_SDONE = BARS + 144, B_BFREE = BARS + 152, B_W1 = PM1, B_W2 = PM1 + 8, B_WO = PM1 + 16;
constexpr uint32_t SMEM = BARS + 160;
static_assert(SMEM <= 232448 && QB % 1024 == 0, "smem map");
constexpr int R1 = (PM1 - WO) / 4096, RB = NRS - R1;
__host__ __device__ constexpr uint32_t stage_at(int t, int r) { return r < R1 ? WO + (t * R1 + r) * 2048 : WS + (t * NSS + NSS - RB + r - R1) * 2048; }
constexpr int NB_WO = 1, NB_ST = 2, NB_P = 3, NB_TR = 4, NB_X = 5, NB_G = 6, NB_G1 = 7, NB_G2 = 8, NB_G4 = 9, NB_S = 10;
__host__ __device__ constexpr bool is_lo(int j) { return j % 12 == 8; }
__host__ __device__ constexpr int lo_before(int j) { return (j + 3) / 12; }
__host__ __device__ constexpr int ss_before(int j) { return (j - lo_before(j)) * NSS / (64 - NLO); }
__host__ __device__ constexpr bool is_ss(int j) { return ss_before(j + 1) != ss_before(j); }
__host__ __device__ constexpr int reg_idx(int j) { return is_lo(j) ? NHI + lo_before(j) : j - ss_before(j) - lo_before(j); }
template<int j> using OpW = Op<WS + ss_before(j) * 2048, 16, 1024, 1, 1>;
#define P_G1 1
#define P_G2 3
#define P_G2L 0
#define P_OS 1
#define P_NA 6
#define P_G4 10
#define P_G5 12
#define P_FW 1
#define P_SEND 0xff3210ffu
#define P_WB 2
#define P_WOL 0
#define P_G4L 2
#define P_S1 1
#define P_S2 2
#define P_SPEC 1
#define P_S0 3
#define P_MB 0
#define P_S4 5
#define P_S5 8
constexpr uint32_t SLOT1 = 0x32410324, USE1 = 0x22111110;
DEVI bool single(int s) { return s < LAG - 1 || s >= NSEG - 1; }
DEVI uint32_t flip(int s) { return (s < LAG - 1 ? s + 1 : s < NSEG - 1 ? LAG : LAG + s + 1) & 1; }
#define TUN(i, v) (v)
}
#define PROFW(wq, i)
#define SPROF(i)
DEVI uint32_t mapr(int h, uint32_t addr, int rank) { return mapa(addr, rank + (R_CL == 6 ? (h & 1) * 3 : 0)); }
template<int N> DEVI void pin(float* d) {
#pragma unroll
  for (int i = 0; i < N; i++) asm volatile("" : "+f"(d[i]) :: "memory");
}
DEVI void keep(const void* a) { asm volatile("{.reg .pred p; setp.eq.u64 p, %0, 0; vote.sync.any.pred p, p, 0xffffffff; @p exit;}" :: "l"(a) : "memory"); }
DEVI int lane_reg() { return __shfl_sync(0xffffffffu, threadIdx.x & 31, threadIdx.x & 31); }
#define LANE_NOW [[maybe_unused]] const int lane = lane0 + ((uint32_t)budget >> 30), g = lane >> 2, c = lane & 3

DEVI void rec_proj(const uint32_t sb, const int h, const int rank, const int w, const CUtensorMap* mW, const uint32_t zero) {
  using namespace rec;
  const int lane0 = lane_reg(), wg = w >> 2, ww = w & 3;
  int budget = SPIN_BUDGET;
  uint32_t wr[NRS * 4];
  {
    LANE_NOW;
    const uint32_t wsw = ((lane & 7) + (lane >> 4) * 8) * 128 + (((ww * 2 + ((lane >> 3) & 1)) ^ (lane & 7)) << 4);
    SPROF(0);
    mbar_wait(sb + B_W1, 0, budget);
    SPROF(1);
#pragma unroll
    for (int r = 0; r < NRS; r++) ldsm4t(sb + stage_at(wg, r) + wsw, wr[4*r], wr[4*r+1], wr[4*r+2], wr[4*r+3]);
    fence_proxy_async();
    nbar_sync<NB_ST, 256>();
    if (w < 4) {
      const int j = w * 16 + (lane >> 1), t = lane & 1;
      if (is_ss(j) && ss_before(j) >= NSS - RB) tma_load_2d(sb + WS + (t * NSS + ss_before(j)) * 2048, mW, h * DH + t * 64, j * 16, sb + B_W2);
    }
    __syncwarp();
    cluster_sync();
  }
  const uint32_t d0 = desc_base(sb), da = d0 + wg * (NSS * 128);
  const uint32_t pos = rank == 0 ? POSQ : rank == 1 ? POSK : POSV, bar = rank == 2 ? B_V : B_QK;
  uint32_t stg[2][4] = {}, pk[16] = {};
  auto stage = [&](uint32_t* t, int r) {
#pragma unroll
    for (int i = 0; i < 4; i++) asm volatile("xor.b32 %0, %1, %2;" : "+r"(t[i]) : "r"(wr[4 * r + i]), "r"(zero));
  };
#pragma unroll 1
  for (int s = -1; s < NSTEP; s++) {
    const uint32_t fl = flip(s);
    if (s >= 0) {
      float d[8];
      auto steps = [&](auto J0, auto J1, auto A0) {
        wg_fence();
        sfor<J0, J1>([&](auto J) {
          constexpr int j = J, acc = j ? 1 : A0;
          typedef Op<RING + j * 512, 256, 128, 0, 1> OB;
          if constexpr (is_ss(j)) wg_ss16<acc, OpW<j>, OB>(d, da, d0);
          else wg_rs16<acc, OB>(d, is_lo(j) ? stg[lo_before(j) & 1] : wr + 4 * reg_idx(j), d0);
        });
        wg_commit();
      };
      stage(stg[0], NHI);
      mbar_wait(sb + (P_SPEC ? B_ML0 : B_FULL), P_SPEC ? s & 1 : 0, budget);
      PROFW(0, 16);
      sfor<0, 8>([&](auto E) {
        constexpr int e = E, q = e >> 1;
        steps(IC<8 * e>{}, IC<8 * e + 8>{}, IC<0>{});
        if constexpr (e == 1 && P_SPEC) {
          mbar_wait(sb + B_FULL, 0, budget);
          if (__any_sync(0xffffffffu, lds32v(sb + REDO))) { wg_wait<0>(); steps(IC<0>{}, IC<16>{}, IC<2>{}); }
        }
        if constexpr (((P_SEND >> (4 * e)) & 15) == 0) { if (s > 0) mbar_wait(sb + B_BFREE, (s & 1) ^ 1, budget); }
        if constexpr (e > 0 && !(e & 1)) {
          wg_wait<1>();
          arrive_if_eq(sb + B_EMPTY + 8 * (q - 1), lane0, ww * 32);
        }
        if constexpr (!(e & 1)) stage(stg[(q + 1) & 1], NHI + q + 1);
        if constexpr (e < 6 && (e & 1) == P_FW) mbar_wait(sb + B_FULL + 8 * (q + 1), q ? fl : 0, budget);
        if constexpr (((P_SEND >> (4 * e)) & 15) < 4) {
          constexpr int n = (P_SEND >> (4 * e)) & 15;
          LANE_NOW;
          const uint32_t r = mapr(h, sb, n >> 1);
          uint32_t t[4];
#pragma unroll
          for (int i = 0; i < 4; i++) { if (n == 0) t[i] = pk[i]; else asm volatile("xor.b32 %0, %1, %2;" : "=r"(t[i]) : "r"(pk[4*n+i]), "r"(zero)); }
          st_cl128(rank == n >> 1, r + QB + ((pos >> (4 + 4 * c)) & 15) * RG + w * 256 + (n & 1) * 128 + g * 16, t[0], t[1], t[2], t[3], r + bar);
        }
      });
      LANE_NOW;
      const uint32_t dst = QB + (pos & 15) * RG + w * 256 + lane * 4;
      wg_wait<0>();
      pin<8>(d);
      {
        const uint32_t x0 = pack_bf16(d[0], d[1]), x1 = pack_bf16(d[2], d[3]), y0 = pack_bf16(d[4], d[5]), y1 = pack_bf16(d[6], d[7]);
        const uint32_t r = mapr(h, sb, rank == 0);
        if (rank < 2) { sts32v(sb + dst, rank ? y0 : x0); sts32v(sb + dst + 128, rank ? y1 : x1); fence_proxy_async(); }
        st_async32(r + dst, rank ? x0 : y0, r + bar); st_async32(r + dst + 128, rank ? x1 : y1, r + bar);
        if (rank < 2) e_arrive(sb + B_QK);
        else { const uint32_t r1 = mapr(h, sb, 1); st_async32(r1 + dst, y0, r1 + bar); st_async32(r1 + dst + 128, y1, r1 + bar); }
      }
      PROFW(0, 17);
      if (s == NSTEP - 1) break;
      arrive_if_eq(sb + B_EMPTY + 24, lane0, ww * 32);
    } else {
      e_arrive(sb + B_EMPTY + 8 * ww);
      mbar_wait(sb + B_W2, 0, budget);
      SPROF(2);
    }
    const bool gate = rank < 2 && s >= 0;
    if (single(s)) {
      float d[16];
      sfor<0, 8>([&](auto C) {
        constexpr int cc = C, sl = (SLOT1 >> (4 * cc)) & 15;
        if constexpr (cc == 0) mbar_wait(sb + B_FULL + 8 * sl, 0, budget);
        if constexpr (cc == P_S1) { if (gate) nbar_sync<NB_G1, 384>(); }
        if constexpr (cc == P_S2) { if (gate) nbar_sync<NB_G2, 384>(); }
        if constexpr (cc == P_S0) nbar_sync<NB_WO, 384>();
        if constexpr (cc == P_S4 || cc == P_S5) { if (gate && cc == (rank ? P_S5 : P_S4)) nbar_sync<NB_G4, 384>(); }
        if constexpr (lo_before(cc * 8 + 8) != lo_before(cc * 8)) stage(stg[0], NHI + lo_before(cc * 8));
        wg_fence();
        sfor<0, 8>([&](auto I) {
          constexpr int i = I, j = cc * 8 + i;
          typedef Op<RING + sl * 8192 + (i >> 2) * 4096 + (i & 3) * 32, 16, 1024, 1, 0> OB;
          if constexpr (is_ss(j)) wg_ss32<j != 0, OpW<j>, OB>(d, da, d0);
          else wg_rs32<j != 0, OB>(d, is_lo(j) ? stg[0] : wr + 4 * reg_idx(j), d0);
        });
        wg_commit();
        if constexpr (cc < 7) {
          constexpr int sn = (SLOT1 >> (4 * cc + 4)) & 15;
          mbar_wait(sb + B_FULL + 8 * sn, ((USE1 >> (4 * cc + 4)) & 1) ^ (sn >> 1 == 1 ? fl : 0), budget);
        }
        wg_wait<0>();
        arrive_if_eq(sb + B_EMPTY + 8 * sl, lane0, ww * 32);
      });
      pin<16>(d);
      if (gate && (rank ? P_S5 : P_S4) == 8) nbar_arrive<NB_G4, 384>();
      PROFW(0, 20);
#pragma unroll
      for (int i = 0; i < 8; i++) pk[i] = pk[8 + i] = pack_bf16(d[4 * (i & 3) + ((i >> 1) & 2)], d[4 * (i & 3) + ((i >> 1) & 2) + 1]);
      continue;
    }
    float d[32];
    sfor<0, 16>([&](auto C) {
      constexpr int cc = C, sl = (cc + 4) % 5;
      if constexpr (cc == 0) mbar_wait(sb + B_FULL + 8 * sl, 0, budget);
      if constexpr (cc == P_G1) { if (gate) nbar_sync<NB_G1, 384>(); }
      if constexpr (cc == P_G2) { if (gate) nbar_sync<NB_G2, 384>(); }
      if constexpr (cc == P_NA) {
        PROFW(0, 18);
        nbar_sync<NB_WO, 384>();
      }
      if constexpr (cc == P_G4 || cc == P_G5) { if (gate && cc == (rank ? P_G5 : P_G4)) nbar_sync<NB_G4, 384>(); }
      wg_fence();
      sfor<0, 4>([&](auto I) {
        constexpr int i = I, j = cc * 4 + i;
        typedef Op<RING + sl * 8192 + i * 32, 16, 1024, 1, 0> OB;
        if constexpr (is_ss(j)) wg_ss64<j != 0, OpW<j>, OB>(d, da, d0);
        else wg_rs64<j != 0, OB>(d, is_lo(j) ? stg[0] : wr + 4 * reg_idx(j), d0);
      });
      wg_commit();
      if constexpr (cc == P_NA) PROFW(0, 19);
      if constexpr (cc < 15) {
        if constexpr (is_lo(cc * 4 + 4)) stage(stg[0], reg_idx(cc * 4 + 4));
        mbar_wait(sb + B_FULL + 8 * ((sl + 1) % 5), ((cc + 5) / 5 + (sl == 1 || sl == 2 ? LAG : 0)) & 1, budget);
      }
      wg_wait<0>();
      arrive_if_eq(sb + B_EMPTY + 8 * sl, lane0, ww * 32);
    });
    pin<32>(d);
    if (gate && (rank ? P_G5 : P_G4) == 16) nbar_arrive<NB_G4, 384>();
    PROFW(0, 20);
#pragma unroll
    for (int i = 0; i < 16; i++) pk[i] = pack_bf16(d[16 * (i >> 3) + 4 * (i & 3) + ((i >> 1) & 2)], d[16 * (i >> 3) + 4 * (i & 3) + ((i >> 1) & 2) + 1]);
  }
}

DEVI float softmax_row(float* v, uint32_t* p) {
  constexpr float SC = 0.08838834764831845f * 1.4426950408889634f;
  float m = fmaxf(fmaxf(fmaxf(fmaxf(v[0], v[1]), fmaxf(v[2], v[3])), fmaxf(fmaxf(v[4], v[5]), fmaxf(v[6], v[7]))), fmaxf(v[8], v[9]));
  m = fmaxf(m, __shfl_xor_sync(0xffffffffu, m, 1));
  m = fmaxf(m, __shfl_xor_sync(0xffffffffu, m, 2));
  const float ms = -m * SC, mh = fmaf(m, -SC, -1.f);
#pragma unroll
  for (int i = 0; i < 10; i++) asm("ex2.approx.ftz.f32 %0, %1;" : "=f"(v[i]) : "f"(fmaf(v[i], SC, i < 8 ? ms : mh)));
#pragma unroll
  for (int n = 0; n < 5; n++) p[n] = pack_bf16(v[2*n], v[2*n+1]);
  return fmaf(v[8] + v[9], 2.f, ((v[0] + v[1]) + (v[2] + v[3])) + ((v[4] + v[5]) + (v[6] + v[7])));
}

template<bool ATT>
DEVI void rec_attn(const uint32_t sb, int h, int rank, int w, const bf16* __restrict__ Wo, const bf16* __restrict__ mem0) {
  using namespace rec;
  const int lane0 = lane_reg();
  int budget = SPIN_BUDGET;
  constexpr int NT = ATT ? 5 : 6;
  uint32_t wl[16];
  if (!ATT) {
    LANE_NOW;
#pragma unroll
    for (int i = 0; i < 16; i++) {
      const int dh = 8 * (i >> 1) + 2 * c;
      const unsigned short* p = (const unsigned short*)Wo + (size_t)(h * DH + dh) * DM + 15 * 64 + 16 * w + 8 * (i & 1) + g;
      wl[i] = p[0] | (uint32_t)p[DM] << 16;
    }
  }
  cluster_sync();
  const uint32_t d0 = desc_base(sb);
  uint32_t pph = 0;
#pragma unroll 1
  for (int s = -1; s < NSTEP; s++) {
    asm volatile("" : "+r"(h), "+r"(rank), "+r"(w));
    const uint32_t sp = s & 1;
    const int t0 = ATT ? rank + 1 : 0;
    const bool more = s + 1 < NSTEP;
    if (s == 0) mbar_wait(sb + B_WO, 0, budget);
    float hold[10] = {0, 0, 0, 0, 0, 0, 0, 0, 0, 0};
    if (ATT && s >= 0) {
      float sc[20];
      LANE_NOW;
      mbar_wait(sb + B_QK, sp, budget);
      PROFW(0, 1);
      fence_proxy_async();
      wg_fence();
      sfor<0, 8>([&](auto K) { constexpr int k = K; wg_ss40<k != 0, Op<QB + k * 256, 128, RG, 0, 1>, Op<QB + 3 * RG + k * 256, 128, 2 * RG, 0, 1>>(sc, d0, d0); });
      wg_commit();
      if (P_G1 < 16 && more) nbar_arrive<NB_G1, 384>();
      wg_wait<0>();
      pin<20>(sc);
      if (w == 3 && more) nbar_arrive<NB_S, 64>();
      PROFW(1, 2);
      if (w == 0) {
        uint32_t p[5];
        float v[10];
#pragma unroll
        for (int i = 0; i < 10; i++) v[i] = sc[4 * (i >> 1) + (i & 1)];
        softmax_row(v, p);
        const uint32_t a = sb + lane * 4;
        sts32v(a + PM0, p[0]); sts32v(a + PM0 + 128, p[1]); sts32v(a + PM1, p[2]); sts32v(a + PM1 + 128, p[3]); sts32v(a + PM2, p[4]);
      }
      if (w || !more) mbar_wait(sb + B_V, sp, budget);
      if (w == 1 && more) e_expect_tx(sb + B_V, 10240);
      if (more) {
        float rs[4], ot[2][4];
        uint32_t one[4];
#pragma unroll
        for (int i = 0; i < 4; i++) one[i] = 0x3F803F80u + ((uint32_t)budget >> (31 - i));
        typedef Op<PM0, 128, 128, 0, 0> P0; typedef Op<PM1, 128, 128, 0, 0> P1; typedef Op<PM2, 0, 128, 0, 0> P2;
        fence_proxy_async();
        nbar_sync<NB_P, 128>();
        PROFW(0, 3);
        wg_fence();
        wg_rs8<0, P0>(rs, one, d0); wg_rs8<1, P1>(rs, one, d0); wg_rs8<1, P2>(rs, one, d0);
        wg_commit();
        sfor<0, 2>([&](auto T) {
          constexpr int t = T;
          wg_ss8<0, Op<QB + 8 * RG + t * 1024, 2 * RG, 128, 0, 0>, P0>(ot[t], d0, d0);
          wg_ss8<1, Op<QB + 12 * RG + t * 1024, RG, 128, 0, 0>, P1>(ot[t], d0, d0);
          wg_ss8<1, Op<QB + 14 * RG + t * 1024, 0, 128, 0, 0>, P2>(ot[t], d0, d0);
        });
        wg_commit();
        if (P_G2 < 16 && !P_G2L) nbar_arrive<NB_G2, 384>();
        const uint32_t oa = w * 256 + lane * 4, r1 = mapr(h, sb, rank ^ 1), r2 = mapr(h, sb, 2);
        mbar_wait(sb + B_SDONE, sp, budget);
        wg_wait<1>();
        pin<4>(rs);
        float i0, i1;
        asm volatile("rcp.approx.ftz.f32 %0, %1;" : "=f"(i0) : "f"(rs[0]));
        asm volatile("rcp.approx.ftz.f32 %0, %1;" : "=f"(i1) : "f"(rs[1]));
        wg_wait<0>();
        pin<4>(ot[0]); pin<4>(ot[1]);
        uint32_t x[4];
#pragma unroll
        for (int j = 0; j < 4; j++) {
          x[j] = pack_bf16(ot[j >> 1][2 * (j & 1)] * i0, ot[j >> 1][2 * (j & 1) + 1] * i1);
          sts32v(sb + OM + rank * OMS + oa + (j >> 1) * 1024 + (j & 1) * 128, x[j]);
        }
        fence_proxy_async();
#pragma unroll
        for (int j = 0; j < 8; j++) {
          const int i = P_OS ? j >> 1 : j & 3;
          if (P_OS ? j & 1 : j >> 2) st_async32(r1 + OM + rank * OMS + oa + (i >> 1) * 1024 + (i & 1) * 128, x[i], r1 + B_OM);
          else st_async32(r2 + OM2 + rank * OM2S + oa + (i >> 1) * 1024 + (i & 1) * 128, x[i], r2 + B_OM);
        }
        e_arrive(sb + B_OM);
        if (P_G2 < 16 && P_G2L) nbar_arrive<NB_G2, 384>();
        PROFW(0, 4);
      }
#pragma unroll
      for (int i = 0; i < 10; i++) hold[i] = w ? sc[4 * (i >> 1) + (i & 1)] : sc[4 * (i >> 1) + 2 + (i & 1)];
    }
    if (more && s >= 0) {
      LANE_NOW;
      char* const pw = (char*)g_part + (uint32_t)((t0 * 16 + w * 4 + (lane >> 3)) * 4096 + h * 128 + ((lane ^ h) & 7) * 16);
      mbar_wait(sb + B_OM, sp, budget);
      if (w == 0) nbar_arrive<NB_G, 128>();
      PROFW(1, 5);
      if (!ATT) fence_proxy_async();
      float acc[3][8];
      auto store = [&](auto J) {
        constexpr int j = J;
        float* d = acc[j % 3];
        pin<8>(d);
        uint32_t x[4];
#pragma unroll
        for (int i = 0; i < 4; i++) { const uint32_t m = (h >> 3) == i; x[i] = (pack_bf16(d[2*i], d[2*i+1]) & ~m) | (m & ~sp); }
        stg_rlx128(pw + j * (48 * 4096), x[0], x[1], x[2], x[3]);
        if constexpr (ATT && j == JA) nbar_arrive<NB_TR, 160>();
        if constexpr (j == 2) PROFW(3, 26);
      };
      sfor<0, NT>([&](auto J) {
        constexpr int j = J;
        if constexpr (ATT && j == JA) { mbar_wait(sb + B_WA, sp, budget); PROFW(2, 0); }
        wg_fence();
        sfor<0, 8>([&](auto K) {
          constexpr int k = K;
          typedef Op<(ATT ? OM : OM2) + k * 256, 128, ATT ? OMS : OM2S, 0, 1> OB;
          if constexpr (j == 5 && k < 4) wg_rs16<k ? 1 : 2, OB>(acc[j % 3], wl + 4 * k, d0);
          else wg_ss16<k ? 1 : j < 3 ? 0 : 2, Op<(j == JA ? WA : j < 5 ? WO + (j - (j > JA)) * 16384 : WH - 8192) + k * 2048, 16, 1024, 1, 1>, OB>(acc[j % 3], d0, d0);
        });
        wg_commit();
        if constexpr (j == 0) { if (w == 3) e_expect_tx(sb + B_OM, ATT ? 2048 : 4096); }
        if constexpr (j == NT - 1 && !P_WOL) nbar_arrive<NB_WO, 384>();
        if constexpr (j > 0 && j != P_WB + 1) { wg_wait<1>(); store(IC<j - 1>{}); }
        if constexpr (j == P_WB || j == NT - 1) { wg_wait<0>(); store(IC<j>{}); }
        if constexpr (j == P_WB) {
          const uint32_t t = clock32();
          if (ATT) {
            if (w == 3 && lane < 14) sts128(sb + PM1 + lane * 16, (lane >> 1) == 3 ? 0x3F803F80u : 0);
            if (w == 3 || P_MB) fence_proxy_async();
            nbar_sync<NB_P, 128>();
          } else if (P_MB) fence_proxy_async();
          spin_until(t, TUN(8, 100));
        }
      });
      if (P_WOL) { spin_until(clock32(), TUN(9, 0)); nbar_arrive<NB_WO, 384>(); }
    } else if (more) nbar_arrive<NB_WO, 384>();
    PROFW(0, 6);
    asm volatile("" : "+r"(h), "+r"(rank), "+r"(w));
#pragma unroll 1
    for (int pass = 0; ATT && pass < 2; pass++)
    if (pass != rank) {
      LANE_NOW;
      const int lim = 8 * (g >> 1) + (g & 1) + 2 * w - 8 * c;
      uint32_t p[5];
#pragma unroll
      for (int i = 0; i < 8; i++) hold[2+i] = i <= lim ? hold[2+i] : -INFINITY;
      const float psum = softmax_row(hold, p);
#pragma unroll
      for (int i = 0; i < 5; i++) hold[i] = __uint_as_float(p[i]);
      hold[5] = psum;
    } else if (more) {
      LANE_NOW;
      const int blk = rank * 32 + (h ^ 16);
      char* const mw = (char*)g_mem + (uint32_t)(sp * 32768 + blk * 512 + w * 128 + lane * 4);
      uint32_t v0 = 0;
      if (s == -1 || (s == LAG - 1 && (w & 1))) {
        const unsigned short* q = (const unsigned short*)mem0 + c * 2 * DM + blk * 16 + (w >> 1) * 8 + g;
        v0 = q[0] | (uint32_t)q[DM] << 16;
        if (v0 == 0) v0 = 0x8000u;
      }
      keep(mw);
      if (s >= 0) {
        const uint32_t ca = sb + WA + lane * 128 + (((2 * w) ^ lane) & 7) * 16 + (lane >> 3) * 4;
        const uint32_t sa = sb + OM + (((g >> 1) & 1) * 2 + (g >> 2)) * 128 + (2 * c + (w >> 1)) * 16 + (w & 1) * 8 + (g & 1) * 2;
        const bool g4l = P_G4L == 1 || (P_G4L == 2 && single(s));
        for (bool first = true; ; first = false) {
          float r[4];
          mbar_wait(sb + B_PART, pph, budget);
          PROFW(0, 11);
          pph ^= 1;
          wg_fence();
          sfor<0, 8>([&](auto K) { constexpr int k = K; wg_ss8<k != 0, Op<WA + k * 2048, 16, 1024, 1, 1>, Op<PM1 + (6 - (k & 6)) * 16, 0, 128, 0, 0>>(r, d0, d0); });
          wg_commit();
          if (!g4l && first) nbar_arrive<NB_G4, 384>();
          const uint32_t x0 = lds32v(ca), x1 = lds32v(ca + 4096), x2 = lds32v(ca + 8192), x3 = lds32v(ca + 12288);
          bool bad = __any_sync(0xffffffffu, (sp ? x0 | x1 | x2 | x3 : ~(x0 & x1 & x2 & x3)) & 1) && budget > 0;
          wg_wait<0>();
          pin<4>(r);
          uint32_t y = pack_bf16(r[0], r[2]);
          y |= (y & 0xffffu) ? 0 : 0x8000u;
          y |= (y >> 16) ? 0 : 0x80000000u;
          if (bad) y = 0;
          sts16(sa, y); sts16(sa + 4, y >> 16);
          nbar_sync<NB_P, 128>();
          y = lds32v(sb + OM + w * 128 + lane * 4);
          const bool ok = !__any_sync(0xffffffffu, y == 0);
          if (ok) stg_rlx32(mw, v0 ? v0 : y);
          if (g4l && first) nbar_arrive<NB_G4, 384>();
          if (ok) break;
          nbar_sync<NB_P, 128>();
          budget--;
          if (w == 0) { e_expect_tx(sb + B_PART, 16384); e_bulk_g2s(sb + WA, (const char*)g_part + blk * 16384, 16384, sb + B_PART); }
          __syncwarp();
        }
        nbar_sync<NB_P, 128>();
        if (w < 2) e_arrive_cl(mapr(h, sb + B_BFREE, w));
      } else stg_rlx32(mw, v0);
      stg_rlx32(mw + (sp ? -32768 : 32768), 0);
      PROFW(1, 8);
    }
    if (ATT && s >= 0) {
      const int seg = s - (rank ? LAG : 0);
      const bool act = (unsigned)seg < NSEG;
      LANE_NOW;
      uint32_t a[12];
#pragma unroll
      for (int i = 0; i < 12; i++) a[i] = __float_as_uint(hold[i < 10 ? i >> 1 : 4]) + ((uint32_t)budget >> (31 - (i & 3)));
      float o[32], inv, psum = hold[5];
      char* const ob = (char*)g_o[rank] + ((size_t)(seg * 32 + 8 * (g >> 1) + (g & 1) + 2 * w) * (NH * DH) + h * DH + c * 8) * 2;
      sfor<0, 2>([&](auto HF) {
        constexpr int hf = HF;
        wg_fence();
        wg_rs64<hf * 2, Op<QB + 8 * RG + hf * 1024, 2 * RG, 128, 0, 0>>(o, a, d0);
        wg_rs64<1, Op<QB + 12 * RG + hf * 1024, RG, 128, 0, 0>>(o, a + 4, d0);
        wg_rs64<1, Op<QB + 14 * RG + hf * 1024, 0, 128, 0, 0>>(o, a + 8, d0);
        wg_commit();
        if constexpr (hf == 0) {
          psum += __shfl_xor_sync(0xffffffffu, psum, 1);
          psum += __shfl_xor_sync(0xffffffffu, psum, 2);
          asm("rcp.approx.ftz.f32 %0, %1;" : "=f"(inv) : "f"(psum));
        }
        wg_wait<0>();
        pin<32>(o);
        if constexpr (hf == 1) { if (w == 2 && more) e_arrive_cl(mapr(h, sb + B_BFREE, 2)); }
        if (act) {
#pragma unroll
          for (int i = 0; i < 2; i++)
            stg128(ob + (hf * 2 + i) * 64, pack_bf16(o[16*i] * inv, o[16*i+1] * inv), pack_bf16(o[16*i+4] * inv, o[16*i+5] * inv),
                   pack_bf16(o[16*i+8] * inv, o[16*i+9] * inv), pack_bf16(o[16*i+12] * inv, o[16*i+13] * inv));
        }
      });
      PROFW(0, 7);
      if (act && (seg & 3) == 3) {
        nbar_sync<NB_P, 128>();
        if (w == 0) e_flag_add(g_fl.dep + grp(0, rank, seg >> 2), 4);
      }
    } else if (!ATT && w == 3) {
      if (s + 4 < NSEG) e_prefetch(g_xn[0] + (size_t)((s + 4) * 32 + h) * DM, 2048);
    }
  }
  cluster_sync();
}

DEVI void rec_load(const uint32_t sb, const int h, const int rank, const int w, const CUtensorMap* mX, const CUtensorMap* mWo) {
  using namespace rec;
  const int lane0 = lane_reg(), mq = (w + 3) & 3;
  int budget = SPIN_BUDGET;
  if (w == 0) flag_wait(g_fl.xn[0][0], 96, budget);
  SPROF(3);
  bool late = false;
  cluster_sync();
  if (w == 0) { if (lane0 < 4) mbar_arrive(sb + B_FULL + 8 * lane0); __syncwarp(); }
  if (w == 3) {
    mbar_wait(sb + B_W2, 0, budget);
    e_expect_tx(sb + B_WO, rank == 2 ? 65536 + 16384 + 8192 : 65536);
    const int t0 = (rank + 1) % 3;
    if (lane0 < 8) tma_load_2d(sb + WO + lane0 * 8192, mWo, (3 * ((lane0 >> 1) + (lane0 >> 1 >= JA)) + t0) * 64, h * DH + (lane0 & 1) * 64, sb + B_WO);
    else if (rank < 2 && lane0 < 10) tma_prefetch_2d(mWo, (3 * JA + t0) * 64, h * DH + (lane0 & 1) * 64);
    else if (rank == 2 && lane0 < 11) tma_load_2d(lane0 < 10 ? sb + WA + (lane0 - 8) * 8192 : sb + WH, mWo, lane0 < 10 ? 3 * JA * 64 : 15 * 64, h * DH + (lane0 > 8) * 64, sb + B_WO);
    __syncwarp();
  }
  uint32_t lph = 0;
#pragma unroll 1
  for (int s = -1; s < NSTEP - 1; s++) {
    if (w == 0) {
      if (late) flag_wait(g_fl.xn[1][(s + 1 - LAG) >> 2], 128, budget);
      if (single(s)) {
#pragma unroll 1
        for (int i = 0; i < 8; i++) {
          const int k = i < 5 ? (0x21430 >> (4 * i)) & 15 : i;
          const int sl = (SLOT1 >> (4 * k)) & 15;
          mbar_wait(sb + B_EMPTY + 8 * sl, (((USE1 >> (4 * k)) ^ (sl >> 1 == 1 ? flip(s) : 0)) & 1) ^ 1, budget);
          e_expect_tx(sb + B_FULL + 8 * sl, 8192);
          e_tma_3d(sb + RING + sl * 8192, mX + 1, 0, (s + 1 + (s < LAG ? 0 : NSTEP)) * 32, k * 2, sb + B_FULL + 8 * sl);
        }
      } else {
        int sl = 4, ph = 1;
#pragma unroll 1
        for (int i = 0; i < 16; i++) {
          mbar_wait(sb + B_EMPTY + 8 * sl, ph ^ (sl >> 1 & LAG & 1), budget);
          e_expect_tx(sb + B_FULL + 8 * sl, 8192);
          e_tma_3d(sb + RING + sl * 8192, mX, i * 64, (s + 1) * 32, 0, sb + B_FULL + 8 * sl);
          if (++sl == 5) { sl = 0; ph ^= 1; }
        }
      }
      nbar_arrive<NB_X, 128>();
      const int sn = s + 2 - LAG;
      late = (sn & 3) == 0 && (unsigned)sn < NSEG && ld_acquire(g_fl.xn[1][sn >> 2]) < 128;
      asm volatile("fence.proxy.async.global;" ::: "memory");
    }
    uint32_t t = gtime();
    if (s >= 0) {
      uint2 a;
      if (w == 2 && rank < 2) {
        nbar_sync<NB_S, 64>();
        e_expect_tx(sb + B_WA, 16384);
        e_tma_2d(sb + WA, mWo, (3 * JA + 1 + rank) * 64, h * DH, sb + B_WA);
        e_tma_2d(sb + WA + 8192, mWo, (3 * JA + 1 + rank) * 64, h * DH + 64, sb + B_WA);
        e_arrive_cl(mapr(h, sb + B_SDONE, rank ^ 1));
        stg_rlx32(&g_ann[s & 1][lane0][h * 2 + rank], (gtime() & ~31u) | ((s + 1) & 31));
        e_expect_tx(sb + B_QK, 10240);
      }
      if (w) nbar_sync<NB_G, 128>();
      do { a = ldg_rlx64(&g_ann[s & 1][h][lane0 * 2]); } while (__any_sync(0xffffffffu, ((a.x ^ (s + 1)) | (a.y ^ (s + 1))) & 31) && --budget > 0);
      t += __reduce_max_sync(0xffffffffu, max((int)(a.x - t), (int)(a.y - t)));
      t &= ~31u;
      PROFW(1, 12);
      if (w == 1 && rank < 2) {
        nbar_sync<NB_TR, 160>();
        e_expect_tx(sb + B_PART, 16384);
        wait_time(t + (single(s) ? (rank ? TUN(11, 1600) : TUN(10, 1200)) : rank ? TUN(1, 1700) : TUN(0, 1300)), budget);
        e_bulk_g2s(sb + WA, (const char*)g_part + (rank * 32 + (h ^ 16)) * 16384, 16384, sb + B_PART);
        PROFW(1, 21);
      }
      t += single(s) ? (mq == 0 ? TUN(12, 2050) : mq == 1 ? TUN(13, 2250) : mq == 2 ? TUN(14, 2500) : TUN(15, 2750))
                     : (mq == 0 ? TUN(2, 2250) : mq == 1 ? TUN(3, 2450) : mq == 2 ? TUN(4, 2700) : TUN(5, 2950));
    }
    if (w) nbar_sync<NB_X, 128>();
    mbar_wait(sb + B_EMPTY + 8 * mq, mq >= 2 ? flip(s + 1) ^ 1 : 1, budget);
    PROFW(1, 9);
    uint32_t bar = sb + (P_SPEC && mq == 0 ? B_ML0 : B_MLAND + 8 * mq), redo = 0;
    e_expect_tx(bar, 8192);
    wait_time(t, budget);
    PROFW(1, 22); PROFW(3, 23);
    while (true) {
      e_bulk_g2s(sb + RING + mq * 8192, (const char*)g_mem + (s & 1) * 32768 + mq * 8192, 8192, bar);
      const uint32_t a = sb + RING + mq * 8192 + lane0 * 32 + (lane0 >> 2) * 4;
      if (bar == sb + B_ML0) mbar_wait(bar, (s + 1) & 1, budget);
      else { mbar_wait(bar, lph, budget); lph ^= 1; }
      PROFW(1, 24);
      uint32_t mn = 0xffffffffu;
#pragma unroll
      for (int i = 0; i < 8; i++) mn = min(mn, lds32v(a + i * 1024));
      if (!__any_sync(0xffffffffu, mn == 0) || --budget <= 0) break;
      bar = sb + B_MLAND + 8 * mq; redo = 1;
      e_expect_tx(bar, 8192);
    }
    if (mq == 0) sts32v(sb + REDO, redo);
    e_arrive(sb + B_FULL + 8 * mq);
    PROFW(1, 10); PROFW(2, 13); PROFW(3, 14); PROFW(0, 15);
  }
}

DEVI void ln_row(const uint4* u, bf16* dst, int lane) {
  const uint32_t* x = (const uint32_t*)u;
  float mean = 0, q = 0;
#pragma unroll
  for (int i = 0; i < 16; i++) mean += bf_lo(x[i]) + bf_hi(x[i]);
  mean *= 1.f / 32;
#pragma unroll
  for (int i = 0; i < 16; i++) { const float a = bf_lo(x[i]) - mean, b = bf_hi(x[i]) - mean; q = fmaf(a, a, fmaf(b, b, q)); }
#pragma unroll
  for (int o = 1; o < 32; o *= 2) {
    const float m2 = __shfl_xor_sync(0xffffffffu, mean, o), q2 = __shfl_xor_sync(0xffffffffu, q, o), dl = m2 - mean;
    q = fmaf(dl * dl, 16.f * o, q + q2);
    mean = 0.5f * (mean + m2);
  }
  const float rs = rsqrtf(q * (1.f / DM) + 1e-5f), mr = -mean * rs;
#pragma unroll
  for (int i = 0; i < 4; i++) {
    uint32_t y[4];
#pragma unroll
    for (int k = 0; k < 4; k++) y[k] = pack_bf16(fmaf(bf_lo(x[4*i+k]), rs, mr), fmaf(bf_hi(x[4*i+k]), rs, mr));
    stg128((uint4*)dst + i * 32 + lane, y[0], y[1], y[2], y[3]);
  }
}

struct RecMaps { CUtensorMap w[3], wo, x[2]; };
__global__ void __cluster_dims__(R_CL, 1, 1) __launch_bounds__(512, 1)
rec_kernel(const __grid_constant__ RecMaps M, const bf16* __restrict__ Wo, const bf16* __restrict__ mem0, const bf16* __restrict__ x, uint32_t zero) {
  using namespace rec;
  extern __shared__ __align__(1024) uint8_t smem[];
  const uint32_t sb = smem_u32(smem);
  const int tid = threadIdx.x, warp = __shfl_sync(0xffffffffu, tid >> 5, 0), wg = warp >> 2, lane = tid & 31;
  const int h = blockIdx.x / 3, rank = blockIdx.x % 3;
  if (warp >= 4) {
    const bool ln = warp >= 5 && blockIdx.x * 11 + warp - 5 < SEQ / 2;
    const size_t lo = (size_t)(blockIdx.x * 11 + warp - 5) * (2 * DM);
    uint4 u[8];
    if (ln) {
#pragma unroll
      for (int i = 0; i < 8; i++) u[i] = ldg_rlx128((const uint4*)(x + lo) + i * 32 + lane);
    }
    const uint4 z = make_uint4(0, 0, 0, 0);
    const int t = blockIdx.x * 384 + tid - 128;
    constexpr int N = (sizeof(Flags) - sizeof(g_fl.xn)) / 16;
    g_part[t] = z;
    if (t < 28672) g_part[96 * 384 + t] = z;
    else if (t < 32768) g_mem[0][t - 28672] = ((uint4*)g_stat[4])[t - 28672] = z;
    else if (t < 33792) ((uint4*)g_ann)[t - 32768] = z;
    else if (t < 33792 + N) ((uint4*)g_fl.dep)[t - 33792] = z;
    __syncwarp();
    if (ln) { ln_row(u, g_xn[0] + lo, lane); ln_row(u + 4, g_xn[0] + lo + DM, lane); }
    nbar_sync<NB_WO, 384>();
    if (warp == 4) {
      e_flag_add(g_fl.xn[0][0]);
      asm volatile("griddepcontrol.launch_dependents;" ::: "memory");
    }
  } else {
    if (warp == 0) {
      if (lane < 20) mbar_init(sb + BARS + 8 * lane, (lane >= 5 && lane < 10) || lane == 19 ? 2 : lane == 14 ? 9 : lane == 16 && rank < 2 ? 5 : 1);
      else if (lane < 23) mbar_init(sb + B_W1 + 8 * (lane - 20), 1);
      else if (lane < 25) mbar_init(sb + B_PART + 8 * (lane - 23), 1);
      fence_mbar_init();
      __syncwarp();
      e_expect_tx(sb + B_W1, NRS * 4096); e_expect_tx(sb + B_W2, NSS * 4096);
      e_expect_tx(sb + B_QK, 10240); e_expect_tx(sb + B_V, 10240); e_expect_tx(sb + B_OM, rank < 2 ? 2048 : 4096);
    }
    nbar_sync<NB_ST, 128>();
    if (!is_ss(tid >> 1)) tma_load_2d(sb + stage_at(tid & 1, reg_idx(tid >> 1)), &M.w[rank], h * DH + (tid & 1) * 64, (tid >> 1) * 16, sb + B_W1);
    __syncwarp();
  }
  __syncthreads();
  if (warp < 4) {
    const int j = tid >> 1, t = tid & 1;
    if (!is_ss(j)) {}
    else if (ss_before(j) < NSS - RB) tma_load_2d(sb + WS + (t * NSS + ss_before(j)) * 2048, &M.w[rank], h * DH + t * 64, j * 16, sb + B_W2);
    else tma_prefetch_2d(&M.w[rank], h * DH + t * 64, j * 16);
    __syncwarp();
  }
  if (wg == 3) {
    reg_dec<24>();
    rec_load(sb, h, rank, warp & 3, M.x, &M.wo);
    cluster_sync();
  } else if (wg == 2) {
    reg_dec<72>();
    if (rank < 2) rec_attn<true>(sb, h, rank, warp & 3, Wo, mem0);
    else rec_attn<false>(sb, h, rank, warp & 3, Wo, mem0);
  } else {
    reg_inc<208>();
    rec_proj(sb, h, rank, warp, &M.w[rank], zero);
    cluster_sync();
  }
}

namespace gm {
constexpr int STAGES = 6, STAGE_BYTES = 32768;
constexpr uint32_t SO = STAGES * STAGE_BYTES, B_FULL = SO + 32768, B_TRIG = B_FULL + 56, B_EMPTY = B_FULL + 64, B_JOB = B_FULL + 128,
                   B_MSG = B_FULL + 144, B_XF = B_FULL + 160, B_SF = B_FULL + 176, JOB = B_FULL + 192, MSG = JOB + 8, SMEM = B_FULL + 256;
constexpr int T_O = 0, T_GU = 1, T_D = 2, T_END = 3;
#define G_LOOK 8
#define G_FILL 7
#define G_SLEEP 100
#define G_SLEEP2 500
#define G_SLEEP3 100
#define G_DF 2
#define G_FL 10
#define G_DE 0
#define G_BOOT 3
#define G_DS 14
DEVI bool is_split(int ty, int l, int cb) { return ty == T_O || (ty == T_D && (!l || cb >= G_DS)); }
#define G_ROLES 16, 17, 8, 9, 10, 0, 1, 2, 3, 4, 5, 6, 7, 11, 12, 13, 14, 15
constexpr uint64_t pack_roles(int i0, int i1) { constexpr int r[18] = {G_ROLES}; uint64_t v = 0; for (int i = i0; i < i1; i++) v |= (uint64_t)r[i] << (5 * (i - i0)); return v; }
constexpr uint64_t ROLE0 = pack_roles(0, 12), ROLE1 = pack_roles(12, 18);
struct Pipe { int s, ph; DEVI void next() { if (++s == STAGES) { s = 0; ph ^= 1; } } };
}
struct GemmMaps { CUtensorMap o, wo, x, x1, x1s, xm, xms, xn, wg, wu, h, hs, wd, x2, out, outs; };

DEVI float geglu(float g, float u) {
  const float z = g * (0.7978845608028654f + 0.035677408136300125f * g * g);
  float t; asm("tanh.approx.f32 %0, %1;" : "=f"(t) : "f"(z));
  const float hg = 0.5f * g;
  return fmaf(hg, t, hg) * u;
}
DEVI int h_ready(int v) { const int t = v ^ 0x10141014; return t & 0xff0000ff ? 0 : t & 0xff00 ? 20 : t ? 36 : 56; }
DEVI int a_ready(int ty, int l, int cb) {
  int v;
  asm volatile("ld.acquire.gpu.global.s32 %0, [%1];" : "=r"(v) : "l"(g_fl.dep + grp(ty, l, cb) + (threadIdx.x & 1)) : "memory");
  v = __shfl_sync(0xffffffffu, v, 0);
  asm volatile("fence.proxy.async.global;" ::: "memory");
  return ty == gm::T_D ? h_ready(v) : v >= (ty == gm::T_O && l ? 256 : 128) ? 64 : 0;
}

__global__ void __cluster_dims__(2, 1, 1) __launch_bounds__(512, 1) gemm_kernel(const __grid_constant__ GemmMaps M) {
  using namespace gm;
  extern __shared__ __align__(1024) uint8_t smem[];
  const uint32_t sb = smem_u32(smem);
  const int tid = threadIdx.x, wid = __shfl_sync(0xffffffffu, tid >> 5, 0), wg = wid >> 2, warp = wid & 3;
  int budget = SPIN_BUDGET;
  const int rank = blockIdx.x & 1;
  const uint32_t peer = mapa(sb, rank ^ 1);
  if (tid < 24) mbar_init(sb + B_FULL + 8 * tid, tid >> 3 == 1 ? 2 : 1);
  fence_mbar_init();
  if (wid == 1 && tid < 32 + sizeof(GemmMaps) / 128) asm volatile("prefetch.tensormap [%0];" :: "l"(&M.o + (tid - 32)) : "memory");
  __syncthreads();
  cluster_sync();
  const int cta = blockIdx.x, lane = lane_reg();
  if (wg >= 2) {
    reg_dec<72>();
    if (wid == 8 || wid == 10) {
      Pipe p; p.s = 0; p.ph = 1;
      for (int n = 0; ; n++) {
        if (wid == 8) e_expect_tx(sb + B_MSG + 8 * (n & 1), 4);
        mbar_wait(sb + B_MSG + 8 * (n & 1), (n >> 1) & 1, budget);
        const int msg = __shfl_sync(0xffffffffu, lds32v(sb + MSG + 4 * (n & 1)), 0);
        const int ty = (msg >> 11) & 3, l = (msg >> 10) & 1;
        const bool shb = ty == T_GU && l, spl = is_split(ty, l, (msg >> 6) & 15);
        const int cb = ((msg >> 6) & 15) + (shb ? rank : 0), j = (msg & 63) + (ty == T_END || shb ? 0 : rank);
        const int ke = ty == T_O ? 64 : ty == T_GU ? 16 : 56, k0 = spl ? rank : 0, dk = spl ? 2 : 1;
        const int c0 = ty == T_GU ? j * 64 : spl ? (j >> 1) * 128 : j * 128, c1 = ty == T_GU ? c0 : c0 + 64;
        mbar_wait(sb + B_EMPTY + 8 * p.s, p.ph, budget);
        trap_if_spent(budget);
        auto stages = [&](auto f) {
#pragma unroll 1
          for (int k = k0; k < ke; k += dk) {
            mbar_wait(sb + B_EMPTY + 8 * p.s, p.ph, budget);
            f(k, sb + p.s * STAGE_BYTES, sb + B_FULL + 8 * p.s);
            p.next();
          }
        };
        if (wid == 8) {
          const int job = ty << 11 | l << 10 | cb << 6 | j;
          sts32v(sb + JOB + 4 * (n & 1), job | p.s << 16 | (p.ph ^ 1) << 20);
          e_arrive(sb + B_JOB + 8 * (n & 1));
          if (ty == T_END) break;
          if (ty != T_GU) { e_expect_tx(sb + B_FULL + 8 * p.s, spl ? 16384 : STAGE_BYTES); p.next(); }
          const CUtensorMap* const m0 = ty == T_D ? &M.wd : shb && rank ? &M.wu : &M.wg, * const m1 = ty == T_D ? &M.wd : &M.wu;
          if (ty == T_O) stages([&](int k, uint32_t a, uint32_t fb) { e_expect_tx(fb, STAGE_BYTES); e_tma_5d(a + 16384, &M.wo, c0, k * 2, fb); e_tma_5d(a + 24576, &M.wo, c1, k * 2, fb); });
          else if (shb) stages([&](int k, uint32_t a, uint32_t fb) { e_expect_tx(fb, STAGE_BYTES); e_tma_2d_mc(a + 16384 + rank * 8192, m0, c0, k * 64, fb); });
          else stages([&](int k, uint32_t a, uint32_t fb) { e_expect_tx(fb, STAGE_BYTES); e_tma_2d(a + 16384, m0, c0, k * 64, fb); e_tma_2d(a + 24576, m1, c1, k * 64, fb); });
        } else {
          if (ty == T_END) break;
          const int row = l * SEQ + cb * 128, kt = ke + k0 - G_LOOK * dk;
          const uint64_t polA = ty != T_GU ? EVICT_FIRST : EVICT_NORMAL;
          int rdy = msg >> 16;
          auto need = [&](int k) {
            if (k == kt) e_arrive(sb + B_TRIG);
            while (k >= rdy && k >= (rdy = a_ready(ty, l, cb))) { __nanosleep(G_SLEEP); trap_if_spent(--budget); }
          };
          if (ty != T_GU) {
            need(0);
            const uint32_t a = sb + p.s * STAGE_BYTES, fb = sb + B_FULL + 8 * p.s;
            const CUtensorMap* const m = ty == T_D ? (spl ? &M.x1 : &M.x1s) : l ? &M.x2 : &M.x;
            const int r = (ty == T_D ? row : cb * 128) + (spl ? rank * 64 : 0);
            e_tma_2d(a, m, c0, r, fb, polA); e_tma_2d(a + 16384, m, c1, r, fb, polA);
            p.next();
          }
          if (shb || spl) {
            const CUtensorMap* const ma = ty == T_O ? &M.o : ty == T_GU ? &M.xms : &M.hs;
            stages([&](int k, uint32_t a, uint32_t fb) { need(k); e_tma_2d(a, ma, k * 64, row, fb, polA); });
          } else {
            const CUtensorMap* const ma = ty == T_GU ? &M.xm : &M.h;
            stages([&](int k, uint32_t a, uint32_t fb) { need(k); e_tma_2d_mc(a + rank * 8192, ma, k * 64, row + rank * 64, fb, polA); });
          }
        }
      }
    } else if (wid == 9 && rank == 0) {
      uint32_t sm; asm volatile("mov.u32 %0, %%smid;" : "=r"(sm));
      const bool crowd = sm >= 124 || sm < 50;
      int d0, d1, t0, t1, pair = e_ticket(g_fl.ticket, crowd ? 1 : 256);
      auto peek = [&]() {
        d0 = ld_relaxed(g_fl.dep + lane); d1 = ld_relaxed(g_fl.dep + 32 + lane);
        t0 = ld_relaxed(g_fl.taken + lane); t1 = ld_relaxed(g_fl.taken + 32 + lane);
      };
      peek();
      {
        const int t = bcast(pair), a = t & 255, b = t >> 8, i = crowd ? a : 17 - b;
        pair = a + b >= 18 ? a + b : (int)((i < 12 ? ROLE0 >> (5 * i) : ROLE1 >> (5 * i - 60)) & 31);
      }
      int k1 = pair < 18 ? 0 : 48, skip = pair - 18;
      bool late = false;
      for (int n = 0, ty = 0; ty != T_END; n++) {
        mbar_wait(sb + B_TRIG, (n & 1) ^ 1, budget);
        int l, cb, j, rdy = 64;
        while (true) {
          const int ph = k1 % 3;
          const bool gap = pair < 8 ? ph == 1 : pair >= 16 && ph == 2;
          if (k1 < 48) {
            cb = k1++ / 3;
            if (gap && (late || !(G_FILL & (pair < 8 ? 1 : 2)))) continue;
            if (!gap) {
              l = 0;
              ty = pair < 8 ? (ph ? T_GU : T_O) : ph == 2 ? T_D : T_GU;
              j = 2 * (pair < 8 ? (ph ? pair + 10 : pair) : ph == 1 ? pair + 10 : pair - 8);
              rdy = a_ready(ty, 0, cb);
              if (ph == 0) late = rdy != 0;
              break;
            }
          }
          if (skip < 0) peek();
          const bool l0 = t0 < (lane < 16 ? 8 : lane & 1 ? 0 : 56), l1 = lane < 16 && t1 < (lane < G_DS ? 4 : 8);
          const uint32_t rd = __ballot_sync(0xffffffffu, d0 >= (lane < 16 ? 256 : 128));
          uint32_t ok0 = __ballot_sync(0xffffffffu, l0) & rd & (rd >> 1 | 0xffff), ok1 = __ballot_sync(0xffffffffu, l1 && h_ready(d1) > 0);
          if (gap) { ok1 = 0; if (pair < 16) ok0 &= 0xffff0000u | G_BOOT; }
          ty = T_END; l = 1; cb = j = 0;
          if (!gap && !__any_sync(0xffffffffu, l0 || l1)) break;
          if (ok1 & ((1u << G_DS) - 1)) ok1 &= (1u << G_DS) - 1;
          const uint32_t dfirst = ok1 & __ballot_sync(0xffffffffu, lane < G_DF && d1 == 0x10141014);
          if (dfirst && !(ok0 & 0xffff)) { ok0 = 0; ok1 = dfirst; }
          else if (__any_sync(0xffffffffu, l0)) ok1 &= (1u << G_DE) - 1;
          else if (!ok1 && !gap) ok1 = __ballot_sync(0xffffffffu, l1);
          uint32_t m = ok0 ? ok0 : ok1;
          if (!m && !gap) __nanosleep(100);
          while (m) {
            const int nth = ok0 ? 0 : pair % __popc(m);
            const int b = __ffs(__ballot_sync(0xffffffffu, __popc(m << (31 - lane)) > nth)) - 1, gn = b + (ok0 ? 0 : 32);
            const int sz = gn < 16 ? 8 : gn < 32 ? 56 : gn < 32 + G_DS ? 4 : 8;
            m &= ~(1u << b);
            if (skip >= 0 && m && (skip -= sz - __shfl_sync(0xffffffffu, ok0 ? t0 : t1, b)) >= 0) continue;
            int t = e_ticket(g_fl.taken + gn);
            rdy = a_ready(gn >> 4, 1, gn & 15);
            t = bcast(t);
            if (t < sz) { ty = gn >> 4; cb = gn & 15; j = sz == 56 ? t : 2 * t; break; }
          }
          skip = -1;
          if (ty != T_END) break;
          trap_if_spent(--budget);
        }
        const int msg = rdy << 16 | ty << 11 | l << 10 | cb << 6 | j;
        e_st_async32(peer + MSG + 4 * (n & 1), msg, peer + B_MSG + 8 * (n & 1));
        e_st_async32(sb + MSG + 4 * (n & 1), msg, sb + B_MSG + 8 * (n & 1));
      }
    } else if (wg == 3) {
      bool open = lane < G_FL && ld_relaxed(g_fl.rows + lane) < 128;
      while (__any_sync(0xffffffffu, open)) {
        int v = 0;
        if (open) asm volatile("ld.acquire.gpu.global.s32 %0, [%1];" : "=r"(v) : "l"(g_fl.part + lane) : "memory");
        const uint32_t ok = __ballot_sync(0xffffffffu, open && v >= 128);
        if (!ok) {
          if (--budget <= 0) break;
          __nanosleep(G_SLEEP2);
          continue;
        }
        const int cb = __ffs(__ballot_sync(0xffffffffu, __popc(ok << (31 - lane)) > (cta >> 5) % __popc(ok))) - 1;
        const int r = bcast(e_ticket(g_fl.rows + cb));
        if (r >= 128) { open = open && lane != cb; continue; }
        uint4 u[4];
#pragma unroll
        for (int i = 0; i < 4; i++) u[i] = ldg_rlx128((const uint4*)(g_x1[1] + (size_t)(cb * 128 + r) * DM) + i * 32 + lane);
        ln_row(u, g_xm[1] + (size_t)(cb * 128 + r) * DM, lane);
        __syncwarp();
        e_flag_add(g_fl.dep + grp(T_GU, 1, cb));
      }
      if (cta == 0 && wid == 12) {
        asm volatile("griddepcontrol.wait;" ::: "memory");
        g_fl.xn[lane >> 4][lane & 15][0] = 0;
      }
    }
    cluster_sync();
  } else {
    reg_inc<184>();
    const bool lead = warp == 0;
    const uint32_t eb = (warp == 1 ? peer : sb) + B_EMPTY;
    const int rl = warp < 2 ? 0 : -1;
    const uint32_t so = sb + SO + wg * 16384;
    const int r0 = warp * 16 + (lane & 7) + ((lane >> 3) & 1) * 8;
    const uint32_t sw = r0 * 128 + (((lane >> 4) ^ (r0 & 7)) << 4);
    int xph = 0;
    for (int n = wg; ; n += 2) {
      float d0[64], d1[64];
      mbar_wait(sb + B_JOB + 8 * wg, (n >> 1) & 1, budget);
      fault_if_spent(budget);
      const int job = __shfl_sync(0xffffffffu, lds32v(sb + JOB + 4 * wg), 0);
      const int ty = (job >> 11) & 3, l = (job >> 10) & 1, cb = (job >> 6) & 15, j = job & 63;
      if (ty == T_END) {
        if (n > 0) nbar_sync_r(1 + wg, 256);
        if (lead && !(job & 1)) { sts32v(sb + JOB + 4 * (wg ^ 1), job | 1); e_arrive(sb + B_JOB + 8 * (wg ^ 1)); }
        if (!(job & 1)) nbar_arrive_r(1 + (wg ^ 1), 256);
        break;
      }
      Pipe q; q.s = (job >> 16) & 15; q.ph = job >> 20;
      const bool spl = is_split(ty, l, cb);
      if (ty != T_GU) mbar_wait(sb + B_FULL + 8 * q.s, q.ph, budget);
#pragma unroll
      for (int m = 0; m < 2; m++) {
        float* d = m ? d1 : d0;
        if (ty != T_GU && !(m && spl)) {
#pragma unroll
          for (int c = 0; c < 8; c++) {
            uint32_t r[4];
            ldsm4(sb + q.s * STAGE_BYTES + (c >> 2) * 16384 + m * 8192 + (sw ^ ((c & 3) << 5)), r[0], r[1], r[2], r[3]);
#pragma unroll
            for (int i = 0; i < 4; i++) { d[8*c+2*i] = bf_lo(r[i]); d[8*c+2*i+1] = bf_hi(r[i]); }
          }
        } else {
#pragma unroll
          for (int i = 0; i < 64; i++) d[i] = 0.f;
        }
      }
      if (ty != T_GU) {
        fence_proxy_async();
        nbar_sync_r(3 + wg, 128);
        arrive_cl_if_eq(eb + 8 * q.s, lane, rl);
        q.next();
      }
      pin<64>(d0); pin<64>(d1);
      if (n > 0) nbar_sync_r(1 + wg, 256);
      const int nk = ty == T_O ? 32 : ty == T_GU ? 16 : spl ? 28 : 56;
      const uint32_t ro = spl ? rank * 512 : 0;
      int prev = 0;
      for (int i = 0; i < nk; i++) {
        mbar_wait(sb + B_FULL + 8 * q.s, q.ph, budget);
        const uint32_t da = desc_base(sb) + q.s * (STAGE_BYTES / 16);
        wg_fence();
        sfor<0, 4>([&](auto K) {
          constexpr int k = K;
          typedef Op<16384 + k * 2048, 8192, 1024, 1, 1> OB;
          wg_ss128<1, Op<k * 32, 16, 1024, 1, 0>, OB>(d0, da + ro, da);
          wg_ss128<1, Op<8192 + k * 32, 16, 1024, 1, 0>, OB>(d1, da - ro, da);
        });
        wg_commit();
        wg_wait<1>();
        arrive_cl_if_eq(eb + 8 * prev, lane, i ? rl : -1);
        prev = q.s;
        q.next();
      }
      nbar_arrive_r(1 + (wg ^ 1), 256);
      wg_wait<0>();
      pin<64>(d0); pin<64>(d1);
      arrive_cl_if_eq(eb + 8 * prev, lane, rl);
      if (spl) {
        const uint32_t xa = SO + wg * 16384 + warp * 512 + lane * 16;
        if (lead) e_expect_tx(sb + B_XF + 8 * wg, 16384);
        mbar_wait(sb + B_SF + 8 * wg, ((n >> 1) & 1) ^ 1, budget);
#pragma unroll
        for (int i = 0; i < 8; i++) {
          const float* d = d1 + 8 * i;
          st_async128(peer + xa + i * 2048, pack_bf16(d[0], d[1]), pack_bf16(d[2], d[3]), pack_bf16(d[4], d[5]), pack_bf16(d[6], d[7]), peer + B_XF + 8 * wg);
        }
        mbar_wait(sb + B_XF + 8 * wg, xph, budget);
        xph ^= 1;
        uint32_t y[32];
#pragma unroll
        for (int i = 0; i < 8; i++) {
          const float* d = d0 + 8 * i;
          const uint4 v = lds128(sb + xa + i * 2048);
          y[4*i] = pack_bf16(d[0] + bf_lo(v.x), d[1] + bf_hi(v.x)); y[4*i+1] = pack_bf16(d[2] + bf_lo(v.y), d[3] + bf_hi(v.y));
          y[4*i+2] = pack_bf16(d[4] + bf_lo(v.z), d[5] + bf_hi(v.z)); y[4*i+3] = pack_bf16(d[6] + bf_lo(v.w), d[7] + bf_hi(v.w));
        }
        const bool fuse = !l || (ty == T_O && cb >= G_FL);
        float2* const st = &g_stat[l ? 4 + (cb & 7) : ty + (cb & 1)][0][rank * 64 + warp * 16 + (lane >> 2) * 2];
        if (fuse) {
          float mn[2], sq[2];
#pragma unroll
          for (int z = 0; z < 2; z++) {
            float m = 0, s2 = 0;
#pragma unroll
            for (int i = 0; i < 16; i++) m += bf_lo(y[2*i+z]) + bf_hi(y[2*i+z]);
            m += __shfl_xor_sync(0xffffffffu, m, 1); m += __shfl_xor_sync(0xffffffffu, m, 2);
            m *= 1.f / 128;
#pragma unroll
            for (int i = 0; i < 16; i++) { const float a = bf_lo(y[2*i+z]) - m, b = bf_hi(y[2*i+z]) - m; s2 = fmaf(a, a, fmaf(b, b, s2)); }
            s2 += __shfl_xor_sync(0xffffffffu, s2, 1); s2 += __shfl_xor_sync(0xffffffffu, s2, 2);
            mn[z] = m; sq[z] = s2;
          }
          if ((lane & 3) == 0) stg_rlx128(st + (j >> 1) * 128, __float_as_uint(mn[0]), (__float_as_uint(sq[0]) & ~31u) | (cb + 1), __float_as_uint(mn[1]), __float_as_uint(sq[1]));
          __syncwarp();
        }
        const int row = (ty == T_O ? l * SEQ : 0) + cb * 128 + rank * 64;
        auto put = [&](const CUtensorMap* mo, auto f) {
          nbar_sync_r(3 + wg, 128);
#pragma unroll
          for (int c = 0; c < 8; c++) stsm4(so + (c >> 2) * 8192 + (sw ^ ((c & 3) << 5)), f(4*c), f(4*c+1), f(4*c+2), f(4*c+3));
          fence_proxy_async();
          nbar_sync_r(3 + wg, 128);
          if (lead) { e_tma_store_2d(mo, so, (j >> 1) * 128, row); e_tma_store_2d(mo, so + 8192, (j >> 1) * 128 + 64, row); bulk_commit(); }
        };
        if (fuse) {
          uint4 u[2];
          while (true) {
            __nanosleep(G_SLEEP3);
            u[0] = ldg_rlx128(st + (lane & 3) * 256); u[1] = ldg_rlx128(st + (lane & 3) * 256 + 128);
            if (!__any_sync(0xffffffffu, ((u[0].y ^ (cb + 1)) | (u[1].y ^ (cb + 1))) & 31) || --budget <= 0) break;
          }
          float rs[2], mr[2];
#pragma unroll
          for (int z = 0; z < 2; z++) {
            const float ma = __uint_as_float(z ? u[0].z : u[0].x), mb = __uint_as_float(z ? u[1].z : u[1].x);
            float m = ma + mb;
            m += __shfl_xor_sync(0xffffffffu, m, 1); m += __shfl_xor_sync(0xffffffffu, m, 2);
            m *= 0.125f;
            float s2 = __uint_as_float(z ? u[0].w : u[0].y & ~31u) + __uint_as_float(z ? u[1].w : u[1].y & ~31u) + 128.f * ((ma - m) * (ma - m) + (mb - m) * (mb - m));
            s2 += __shfl_xor_sync(0xffffffffu, s2, 1); s2 += __shfl_xor_sync(0xffffffffu, s2, 2);
            rs[z] = rsqrtf(s2 * (1.f / DM) + 1e-5f); mr[z] = -m * rs[z];
          }
          put(ty == T_O ? &M.xm : &M.xn, [&](int i) { return pack_bf16(fmaf(bf_lo(y[i]), rs[i & 1], mr[i & 1]), fmaf(bf_hi(y[i]), rs[i & 1], mr[i & 1])); });
          if (lead) {
            bulk_wait<0>();
            e_flag_add_bulk(ty == T_D ? g_fl.xn[1][cb] : g_fl.dep + grp(T_GU, l, cb), 8);
          }
        }
        put(ty == T_O ? &M.x1 : l ? &M.out : &M.x2, [&](int i) { return y[i]; });
      } else {
        if (ty == T_GU) {
#pragma unroll
          for (int i = 0; i < 32; i++) { d0[i] = geglu(d0[i], d0[32 + i]); d1[i] = geglu(d1[i], d1[32 + i]); }
        }
#pragma unroll
        for (int hf = 0; hf < 2; hf++) {
          if (hf) {
            if (ty == T_GU) break;
            if (lead) bulk_wait_read<0>();
            nbar_sync_r(3 + wg, 128);
          }
#pragma unroll
          for (int m = 0; m < 2; m++)
#pragma unroll
            for (int c = 0; c < 4; c++) {
              const float* d = (m ? d1 : d0) + 32 * hf + 8 * c;
              stsm4(so + m * 8192 + (sw ^ (c << 5)), pack_bf16(d[0], d[1]), pack_bf16(d[2], d[3]), pack_bf16(d[4], d[5]), pack_bf16(d[6], d[7]));
            }
          fence_proxy_async();
          nbar_sync_r(3 + wg, 128);
          if (lead) {
            if (ty == T_GU) e_tma_store_2d(&M.hs, so, j * 64, l * SEQ + cb * 128); else e_tma_store_2d(&M.outs, so, j * 128 + hf * 64, cb * 128);
            bulk_commit();
          }
        }
      }
      if (lead) {
        bulk_wait<0>();
        e_arrive_cl(peer + B_SF + 8 * wg);
        if (ty == T_GU) e_flag_add_bulk(g_fl.dep + grp(T_D, l, cb), j < 20 ? 1 : j < 36 ? 1 << 8 : 1 << 16);
        else if (ty == T_O) { e_flag_add_bulk(g_fl.dep + grp(T_D, l, cb), 1 << 24); if (l && cb < G_FL) e_flag_add_bulk(g_fl.part + cb, 8); }
        else if (!l) e_flag_add_bulk(g_fl.dep + grp(T_O, 1, cb), 8);
      }
    }
    cluster_sync();
  }
}

typedef CUresult (*PFN_encodeTiled)(CUtensorMap*, CUtensorMapDataType, cuuint32_t, void*, const cuuint64_t*, const cuuint64_t*,
                                    const cuuint32_t*, const cuuint32_t*, CUtensorMapInterleave, CUtensorMapSwizzle,
                                    CUtensorMapL2promotion, CUtensorMapFloatOOBfill);
static PFN_encodeTiled g_encode = nullptr;
static int g_sms = 0;
static CUtensorMap encode(const void* ptr, int rank, const cuuint64_t* dims, const cuuint64_t* strides, const cuuint32_t* box) {
  CUtensorMap m;
  const cuuint32_t es[5] = {1, 1, 1, 1, 1};
  g_encode(&m, CU_TENSOR_MAP_DATA_TYPE_BFLOAT16, rank, (void*)ptr, dims, strides, box, es, CU_TENSOR_MAP_INTERLEAVE_NONE,
           CU_TENSOR_MAP_SWIZZLE_128B, CU_TENSOR_MAP_L2_PROMOTION_L2_256B, CU_TENSOR_MAP_FLOAT_OOB_FILL_NONE);
  return m;
}
static CUtensorMap make_map(const void* ptr, uint64_t rows, uint64_t cols, uint32_t box_rows) {
  const cuuint64_t dims[2] = {cols, rows}, strides[1] = {cols * 2};
  const cuuint32_t box[2] = {64, box_rows};
  return encode(ptr, 2, dims, strides, box);
}
static CUtensorMap make_map_x(const void* ptr) {
  const cuuint64_t dims[3] = {DM, NSTEP * 32, 2}, strides[2] = {DM * 2, (cuuint64_t)NSTEP * 32 * DM * 2};
  const cuuint32_t box[3] = {64, 32, 2};
  return encode(ptr, 3, dims, strides, box);
}
static CUtensorMap make_map_x1(const void* ptr) {
  const cuuint64_t dims[3] = {64, 2 * NSTEP * 32, DM / 64}, strides[2] = {DM * 2, 128};
  const cuuint32_t box[3] = {64, 32, 2};
  return encode(ptr, 3, dims, strides, box);
}
static CUtensorMap make_map_wo(const void* ptr) {
  const cuuint64_t dims[5] = {DM, 2, 4, 4, NH * DH / 32}, strides[4] = {DM * 2, 8 * DM * 2, 2 * DM * 2, 32 * DM * 2};
  const cuuint32_t box[5] = {64, 2, 4, 4, 2};
  return encode(ptr, 5, dims, strides, box);
}

extern "C" void kernel_launch(void* const* d_in, const int* in_sizes, int n_in, void* d_out, int out_size) {
  const bf16 *x = (const bf16*)d_in[0], *mem0 = (const bf16*)d_in[1], *Wo = (const bf16*)d_in[5];
  if (!g_encode) {
    void* p = nullptr; cudaDriverEntryPointQueryResult q;
    cudaGetDriverEntryPoint("cuTensorMapEncodeTiled", &p, cudaEnableDefault, &q);
    g_encode = (PFN_encodeTiled)p;
    int dev = 0;
    cudaGetDevice(&dev);
    cudaDeviceGetAttribute(&g_sms, cudaDevAttrMultiProcessorCount, dev);
    cudaFuncSetAttribute(rec_kernel, cudaFuncAttributeMaxDynamicSharedMemorySize, rec::SMEM);
    cudaFuncSetAttribute(gemm_kernel, cudaFuncAttributeMaxDynamicSharedMemorySize, gm::SMEM);
  }
  void *xn, *o, *x1, *xm, *x2, *hh;
  cudaGetSymbolAddress(&xn, g_xn); cudaGetSymbolAddress(&o, g_o); cudaGetSymbolAddress(&x1, g_x1);
  cudaGetSymbolAddress(&xm, g_xm); cudaGetSymbolAddress(&x2, g_x2); cudaGetSymbolAddress(&hh, g_h);
  RecMaps R;
  for (int i = 0; i < 3; i++) R.w[i] = make_map(d_in[2 + i], DM, NH * DH, 16);
  R.wo = make_map(Wo, NH * DH, DM, 64); R.x[0] = make_map_x(xn); R.x[1] = make_map_x1(xn);
  rec_kernel<<<96, 512, rec::SMEM>>>(R, Wo, mem0, x, 0);
  GemmMaps G;
  G.o = make_map(o, 2 * SEQ, NH * DH, 128); G.wo = make_map_wo(Wo);
  G.x1 = make_map(x1, 2 * SEQ, DM, 64); G.x1s = make_map(x1, 2 * SEQ, DM, 128);
  G.xn = make_map((bf16*)xn + (NSTEP + LAG) * 32 * DM, SEQ, DM, 64);
  G.xm = make_map(xm, 2 * SEQ, DM, 64); G.xms = make_map(xm, 2 * SEQ, DM, 128);
  G.wg = make_map(d_in[8], DM, DF, 64); G.wu = make_map(d_in[9], DM, DF, 64); G.wd = make_map(d_in[10], DF, DM, 64);
  G.h = make_map(hh, 2 * SEQ, DF, 64); G.hs = make_map(hh, 2 * SEQ, DF, 128);
  G.x = make_map(x, SEQ, DM, 64); G.x2 = make_map(x2, SEQ, DM, 64); G.out = make_map(d_out, SEQ, DM, 64); G.outs = make_map(d_out, SEQ, DM, 128);
  cudaLaunchConfig_t cfg = {};
  cfg.gridDim = dim3(g_sms & ~1); cfg.blockDim = dim3(512); cfg.dynamicSmemBytes = gm::SMEM; cfg.stream = cudaStreamPerThread;
  cudaLaunchAttribute at;
  at.id = cudaLaunchAttributeProgrammaticStreamSerialization; at.val.programmaticStreamSerializationAllowed = 1;
  cfg.attrs = &at; cfg.numAttrs = 1;
  cudaLaunchKernelEx(&cfg, gemm_kernel, G);
}
```

```cpp
#include <cuda_runtime.h>
#include <cuda_bf16.h>
#include <cuda.h>
#include <stdint.h>

#define DEVI __device__ __forceinline__
typedef __nv_bfloat16 bf16;

#define LAG 14
constexpr int SEQ = 2048, DM = 1024, NH = 32, DH = 128, DF = 3584, NSEG = 64, NSTEP = NSEG + LAG;

__device__ __align__(1024) bf16 g_xn[2][NSTEP * 32 * DM];
__device__ __align__(1024) bf16 g_o[2][SEQ * NH * DH];
__device__ __align__(1024) bf16 g_x1[2][SEQ * DM];
__device__ __align__(1024) bf16 g_xm[2][SEQ * DM];
__device__ __align__(1024) bf16 g_x2[SEQ * DM];
__device__ __align__(1024) bf16 g_h[2][SEQ * DF];
__device__ __align__(1024) uint4 g_part[256 * 32 * 8];
__device__ __align__(1024) uint32_t g_ann[2][32][64];
__device__ __align__(1024) uint4 g_mem[2][2048];
__device__ __align__(128) float2 g_stat[12][8][128];
__host__ __device__ constexpr int grp(int type, int layer, int blk) { return layer ? 16 * type + blk : 64 + (16 * type + blk) * 32; }
struct Flags {
  int xn[2][16][32];
  int dep[64 + 48 * 32];
  int taken[64];
  int rows[32];
  int part[32];
  int ticket[32];
};
__device__ __align__(128) Flags g_fl;

DEVI uint32_t smem_u32(const void* p) { return (uint32_t)__cvta_generic_to_shared(p); }
DEVI void mbar_init(uint32_t bar, uint32_t cnt) { asm volatile("mbarrier.init.shared::cta.b64 [%0], %1;" :: "r"(bar), "r"(cnt) : "memory"); }
DEVI void mbar_expect_tx(uint32_t bar, uint32_t bytes) { asm volatile("mbarrier.arrive.expect_tx.shared::cta.b64 _, [%0], %1;" :: "r"(bar), "r"(bytes) : "memory"); }
DEVI void mbar_arrive(uint32_t bar) { asm volatile("mbarrier.arrive.shared::cta.b64 _, [%0];" :: "r"(bar) : "memory"); }
DEVI bool mbar_try(uint32_t bar, uint32_t parity) {
  uint32_t p;
  asm volatile("{.reg .pred p; mbarrier.try_wait.parity.shared::cta.b64 p, [%1], %2; selp.u32 %0, 1, 0, p;}" : "=r"(p) : "r"(bar), "r"(parity) : "memory");
  return p;
}
DEVI bool mbar_test(uint32_t bar, uint32_t parity) {
  uint32_t p;
  asm volatile("{.reg .pred p; mbarrier.test_wait.parity.shared::cta.b64 p, [%1], %2; selp.u32 %0, 1, 0, p;}" : "=r"(p) : "r"(bar), "r"(parity) : "memory");
  return p;
}
constexpr int SPIN_BUDGET = 1 << 20;
DEVI void mbar_wait(uint32_t bar, uint32_t parity, int& budget) {
  while (!mbar_try(bar, parity)) { if (--budget < 0) break; }
}
DEVI void trap_if_spent(int budget) { asm volatile("{.reg .pred p; setp.le.s32 p, %0, 0; @p trap;}" :: "r"(budget) : "memory"); }
DEVI void fault_if_spent(int budget) { asm volatile("{.reg .pred p; setp.le.s32 p, %0, 0; @p st.global.u32 [%1], 0;}" :: "r"(budget), "l"(0ull) : "memory"); }
DEVI uint32_t mapa(uint32_t addr, uint32_t rank) { uint32_t r; asm("mapa.shared::cluster.u32 %0, %1, %2;" : "=r"(r) : "r"(addr), "r"(rank)); return r; }
DEVI void cluster_sync() { asm volatile("barrier.cluster.arrive.relaxed.aligned; barrier.cluster.wait.aligned;" ::: "memory"); }
DEVI void fence_mbar_init() { asm volatile("fence.mbarrier_init.release.cluster;" ::: "memory"); }
DEVI void fence_proxy_async() { asm volatile("fence.proxy.async.shared::cta;" ::: "memory"); }
DEVI void tma_load_2d(uint32_t dst, const CUtensorMap* m, int c0, int c1, uint32_t bar) {
  asm volatile("cp.async.bulk.tensor.2d.shared::cluster.global.mbarrier::complete_tx::bytes [%0], [%1, {%3, %4}], [%2];"
    :: "r"(dst), "l"(m), "r"(bar), "r"(c0), "r"(c1) : "memory");
}
DEVI void tma_load_5d(uint32_t dst, const CUtensorMap* m, int c0, int c4, uint32_t bar) {
  asm volatile("cp.async.bulk.tensor.5d.shared::cluster.global.mbarrier::complete_tx::bytes [%0], [%1, {%3, %5, %5, %5, %4}], [%2];"
    :: "r"(dst), "l"(m), "r"(bar), "r"(c0), "r"(c4), "r"(0) : "memory");
}
DEVI void tma_prefetch_2d(const CUtensorMap* m, int c0, int c1) {
  asm volatile("cp.async.bulk.prefetch.tensor.2d.L2.global [%0, {%1, %2}];" :: "l"(m), "r"(c0), "r"(c1) : "memory");
}
DEVI void tma_prefetch_5d(const CUtensorMap* m, int c0, int c4) {
  asm volatile("cp.async.bulk.prefetch.tensor.5d.L2.global [%0, {%1, %3, %3, %3, %2}];" :: "l"(m), "r"(c0), "r"(c4), "r"(0) : "memory");
}
#define ELECT "{.reg .pred p; elect.sync _|p, 0xffffffff;\n @p "
DEVI void e_expect_tx(uint32_t bar, uint32_t bytes) { asm volatile(ELECT "mbarrier.arrive.expect_tx.shared::cta.b64 _, [%0], %1;}" :: "r"(bar), "r"(bytes) : "memory"); }
DEVI void e_arrive(uint32_t bar) { asm volatile(ELECT "mbarrier.arrive.shared::cta.b64 _, [%0];}" :: "r"(bar) : "memory"); }
DEVI void e_arrive_cl(uint32_t bar) { asm volatile(ELECT "mbarrier.arrive.shared::cluster.b64 _, [%0];}" :: "r"(bar) : "memory"); }
constexpr uint64_t EVICT_NORMAL = 0x1000000000000000ull, EVICT_FIRST = 0x12F0000000000000ull;
DEVI void e_tma_2d(uint32_t dst, const CUtensorMap* m, int c0, int c1, uint32_t bar, uint64_t pol = EVICT_NORMAL) {
  asm volatile(ELECT "cp.async.bulk.tensor.2d.shared::cluster.global.mbarrier::complete_tx::bytes.L2::cache_hint [%0], [%1, {%3, %4}], [%2], %5;}"
    :: "r"(dst), "l"(m), "r"(bar), "r"(c0), "r"(c1), "l"(pol) : "memory");
}
DEVI void e_tma_2d_mc(uint32_t dst, const CUtensorMap* m, int c0, int c1, uint32_t bar, uint64_t pol = EVICT_NORMAL) {
  asm volatile(ELECT "cp.async.bulk.tensor.2d.shared::cluster.global.mbarrier::complete_tx::bytes.multicast::cluster.L2::cache_hint [%0], [%1, {%3, %4}], [%2], %5, %6;}"
    :: "r"(dst), "l"(m), "r"(bar), "r"(c0), "r"(c1), "h"((unsigned short)3), "l"(pol) : "memory");
}
DEVI void e_st_async32(uint32_t a, uint32_t x, uint32_t bar) {
  asm volatile(ELECT "st.async.weak.shared::cluster.mbarrier::complete_tx::bytes.b32 [%0], %1, [%2];}" :: "r"(a), "r"(x), "r"(bar) : "memory");
}
DEVI void e_tma_store_2d(const CUtensorMap* m, uint32_t src, int c0, int c1) {
  asm volatile(ELECT "cp.async.bulk.tensor.2d.global.shared::cta.bulk_group [%0, {%2, %3}], [%1];}" :: "l"(m), "r"(src), "r"(c0), "r"(c1) : "memory");
}
DEVI void e_flag_add(int* p, int v = 1) {
  asm volatile("{.reg .pred p; elect.sync _|p, 0xffffffff;\n fence.proxy.async.global; @p red.release.gpu.global.add.s32 [%0], %1;}" :: "l"(p), "r"(v) : "memory");
}
DEVI void e_flag_add_bulk(int* p, int v) {
  asm volatile(ELECT "red.relaxed.gpu.global.add.s32 [%0], %1;}" :: "l"(p), "r"(v) : "memory");
}
DEVI int e_ticket(int* p, int n = 1) { int v = 0; asm volatile(ELECT "atom.relaxed.gpu.global.add.s32 %0, [%1], %2;}" : "+r"(v) : "l"(p), "r"(n) : "memory"); __syncwarp(); return v; }
DEVI int bcast(int v) { return __reduce_max_sync(0xffffffffu, v); }
DEVI int ld_relaxed(const int* p) { int v; asm volatile("ld.relaxed.gpu.global.s32 %0, [%1];" : "=r"(v) : "l"(p) : "memory"); return v; }
DEVI int ld_acquire(const int* p) { int v; asm volatile("ld.acquire.gpu.global.s32 %0, [%1];" : "=r"(v) : "l"(p) : "memory"); return __shfl_sync(0xffffffffu, v, 0); }
DEVI void e_tma_3d(uint32_t dst, const CUtensorMap* m, int c0, int c1, int c2, uint32_t bar) {
  asm volatile(ELECT "cp.async.bulk.tensor.3d.shared::cluster.global.mbarrier::complete_tx::bytes [%0], [%1, {%3, %4, %5}], [%2];}"
    :: "r"(dst), "l"(m), "r"(bar), "r"(c0), "r"(c1), "r"(c2) : "memory");
}
DEVI void e_tma_5d(uint32_t dst, const CUtensorMap* m, int c0, int c4, uint32_t bar) {
  asm volatile(ELECT "cp.async.bulk.tensor.5d.shared::cluster.global.mbarrier::complete_tx::bytes [%0], [%1, {%3, %5, %5, %5, %4}], [%2];}"
    :: "r"(dst), "l"(m), "r"(bar), "r"(c0), "r"(c4), "r"(0) : "memory");
}
DEVI void e_bulk_g2s(uint32_t dst, const void* src, uint32_t bytes, uint32_t bar) {
  asm volatile(ELECT "cp.async.bulk.shared::cluster.global.mbarrier::complete_tx::bytes [%0], [%1], %2, [%3];}" :: "r"(dst), "l"(src), "r"(bytes), "r"(bar) : "memory");
}
DEVI void e_prefetch(const void* src, uint32_t bytes) {
  asm volatile(ELECT "cp.async.bulk.prefetch.L2.global [%0], %1;}" :: "l"(src), "r"(bytes) : "memory");
}
DEVI void bulk_commit() { asm volatile("cp.async.bulk.commit_group;" ::: "memory"); }
template<int N> DEVI void bulk_wait_read() { asm volatile("cp.async.bulk.wait_group.read %0;" :: "n"(N) : "memory"); }
template<int N> DEVI void bulk_wait() { asm volatile("cp.async.bulk.wait_group %0;" :: "n"(N) : "memory"); }
template<int ID, int N> DEVI void nbar_sync() { asm volatile("bar.sync %0, %1;" :: "n"(ID), "n"(N) : "memory"); }
template<int ID, int N> DEVI void nbar_arrive() { asm volatile("bar.arrive %0, %1;" :: "n"(ID), "n"(N) : "memory"); }
DEVI void nbar_sync_r(int id, int n) { asm volatile("bar.sync %0, %1;" :: "r"(id), "r"(n) : "memory"); }
DEVI void nbar_arrive_r(int id, int n) { asm volatile("bar.arrive %0, %1;" :: "r"(id), "r"(n) : "memory"); }
template<int R> DEVI void reg_inc() { asm volatile("setmaxnreg.inc.sync.aligned.u32 %0;" :: "n"(R)); }
template<int R> DEVI void reg_dec() { asm volatile("setmaxnreg.dec.sync.aligned.u32 %0;" :: "n"(R)); }
DEVI void wg_fence() { asm volatile("wgmma.fence.sync.aligned;" ::: "memory"); }
DEVI void wg_commit() { asm volatile("wgmma.commit_group.sync.aligned;" ::: "memory"); }
template<int N> DEVI void wg_wait() { asm volatile("wgmma.wait_group.sync.aligned %0;" :: "n"(N) : "memory"); }
DEVI uint32_t pack_bf16(float lo, float hi) { uint32_t r; asm("cvt.rn.bf16x2.f32 %0, %1, %2;" : "=r"(r) : "f"(hi), "f"(lo)); return r; }
DEVI float bf_lo(uint32_t v) { return __uint_as_float(v << 16); }
DEVI float bf_hi(uint32_t v) { return __uint_as_float(v & 0xffff0000u); }
DEVI uint32_t movmat(uint32_t a) { uint32_t r; asm volatile("movmatrix.sync.aligned.m8n8.trans.b16 %0, %1;" : "=r"(r) : "r"(a)); return r; }
DEVI void ldsm4(uint32_t addr, uint32_t& r0, uint32_t& r1, uint32_t& r2, uint32_t& r3) {
  asm volatile("ldmatrix.sync.aligned.m8n8.x4.shared.b16 {%0,%1,%2,%3}, [%4];" : "=r"(r0), "=r"(r1), "=r"(r2), "=r"(r3) : "r"(addr) : "memory");
}
DEVI void ldsm4t(uint32_t addr, uint32_t& r0, uint32_t& r1, uint32_t& r2, uint32_t& r3) {
  asm volatile("ldmatrix.sync.aligned.m8n8.x4.trans.shared.b16 {%0,%1,%2,%3}, [%4];" : "=r"(r0), "=r"(r1), "=r"(r2), "=r"(r3) : "r"(addr) : "memory");
}
DEVI void stsm4(uint32_t addr, uint32_t r0, uint32_t r1, uint32_t r2, uint32_t r3) {
  asm volatile("stmatrix.sync.aligned.m8n8.x4.shared.b16 [%0], {%1,%2,%3,%4};" :: "r"(addr), "r"(r0), "r"(r1), "r"(r2), "r"(r3) : "memory");
}
DEVI uint4 lds128(uint32_t a) { uint4 v; asm volatile("ld.shared.v4.u32 {%0,%1,%2,%3}, [%4];" : "=r"(v.x), "=r"(v.y), "=r"(v.z), "=r"(v.w) : "r"(a) : "memory"); return v; }
DEVI uint32_t lds32v(uint32_t a) { uint32_t v; asm volatile("ld.volatile.shared.u32 %0, [%1];" : "=r"(v) : "r"(a) : "memory"); return v; }
DEVI void sts32v(uint32_t a, uint32_t v) { asm volatile("st.volatile.shared.u32 [%0], %1;" :: "r"(a), "r"(v) : "memory"); }
DEVI void st_async128(uint32_t a, uint32_t x, uint32_t y, uint32_t z, uint32_t w, uint32_t bar) {
  asm volatile("st.async.weak.shared::cluster.mbarrier::complete_tx::bytes.v4.b32 [%0], {%1,%2,%3,%4}, [%5];" :: "r"(a), "r"(x), "r"(y), "r"(z), "r"(w), "r"(bar) : "memory");
}
DEVI void st_async32(uint32_t a, uint32_t x, uint32_t bar) {
  asm volatile("st.async.weak.shared::cluster.mbarrier::complete_tx::bytes.b32 [%0], %1, [%2];" :: "r"(a), "r"(x), "r"(bar) : "memory");
}
DEVI void st_cl128(bool own, uint32_t a, uint32_t x, uint32_t y, uint32_t z, uint32_t w, uint32_t bar) {
  asm volatile("{.reg .pred p; setp.ne.u32 p, %6, 0; @p st.shared.v4.b32 [%0], {%1,%2,%3,%4};\n"
               "@!p st.async.weak.shared::cluster.mbarrier::complete_tx::bytes.v4.b32 [%0], {%1,%2,%3,%4}, [%5];}"
               :: "r"(a), "r"(x), "r"(y), "r"(z), "r"(w), "r"(bar), "r"((uint32_t)own) : "memory");
}
DEVI void st_cl32(bool own, uint32_t a, uint32_t x, uint32_t bar) {
  asm volatile("{.reg .pred p; setp.ne.u32 p, %3, 0; @p st.shared.b32 [%0], %1;\n"
               "@!p st.async.weak.shared::cluster.mbarrier::complete_tx::bytes.b32 [%0], %1, [%2];}" :: "r"(a), "r"(x), "r"(bar), "r"((uint32_t)own) : "memory");
}
DEVI uint4 ldg_rlx128(const void* p) {
  uint4 v;
  asm volatile("ld.relaxed.gpu.global.v4.b32 {%0,%1,%2,%3}, [%4];" : "=r"(v.x), "=r"(v.y), "=r"(v.z), "=r"(v.w) : "l"(p) : "memory");
  return v;
}
DEVI void stg_rlx128(void* p, uint32_t x, uint32_t y, uint32_t z, uint32_t w) {
  asm volatile("st.relaxed.gpu.global.v4.b32 [%0], {%1,%2,%3,%4};" :: "l"(p), "r"(x), "r"(y), "r"(z), "r"(w) : "memory");
}
DEVI void stg128(void* p, uint32_t x, uint32_t y, uint32_t z, uint32_t w) {
  asm volatile("st.global.v4.b32 [%0], {%1,%2,%3,%4};" :: "l"(p), "r"(x), "r"(y), "r"(z), "r"(w) : "memory");
}
DEVI void stg_rlx64(void* p, uint32_t x, uint32_t y) { asm volatile("st.relaxed.gpu.global.v2.b32 [%0], {%1,%2};" :: "l"(p), "r"(x), "r"(y) : "memory"); }
DEVI void stg_rlx32(void* p, uint32_t x) { asm volatile("st.relaxed.gpu.global.b32 [%0], %1;" :: "l"(p), "r"(x) : "memory"); }
DEVI uint32_t clock32() { uint32_t c; asm volatile("mov.u32 %0, %%clock;" : "=r"(c) :: "memory"); return c; }
DEVI uint32_t gtime() { uint32_t c; asm volatile("mov.u32 %0, %%globaltimer_lo;" : "=r"(c) :: "memory"); return c; }
DEVI void wait_time(uint32_t t, int& budget) { while ((int)(gtime() - t) < 0 && --budget > 0) {} }
DEVI uint2 ldg_rlx64(const void* p) { uint2 v; asm volatile("ld.relaxed.gpu.global.v2.b32 {%0,%1}, [%2];" : "=r"(v.x), "=r"(v.y) : "l"(p) : "memory"); return v; }
DEVI void sts16(uint32_t a, uint32_t x) { asm volatile("st.shared.b16 [%0], %1;" :: "r"(a), "h"((unsigned short)x) : "memory"); }
DEVI void sts128(uint32_t a, uint32_t x) { asm volatile("st.shared.v4.b32 [%0], {%1,%1,%1,%1};" :: "r"(a), "r"(x) : "memory"); }
DEVI void arrive_if_eq(uint32_t bar, int a, int b) { asm volatile("{.reg .pred p; setp.eq.s32 p, %1, %2; @p mbarrier.arrive.shared::cta.b64 _, [%0];}" :: "r"(bar), "r"(a), "r"(b) : "memory"); }
DEVI void arrive_cl_if_eq(uint32_t bar, int a, int b) { asm volatile("{.reg .pred p; setp.eq.s32 p, %1, %2; @p mbarrier.arrive.shared::cluster.b64 _, [%0];}" :: "r"(bar), "r"(a), "r"(b) : "memory"); }
template<int ID, int N> DEVI bool nbar_or(bool x) {
  uint32_t r;
  asm volatile("{.reg .pred p, q; setp.ne.u32 p, %1, 0; bar.red.or.pred q, %2, %3, p; selp.u32 %0, 1, 0, q;}" : "=r"(r) : "r"((uint32_t)x), "n"(ID), "n"(N) : "memory");
  return __any_sync(0xffffffffu, r);
}
DEVI void spin_until(uint32_t t0, int d) { while ((int)(clock32() - t0) < d) {} }
DEVI void flag_wait(const int* p, int n, int& budget) {
  while (ld_acquire(p) < n && --budget > 0) __nanosleep(128);
  asm volatile("fence.proxy.async.global;" ::: "memory");
}

#define F4(C, o)  C(d[o+0]), C(d[o+1]), C(d[o+2]), C(d[o+3])
#define F8(C, o)  F4(C, o), F4(C, o+4)
#define F32(C, o) F8(C, o), F8(C, o+8), F8(C, o+16), F8(C, o+24)
#define R4  "{%0,%1,%2,%3}"
#define R8  "{%0,%1,%2,%3,%4,%5,%6,%7}"
#define R16 "{%0,%1,%2,%3,%4,%5,%6,%7,%8,%9,%10,%11,%12,%13,%14,%15}"
#define R20 "{%0,%1,%2,%3,%4,%5,%6,%7,%8,%9,%10,%11,%12,%13,%14,%15,%16,%17,%18,%19}"
#define R32 "{%0,%1,%2,%3,%4,%5,%6,%7,%8,%9,%10,%11,%12,%13,%14,%15,%16,%17,%18,%19,%20,%21,%22,%23,%24,%25,%26,%27,%28,%29,%30,%31}"
#define R64 "{%0,%1,%2,%3,%4,%5,%6,%7,%8,%9,%10,%11,%12,%13,%14,%15,%16,%17,%18,%19,%20,%21,%22,%23,%24,%25,%26,%27,%28,%29,%30,%31," \
  "%32,%33,%34,%35,%36,%37,%38,%39,%40,%41,%42,%43,%44,%45,%46,%47,%48,%49,%50,%51,%52,%53,%54,%55,%56,%57,%58,%59,%60,%61,%62,%63}"
template<uint32_t OFF, uint32_t LBO, uint32_t SBO, uint32_t SW, int T> struct Op {
  static constexpr uint32_t lo = (OFF >> 4) | ((LBO >> 4) << 16), hi = (SBO >> 4) | (SW << 30);
  static constexpr int t = T;
};
DEVI uint32_t desc_base(uint32_t addr) { return (addr & 0x3FFFF) >> 4; }
#define RS_ASM(SHAPE, REGS, A0, A1, A2, A3, B, LO, HI, T, SD) \
  "{.reg .b64 tb; .reg .b32 lb; add.u32 lb, " B ", " LO "; mov.b64 tb, {lb, " HI "};\n" \
  "wgmma.mma_async.sync.aligned." SHAPE ".f32.bf16.bf16 " REGS ", {" A0 "," A1 "," A2 "," A3 "}, tb, " SD ", 1, 1, " T ";}"
#define WG_RS(NAME, SHAPE, REGS, LIST, ...) \
  template<int ACC, class OB> DEVI void NAME(float* d, const uint32_t* a, uint32_t b) { \
    if (ACC) asm volatile(RS_ASM(SHAPE, REGS, __VA_ARGS__) \
      : LIST("+f") : "r"(a[0]), "r"(a[1]), "r"(a[2]), "r"(a[3]), "r"(b), "n"(OB::lo), "n"(OB::hi), "n"(OB::t), "n"(ACC & 1)); \
    else asm volatile(RS_ASM(SHAPE, REGS, __VA_ARGS__) \
      : LIST("=f") : "r"(a[0]), "r"(a[1]), "r"(a[2]), "r"(a[3]), "r"(b), "n"(OB::lo), "n"(OB::hi), "n"(OB::t), "n"(0)); \
  }
#define SS_ASM(SHAPE, REGS, A, B, LA, HA, TA, LB, HB, TB, SD) \
  "{.reg .b64 ta, tb; .reg .b32 la, lb; add.u32 la, " A ", " LA "; mov.b64 ta, {la, " HA "}; add.u32 lb, " B ", " LB "; mov.b64 tb, {lb, " HB "};\n" \
  "wgmma.mma_async.sync.aligned." SHAPE ".f32.bf16.bf16 " REGS ", ta, tb, " SD ", 1, 1, " TA ", " TB ";}"
#define WG_SS(NAME, SHAPE, REGS, LIST, ...) \
  template<int ACC, class OA, class OB> DEVI void NAME(float* d, uint32_t a, uint32_t b) { \
    if (ACC) asm volatile(SS_ASM(SHAPE, REGS, __VA_ARGS__) \
      : LIST("+f") : "r"(a), "r"(b), "n"(OA::lo), "n"(OA::hi), "n"(OA::t), "n"(OB::lo), "n"(OB::hi), "n"(OB::t), "n"(ACC & 1)); \
    else asm volatile(SS_ASM(SHAPE, REGS, __VA_ARGS__) \
      : LIST("=f") : "r"(a), "r"(b), "n"(OA::lo), "n"(OA::hi), "n"(OA::t), "n"(OB::lo), "n"(OB::hi), "n"(OB::t), "n"(0)); \
  }
#define L4(C)  F4(C, 0)
#define L8(C)  F8(C, 0)
#define L16(C) F8(C, 0), F8(C, 8)
#define L20(C) F8(C, 0), F8(C, 8), F4(C, 16)
#define L32(C) F32(C, 0)
WG_RS(wg_rs8, "m64n8k16", R4, L4, "%4", "%5", "%6", "%7", "%8", "%9", "%10", "%11", "%12")
WG_RS(wg_rs16, "m64n16k16", R8, L8, "%8", "%9", "%10", "%11", "%12", "%13", "%14", "%15", "%16")
WG_RS(wg_rs32, "m64n32k16", R16, L16, "%16", "%17", "%18", "%19", "%20", "%21", "%22", "%23", "%24")
WG_SS(wg_ss32, "m64n32k16", R16, L16, "%16", "%17", "%18", "%19", "%20", "%21", "%22", "%23", "%24")
WG_RS(wg_rs64, "m64n64k16", R32, L32, "%32", "%33", "%34", "%35", "%36", "%37", "%38", "%39", "%40")
WG_SS(wg_ss8, "m64n8k16", R4, L4, "%4", "%5", "%6", "%7", "%8", "%9", "%10", "%11", "%12")
WG_SS(wg_ss16, "m64n16k16", R8, L8, "%8", "%9", "%10", "%11", "%12", "%13", "%14", "%15", "%16")
WG_SS(wg_ss40, "m64n40k16", R20, L20, "%20", "%21", "%22", "%23", "%24", "%25", "%26", "%27", "%28")
WG_SS(wg_ss64, "m64n64k16", R32, L32, "%32", "%33", "%34", "%35", "%36", "%37", "%38", "%39", "%40")
#define L64(C) F32(C, 0), F32(C, 32)
WG_SS(wg_ss128, "m64n128k16", R64, L64, "%64", "%65", "%66", "%67", "%68", "%69", "%70", "%71", "%72")
template<int I> struct IC { __host__ __device__ constexpr operator int() const { return I; } };
template<int I, int N, class F> DEVI void sfor(F&& f) {
  if constexpr (I < N) { f(IC<I>{}); sfor<I + 1, N>(f); }
}

#define R_CL 6
namespace rec {
constexpr int NHI = 36, NLO = 5, NRS = NHI + NLO, NSS = 64 - NRS;
constexpr uint32_t WS = 0;
constexpr uint32_t WO = 2 * NSS * 2048;
constexpr uint32_t RING = WO + 65536;
constexpr uint32_t QB = RING + 40960, RG = 2080, POSQ = 0x64210, POSK = 0xB9753, POSV = 0xEDCA8;
#define JA 2
constexpr uint32_t WA = QB;
constexpr uint32_t OM = QB + 9 * RG, OMS = 2 * RG;
constexpr uint32_t OM2 = QB + 16384, OM2S = 2048;
constexpr uint32_t WH = QB + 20480;
constexpr uint32_t B_PART = QB + 15 * RG - 32, B_ML0 = B_PART + 8, REDO = B_PART + 16;
constexpr uint32_t PM0 = QB + 16384, PM1 = QB + 15 * RG, PM2 = PM1 + 256;
constexpr uint32_t BARS = PM2 + 128;
constexpr uint32_t B_FULL = BARS, B_EMPTY = BARS + 40, B_MLAND = BARS + 80, B_QK = BARS + 112, B_V = BARS + 120, B_OM = BARS + 128,
                   B_WA = BARS + 136, B_SDONE = BARS + 144, B_BFREE = BARS + 152, B_W1 = PM1, B_W2 = PM1 + 8, B_WO = PM1 + 16;
constexpr uint32_t SMEM = BARS + 160;
static_assert(SMEM <= 232448 && QB % 1024 == 0, "smem map");
constexpr int R1 = (PM1 - WO) / 4096, RB = NRS - R1;
__host__ __device__ constexpr uint32_t stage_at(int t, int r) { return r < R1 ? WO + (t * R1 + r) * 2048 : WS + (t * NSS + NSS - RB + r - R1) * 2048; }
constexpr int NB_WO = 1, NB_ST = 2, NB_P = 3, NB_TR = 4, NB_X = 5, NB_G = 6, NB_G1 = 7, NB_G2 = 8, NB_G4 = 9, NB_S = 10;
__host__ __device__ constexpr bool is_lo(int j) { return j % 12 == 8; }
__host__ __device__ constexpr int lo_before(int j) { return (j + 3) / 12; }
__host__ __device__ constexpr int ss_before(int j) { return (j - lo_before(j)) * NSS / (64 - NLO); }
__host__ __device__ constexpr bool is_ss(int j) { return ss_before(j + 1) != ss_before(j); }
__host__ __device__ constexpr int reg_idx(int j) { return is_lo(j) ? NHI + lo_before(j) : j - ss_before(j) - lo_before(j); }
template<int j> using OpW = Op<WS + ss_before(j) * 2048, 16, 1024, 1, 1>;
#define P_G1 1
#define P_G2 3
#define P_G2L 0
#define P_OS 1
#define P_NA 6
#define P_G4 10
#define P_G5 12
#define P_FW 1
#define P_SEND 0xff3210ffu
#define P_WB 2
#define P_WOL 0
#define P_G4L 2
#define P_S1 0
#define P_S2 0
#define P_SPEC 1
#define P_S0 2
#define P_MB 0
#define P_S4 5
#define P_S5 8
constexpr uint32_t SLOT1 = 0x32410324, USE1 = 0x22111110;
DEVI bool single(int s) { return s < LAG - 1 || s >= NSEG - 1; }
DEVI uint32_t flip(int s) { return (s < LAG - 1 ? s + 1 : s < NSEG - 1 ? LAG : LAG + s + 1) & 1; }
#define TUN(i, v) (v)
}
#define PROFW(wq, i)
#define SPROF(i)
DEVI uint32_t mapr(int h, uint32_t addr, int rank) { return mapa(addr, rank + (R_CL == 6 ? (h & 1) * 3 : 0)); }
template<int N> DEVI void pin(float* d) {
#pragma unroll
  for (int i = 0; i < N; i++) asm volatile("" : "+f"(d[i]) :: "memory");
}
DEVI void keep(const void* a) { asm volatile("{.reg .pred p; setp.eq.u64 p, %0, 0; vote.sync.any.pred p, p, 0xffffffff; @p exit;}" :: "l"(a) : "memory"); }
DEVI int lane_reg() { return __shfl_sync(0xffffffffu, threadIdx.x & 31, threadIdx.x & 31); }
#define LANE_NOW [[maybe_unused]] const int lane = lane0 + ((uint32_t)budget >> 30), g = lane >> 2, c = lane & 3

DEVI void rec_proj(const uint32_t sb, const int h, const int rank, const int w, const CUtensorMap* mW, const uint32_t zero) {
  using namespace rec;
  const int lane0 = lane_reg(), wg = w >> 2, ww = w & 3;
  int budget = SPIN_BUDGET;
  uint32_t wr[NRS * 4];
  {
    LANE_NOW;
    const uint32_t wsw = ((lane & 7) + (lane >> 4) * 8) * 128 + (((ww * 2 + ((lane >> 3) & 1)) ^ (lane & 7)) << 4);
    SPROF(0);
    mbar_wait(sb + B_W1, 0, budget);
    SPROF(1);
#pragma unroll
    for (int r = 0; r < NRS; r++) ldsm4t(sb + stage_at(wg, r) + wsw, wr[4*r], wr[4*r+1], wr[4*r+2], wr[4*r+3]);
    fence_proxy_async();
    nbar_sync<NB_ST, 256>();
    if (w < 4) {
      const int j = w * 16 + (lane >> 1), t = lane & 1;
      if (is_ss(j) && ss_before(j) >= NSS - RB) tma_load_2d(sb + WS + (t * NSS + ss_before(j)) * 2048, mW, h * DH + t * 64, j * 16, sb + B_W2);
    }
    __syncwarp();
    cluster_sync();
  }
  const uint32_t d0 = desc_base(sb), da = d0 + wg * (NSS * 128);
  const uint32_t pos = rank == 0 ? POSQ : rank == 1 ? POSK : POSV, bar = rank == 2 ? B_V : B_QK;
  uint32_t stg[2][4] = {}, pk[16] = {};
  auto stage = [&](uint32_t* t, int r) {
#pragma unroll
    for (int i = 0; i < 4; i++) asm volatile("xor.b32 %0, %1, %2;" : "+r"(t[i]) : "r"(wr[4 * r + i]), "r"(zero));
  };
#pragma unroll 1
  for (int s = -1; s < NSTEP; s++) {
    const uint32_t fl = flip(s);
    if (s >= 0) {
      float d[8];
      auto steps = [&](auto J0, auto J1, auto A0) {
        wg_fence();
        sfor<J0, J1>([&](auto J) {
          constexpr int j = J, acc = j ? 1 : A0;
          typedef Op<RING + j * 512, 256, 128, 0, 1> OB;
          if constexpr (is_ss(j)) wg_ss16<acc, OpW<j>, OB>(d, da, d0);
          else wg_rs16<acc, OB>(d, is_lo(j) ? stg[lo_before(j) & 1] : wr + 4 * reg_idx(j), d0);
        });
        wg_commit();
      };
      stage(stg[0], NHI);
      mbar_wait(sb + (P_SPEC ? B_ML0 : B_FULL), P_SPEC ? s & 1 : 0, budget);
      PROFW(0, 16);
      sfor<0, 8>([&](auto E) {
        constexpr int e = E, q = e >> 1;
        steps(IC<8 * e>{}, IC<8 * e + 8>{}, IC<0>{});
        if constexpr (e == 1 && P_SPEC) {
          mbar_wait(sb + B_FULL, 0, budget);
          if (__any_sync(0xffffffffu, lds32v(sb + REDO))) { wg_wait<0>(); steps(IC<0>{}, IC<16>{}, IC<2>{}); }
        }
        if constexpr (((P_SEND >> (4 * e)) & 15) == 0) { if (s > 0) mbar_wait(sb + B_BFREE, (s & 1) ^ 1, budget); }
        if constexpr (e > 0 && !(e & 1)) {
          wg_wait<1>();
          arrive_if_eq(sb + B_EMPTY + 8 * (q - 1), lane0, ww * 32);
        }
        if constexpr (!(e & 1)) stage(stg[(q + 1) & 1], NHI + q + 1);
        if constexpr (e < 6 && (e & 1) == P_FW) mbar_wait(sb + B_FULL + 8 * (q + 1), q ? fl : 0, budget);
        if constexpr (((P_SEND >> (4 * e)) & 15) < 4) {
          constexpr int n = (P_SEND >> (4 * e)) & 15;
          LANE_NOW;
          const uint32_t r = mapr(h, sb, n >> 1);
          uint32_t t[4];
#pragma unroll
          for (int i = 0; i < 4; i++) { if (n == 0) t[i] = pk[i]; else asm volatile("xor.b32 %0, %1, %2;" : "=r"(t[i]) : "r"(pk[4*n+i]), "r"(zero)); }
          st_cl128(rank == n >> 1, r + QB + ((pos >> (4 + 4 * c)) & 15) * RG + w * 256 + (n & 1) * 128 + g * 16, t[0], t[1], t[2], t[3], r + bar);
        }
      });
      LANE_NOW;
      const uint32_t dst = QB + (pos & 15) * RG + w * 256 + lane * 4;
      wg_wait<0>();
      pin<8>(d);
      {
        const uint32_t x0 = pack_bf16(d[0], d[1]), x1 = pack_bf16(d[2], d[3]), y0 = pack_bf16(d[4], d[5]), y1 = pack_bf16(d[6], d[7]);
        const uint32_t r = mapr(h, sb, rank == 0);
        if (rank < 2) { sts32v(sb + dst, rank ? y0 : x0); sts32v(sb + dst + 128, rank ? y1 : x1); fence_proxy_async(); }
        st_async32(r + dst, rank ? x0 : y0, r + bar); st_async32(r + dst + 128, rank ? x1 : y1, r + bar);
        if (rank < 2) e_arrive(sb + B_QK);
        else { const uint32_t r1 = mapr(h, sb, 1); st_async32(r1 + dst, y0, r1 + bar); st_async32(r1 + dst + 128, y1, r1 + bar); }
      }
      PROFW(0, 17);
      if (s == NSTEP - 1) break;
      arrive_if_eq(sb + B_EMPTY + 24, lane0, ww * 32);
    } else {
      e_arrive(sb + B_EMPTY + 8 * ww);
      mbar_wait(sb + B_W2, 0, budget);
      SPROF(2);
    }
    const bool gate = rank < 2 && s >= 0;
    if (single(s)) {
      float d[16];
      sfor<0, 8>([&](auto C) {
        constexpr int cc = C, sl = (SLOT1 >> (4 * cc)) & 15;
        if constexpr (cc == 0) mbar_wait(sb + B_FULL + 8 * sl, 0, budget);
        if constexpr (cc == P_S1) { if (gate) nbar_sync<NB_G1, 384>(); }
        if constexpr (cc == P_S2) { if (gate) nbar_sync<NB_G2, 384>(); }
        if constexpr (cc == P_S0) nbar_sync<NB_WO, 384>();
        if constexpr (cc == P_S4 || cc == P_S5) { if (gate && cc == (rank ? P_S5 : P_S4)) nbar_sync<NB_G4, 384>(); }
        if constexpr (lo_before(cc * 8 + 8) != lo_before(cc * 8)) stage(stg[0], NHI + lo_before(cc * 8));
        wg_fence();
        sfor<0, 8>([&](auto I) {
          constexpr int i = I, j = cc * 8 + i;
          typedef Op<RING + sl * 8192 + (i >> 2) * 4096 + (i & 3) * 32, 16, 1024, 1, 0> OB;
          if constexpr (is_ss(j)) wg_ss32<j != 0, OpW<j>, OB>(d, da, d0);
          else wg_rs32<j != 0, OB>(d, is_lo(j) ? stg[0] : wr + 4 * reg_idx(j), d0);
        });
        wg_commit();
        if constexpr (cc < 7) {
          constexpr int sn = (SLOT1 >> (4 * cc + 4)) & 15;
          mbar_wait(sb + B_FULL + 8 * sn, ((USE1 >> (4 * cc + 4)) & 1) ^ (sn >> 1 == 1 ? fl : 0), budget);
        }
        wg_wait<0>();
        arrive_if_eq(sb + B_EMPTY + 8 * sl, lane0, ww * 32);
      });
      pin<16>(d);
      if (gate && (rank ? P_S5 : P_S4) == 8) nbar_arrive<NB_G4, 384>();
      PROFW(0, 20);
#pragma unroll
      for (int i = 0; i < 8; i++) pk[i] = pk[8 + i] = pack_bf16(d[4 * (i & 3) + ((i >> 1) & 2)], d[4 * (i & 3) + ((i >> 1) & 2) + 1]);
      continue;
    }
    float d[32];
    sfor<0, 16>([&](auto C) {
      constexpr int cc = C, sl = (cc + 4) % 5;
      if constexpr (cc == 0) mbar_wait(sb + B_FULL + 8 * sl, 0, budget);
      if constexpr (cc == P_G1) { if (gate) nbar_sync<NB_G1, 384>(); }
      if constexpr (cc == P_G2) { if (gate) nbar_sync<NB_G2, 384>(); }
      if constexpr (cc == P_NA) {
        PROFW(0, 18);
        nbar_sync<NB_WO, 384>();
      }
      if constexpr (cc == P_G4 || cc == P_G5) { if (gate && cc == (rank ? P_G5 : P_G4)) nbar_sync<NB_G4, 384>(); }
      wg_fence();
      sfor<0, 4>([&](auto I) {
        constexpr int i = I, j = cc * 4 + i;
        typedef Op<RING + sl * 8192 + i * 32, 16, 1024, 1, 0> OB;
        if constexpr (is_ss(j)) wg_ss64<j != 0, OpW<j>, OB>(d, da, d0);
        else wg_rs64<j != 0, OB>(d, is_lo(j) ? stg[0] : wr + 4 * reg_idx(j), d0);
      });
      wg_commit();
      if constexpr (cc == P_NA) PROFW(0, 19);
      if constexpr (cc < 15) {
        if constexpr (is_lo(cc * 4 + 4)) stage(stg[0], reg_idx(cc * 4 + 4));
        mbar_wait(sb + B_FULL + 8 * ((sl + 1) % 5), ((cc + 5) / 5 + (sl == 1 || sl == 2 ? LAG : 0)) & 1, budget);
      }
      wg_wait<0>();
      arrive_if_eq(sb + B_EMPTY + 8 * sl, lane0, ww * 32);
    });
    pin<32>(d);
    if (gate && (rank ? P_G5 : P_G4) == 16) nbar_arrive<NB_G4, 384>();
    PROFW(0, 20);
#pragma unroll
    for (int i = 0; i < 16; i++) pk[i] = pack_bf16(d[16 * (i >> 3) + 4 * (i & 3) + ((i >> 1) & 2)], d[16 * (i >> 3) + 4 * (i & 3) + ((i >> 1) & 2) + 1]);
  }
}

DEVI float softmax_row(float* v, uint32_t* p) {
  constexpr float SC = 0.08838834764831845f * 1.4426950408889634f;
  float m = fmaxf(fmaxf(fmaxf(fmaxf(v[0], v[1]), fmaxf(v[2], v[3])), fmaxf(fmaxf(v[4], v[5]), fmaxf(v[6], v[7]))), fmaxf(v[8], v[9]));
  m = fmaxf(m, __shfl_xor_sync(0xffffffffu, m, 1));
  m = fmaxf(m, __shfl_xor_sync(0xffffffffu, m, 2));
  const float ms = -m * SC, mh = fmaf(m, -SC, -1.f);
#pragma unroll
  for (int i = 0; i < 10; i++) asm("ex2.approx.ftz.f32 %0, %1;" : "=f"(v[i]) : "f"(fmaf(v[i], SC, i < 8 ? ms : mh)));
#pragma unroll
  for (int n = 0; n < 5; n++) p[n] = pack_bf16(v[2*n], v[2*n+1]);
  return fmaf(v[8] + v[9], 2.f, ((v[0] + v[1]) + (v[2] + v[3])) + ((v[4] + v[5]) + (v[6] + v[7])));
}

template<bool ATT>
DEVI void rec_attn(const uint32_t sb, int h, int rank, int w, const bf16* __restrict__ Wo, const bf16* __restrict__ mem0) {
  using namespace rec;
  const int lane0 = lane_reg();
  int budget = SPIN_BUDGET;
  constexpr int NT = ATT ? 5 : 6;
  uint32_t wl[16];
  if (!ATT) {
    LANE_NOW;
#pragma unroll
    for (int i = 0; i < 16; i++) {
      const int dh = 8 * (i >> 1) + 2 * c;
      const unsigned short* p = (const unsigned short*)Wo + (size_t)(h * DH + dh) * DM + 15 * 64 + 16 * w + 8 * (i & 1) + g;
      wl[i] = p[0] | (uint32_t)p[DM] << 16;
    }
  }
  cluster_sync();
  const uint32_t d0 = desc_base(sb);
  uint32_t pph = 0;
#pragma unroll 1
  for (int s = -1; s < NSTEP; s++) {
    asm volatile("" : "+r"(h), "+r"(rank), "+r"(w));
    const uint32_t sp = s & 1;
    const int t0 = ATT ? rank + 1 : 0;
    const bool more = s + 1 < NSTEP;
    if (s == 0) mbar_wait(sb + B_WO, 0, budget);
    float hold[10] = {0, 0, 0, 0, 0, 0, 0, 0, 0, 0};
    if (ATT && s >= 0) {
      float sc[20];
      LANE_NOW;
      mbar_wait(sb + B_QK, sp, budget);
      PROFW(0, 1);
      fence_proxy_async();
      wg_fence();
      sfor<0, 8>([&](auto K) { constexpr int k = K; wg_ss40<k != 0, Op<QB + k * 256, 128, RG, 0, 1>, Op<QB + 3 * RG + k * 256, 128, 2 * RG, 0, 1>>(sc, d0, d0); });
      wg_commit();
      if (P_G1 < 16 && more) nbar_arrive<NB_G1, 384>();
      wg_wait<0>();
      pin<20>(sc);
      if (w == 3 && more) nbar_arrive<NB_S, 64>();
      PROFW(1, 2);
      if (w == 0) {
        uint32_t p[5];
        float v[10];
#pragma unroll
        for (int i = 0; i < 10; i++) v[i] = sc[4 * (i >> 1) + (i & 1)];
        softmax_row(v, p);
        const uint32_t a = sb + lane * 4;
        sts32v(a + PM0, p[0]); sts32v(a + PM0 + 128, p[1]); sts32v(a + PM1, p[2]); sts32v(a + PM1 + 128, p[3]); sts32v(a + PM2, p[4]);
      }
      if (w || !more) mbar_wait(sb + B_V, sp, budget);
      if (w == 1 && more) e_expect_tx(sb + B_V, 10240);
      if (more) {
        float rs[4], ot[2][4];
        uint32_t one[4];
#pragma unroll
        for (int i = 0; i < 4; i++) one[i] = 0x3F803F80u + ((uint32_t)budget >> (31 - i));
        typedef Op<PM0, 128, 128, 0, 0> P0; typedef Op<PM1, 128, 128, 0, 0> P1; typedef Op<PM2, 0, 128, 0, 0> P2;
        fence_proxy_async();
        nbar_sync<NB_P, 128>();
        PROFW(0, 3);
        wg_fence();
        wg_rs8<0, P0>(rs, one, d0); wg_rs8<1, P1>(rs, one, d0); wg_rs8<1, P2>(rs, one, d0);
        wg_commit();
        sfor<0, 2>([&](auto T) {
          constexpr int t = T;
          wg_ss8<0, Op<QB + 8 * RG + t * 1024, 2 * RG, 128, 0, 0>, P0>(ot[t], d0, d0);
          wg_ss8<1, Op<QB + 12 * RG + t * 1024, RG, 128, 0, 0>, P1>(ot[t], d0, d0);
          wg_ss8<1, Op<QB + 14 * RG + t * 1024, 0, 128, 0, 0>, P2>(ot[t], d0, d0);
        });
        wg_commit();
        const bool g2l = P_G2L == 1 || (P_G2L == 2 && single(s));
        if (!g2l) nbar_arrive<NB_G2, 384>();
        const uint32_t oa = w * 256 + lane * 4, r1 = mapr(h, sb, rank ^ 1), r2 = mapr(h, sb, 2);
        mbar_wait(sb + B_SDONE, sp, budget);
        wg_wait<1>();
        pin<4>(rs);
        float i0, i1;
        asm volatile("rcp.approx.ftz.f32 %0, %1;" : "=f"(i0) : "f"(rs[0]));
        asm volatile("rcp.approx.ftz.f32 %0, %1;" : "=f"(i1) : "f"(rs[1]));
        wg_wait<0>();
        pin<4>(ot[0]); pin<4>(ot[1]);
        uint32_t x[4];
#pragma unroll
        for (int j = 0; j < 4; j++) {
          x[j] = pack_bf16(ot[j >> 1][2 * (j & 1)] * i0, ot[j >> 1][2 * (j & 1) + 1] * i1);
          sts32v(sb + OM + rank * OMS + oa + (j >> 1) * 1024 + (j & 1) * 128, x[j]);
        }
        fence_proxy_async();
#pragma unroll
        for (int j = 0; j < 8; j++) {
          const int i = P_OS ? j >> 1 : j & 3;
          if (P_OS ? j & 1 : j >> 2) st_async32(r1 + OM + rank * OMS + oa + (i >> 1) * 1024 + (i & 1) * 128, x[i], r1 + B_OM);
          else st_async32(r2 + OM2 + rank * OM2S + oa + (i >> 1) * 1024 + (i & 1) * 128, x[i], r2 + B_OM);
        }
        e_arrive(sb + B_OM);
        if (g2l) nbar_arrive<NB_G2, 384>();
        PROFW(0, 4);
      }
#pragma unroll
      for (int i = 0; i < 10; i++) hold[i] = w ? sc[4 * (i >> 1) + (i & 1)] : sc[4 * (i >> 1) + 2 + (i & 1)];
    }
    if (more && s >= 0) {
      LANE_NOW;
      char* const pw = (char*)g_part + (uint32_t)((t0 * 16 + w * 4 + (lane >> 3)) * 4096 + h * 128 + ((lane ^ h) & 7) * 16);
      mbar_wait(sb + B_OM, sp, budget);
      if (w == 0) nbar_arrive<NB_G, 128>();
      PROFW(1, 5);
      if (!ATT) fence_proxy_async();
      float acc[3][8];
      auto store = [&](auto J) {
        constexpr int j = J;
        float* d = acc[j % 3];
        pin<8>(d);
        uint32_t x[4];
#pragma unroll
        for (int i = 0; i < 4; i++) { const uint32_t m = (h >> 3) == i; x[i] = (pack_bf16(d[2*i], d[2*i+1]) & ~m) | (m & ~sp); }
        stg_rlx128(pw + j * (48 * 4096), x[0], x[1], x[2], x[3]);
        if constexpr (ATT && j == JA) nbar_arrive<NB_TR, 160>();
        if constexpr (j == 2) PROFW(3, 26);
      };
      sfor<0, NT>([&](auto J) {
        constexpr int j = J;
        if constexpr (ATT && j == JA) { mbar_wait(sb + B_WA, sp, budget); PROFW(2, 0); }
        wg_fence();
        sfor<0, 8>([&](auto K) {
          constexpr int k = K;
          typedef Op<(ATT ? OM : OM2) + k * 256, 128, ATT ? OMS : OM2S, 0, 1> OB;
          if constexpr (j == 5 && k < 4) wg_rs16<k ? 1 : 2, OB>(acc[j % 3], wl + 4 * k, d0);
          else wg_ss16<k ? 1 : j < 3 ? 0 : 2, Op<(j == JA ? WA : j < 5 ? WO + (j - (j > JA)) * 16384 : WH - 8192) + k * 2048, 16, 1024, 1, 1>, OB>(acc[j % 3], d0, d0);
        });
        wg_commit();
        if constexpr (j == 0) { if (w == 3) e_expect_tx(sb + B_OM, ATT ? 2048 : 4096); }
        if constexpr (j == NT - 1 && !P_WOL) nbar_arrive<NB_WO, 384>();
        if constexpr (j > 0 && j != P_WB + 1) { wg_wait<1>(); store(IC<j - 1>{}); }
        if constexpr (j == P_WB || j == NT - 1) { wg_wait<0>(); store(IC<j>{}); }
        if constexpr (j == P_WB) {
          const uint32_t t = clock32();
          if (ATT) {
            if (w == 3 && lane < 14) sts128(sb + PM1 + lane * 16, (lane >> 1) == 3 ? 0x3F803F80u : 0);
            if (w == 3 || P_MB) fence_proxy_async();
            nbar_sync<NB_P, 128>();
          } else if (P_MB) fence_proxy_async();
          spin_until(t, TUN(8, 100));
        }
      });
      if (P_WOL) { spin_until(clock32(), TUN(9, 0)); nbar_arrive<NB_WO, 384>(); }
    } else if (more) nbar_arrive<NB_WO, 384>();
    PROFW(0, 6);
    asm volatile("" : "+r"(h), "+r"(rank), "+r"(w));
#pragma unroll 1
    for (int pass = 0; ATT && pass < 2; pass++)
    if (pass != rank) {
      LANE_NOW;
      const int lim = 8 * (g >> 1) + (g & 1) + 2 * w - 8 * c;
      uint32_t p[5];
#pragma unroll
      for (int i = 0; i < 8; i++) hold[2+i] = i <= lim ? hold[2+i] : -INFINITY;
      const float psum = softmax_row(hold, p);
#pragma unroll
      for (int i = 0; i < 5; i++) hold[i] = __uint_as_float(p[i]);
      hold[5] = psum;
    } else if (more) {
      LANE_NOW;
      const int blk = rank * 32 + (h ^ 16);
      char* const mw = (char*)g_mem + (uint32_t)(sp * 32768 + blk * 512 + w * 128 + lane * 4);
      uint32_t v0 = 0;
      if (s == -1 || (s == LAG - 1 && (w & 1))) {
        const unsigned short* q = (const unsigned short*)mem0 + c * 2 * DM + blk * 16 + (w >> 1) * 8 + g;
        v0 = q[0] | (uint32_t)q[DM] << 16;
        if (v0 == 0) v0 = 0x8000u;
      }
      keep(mw);
      if (s >= 0) {
        const uint32_t ca = sb + WA + lane * 128 + (((2 * w) ^ lane) & 7) * 16 + (lane >> 3) * 4;
        const uint32_t sa = sb + OM + (((g >> 1) & 1) * 2 + (g >> 2)) * 128 + (2 * c + (w >> 1)) * 16 + (w & 1) * 8 + (g & 1) * 2;
        const bool g4l = P_G4L == 1 || (P_G4L == 2 && single(s));
        for (bool first = true; ; first = false) {
          float r[4];
          mbar_wait(sb + B_PART, pph, budget);
          PROFW(0, 11);
          pph ^= 1;
          wg_fence();
          sfor<0, 8>([&](auto K) { constexpr int k = K; wg_ss8<k != 0, Op<WA + k * 2048, 16, 1024, 1, 1>, Op<PM1 + (6 - (k & 6)) * 16, 0, 128, 0, 0>>(r, d0, d0); });
          wg_commit();
          if (!g4l && first) nbar_arrive<NB_G4, 384>();
          const uint32_t x0 = lds32v(ca), x1 = lds32v(ca + 4096), x2 = lds32v(ca + 8192), x3 = lds32v(ca + 12288);
          bool bad = __any_sync(0xffffffffu, (sp ? x0 | x1 | x2 | x3 : ~(x0 & x1 & x2 & x3)) & 1) && budget > 0;
          wg_wait<0>();
          pin<4>(r);
          uint32_t y = pack_bf16(r[0], r[2]);
          y |= (y & 0xffffu) ? 0 : 0x8000u;
          y |= (y >> 16) ? 0 : 0x80000000u;
          if (bad) y = 0;
          sts16(sa, y); sts16(sa + 4, y >> 16);
          nbar_sync<NB_P, 128>();
          y = lds32v(sb + OM + w * 128 + lane * 4);
          const bool ok = !__any_sync(0xffffffffu, y == 0);
          if (ok) stg_rlx32(mw, v0 ? v0 : y);
          if (g4l && first) nbar_arrive<NB_G4, 384>();
          if (ok) break;
          nbar_sync<NB_P, 128>();
          budget--;
          if (w == 0) { e_expect_tx(sb + B_PART, 16384); e_bulk_g2s(sb + WA, (const char*)g_part + blk * 16384, 16384, sb + B_PART); }
          __syncwarp();
        }
        nbar_sync<NB_P, 128>();
        if (w < 2) e_arrive_cl(mapr(h, sb + B_BFREE, w));
      } else stg_rlx32(mw, v0);
      stg_rlx32(mw + (sp ? -32768 : 32768), 0);
      PROFW(1, 8);
    }
    if (ATT && s >= 0) {
      const int seg = s - (rank ? LAG : 0);
      const bool act = (unsigned)seg < NSEG;
      LANE_NOW;
      uint32_t a[12];
#pragma unroll
      for (int i = 0; i < 12; i++) a[i] = __float_as_uint(hold[i < 10 ? i >> 1 : 4]) + ((uint32_t)budget >> (31 - (i & 3)));
      float o[32], inv, psum = hold[5];
      char* const ob = (char*)g_o[rank] + ((size_t)(seg * 32 + 8 * (g >> 1) + (g & 1) + 2 * w) * (NH * DH) + h * DH + c * 8) * 2;
      sfor<0, 2>([&](auto HF) {
        constexpr int hf = HF;
        wg_fence();
        wg_rs64<hf * 2, Op<QB + 8 * RG + hf * 1024, 2 * RG, 128, 0, 0>>(o, a, d0);
        wg_rs64<1, Op<QB + 12 * RG + hf * 1024, RG, 128, 0, 0>>(o, a + 4, d0);
        wg_rs64<1, Op<QB + 14 * RG + hf * 1024, 0, 128, 0, 0>>(o, a + 8, d0);
        wg_commit();
        if constexpr (hf == 0) {
          psum += __shfl_xor_sync(0xffffffffu, psum, 1);
          psum += __shfl_xor_sync(0xffffffffu, psum, 2);
          asm("rcp.approx.ftz.f32 %0, %1;" : "=f"(inv) : "f"(psum));
        }
        wg_wait<0>();
        pin<32>(o);
        if constexpr (hf == 1) { if (w == 2 && more) e_arrive_cl(mapr(h, sb + B_BFREE, 2)); }
        if (act) {
#pragma unroll
          for (int i = 0; i < 2; i++)
            stg128(ob + (hf * 2 + i) * 64, pack_bf16(o[16*i] * inv, o[16*i+1] * inv), pack_bf16(o[16*i+4] * inv, o[16*i+5] * inv),
                   pack_bf16(o[16*i+8] * inv, o[16*i+9] * inv), pack_bf16(o[16*i+12] * inv, o[16*i+13] * inv));
        }
      });
      PROFW(0, 7);
      if (act && (seg & 3) == 3) {
        nbar_sync<NB_P, 128>();
        if (w == 0) e_flag_add(g_fl.dep + grp(0, rank, seg >> 2), 4);
      }
    } else if (!ATT && w == 3) {
      if (s + 4 < NSEG) e_prefetch(g_xn[0] + (size_t)((s + 4) * 32 + h) * DM, 2048);
    }
  }
  cluster_sync();
}

DEVI void rec_load(const uint32_t sb, const int h, const int rank, const int w, const CUtensorMap* mX, const CUtensorMap* mWo) {
  using namespace rec;
  const int lane0 = lane_reg(), mq = (w + 3) & 3;
  int budget = SPIN_BUDGET;
  if (w == 0) flag_wait(g_fl.xn[0][0], 96, budget);
  SPROF(3);
  bool late = false;
  cluster_sync();
  if (w == 0) { if (lane0 < 4) mbar_arrive(sb + B_FULL + 8 * lane0); __syncwarp(); }
  if (w == 3) {
    mbar_wait(sb + B_W2, 0, budget);
    e_expect_tx(sb + B_WO, rank == 2 ? 65536 + 16384 + 8192 : 65536);
    const int t0 = (rank + 1) % 3;
    if (lane0 < 8) tma_load_2d(sb + WO + lane0 * 8192, mWo, (3 * ((lane0 >> 1) + (lane0 >> 1 >= JA)) + t0) * 64, h * DH + (lane0 & 1) * 64, sb + B_WO);
    else if (rank < 2 && lane0 < 10) tma_prefetch_2d(mWo, (3 * JA + t0) * 64, h * DH + (lane0 & 1) * 64);
    else if (rank == 2 && lane0 < 11) tma_load_2d(lane0 < 10 ? sb + WA + (lane0 - 8) * 8192 : sb + WH, mWo, lane0 < 10 ? 3 * JA * 64 : 15 * 64, h * DH + (lane0 > 8) * 64, sb + B_WO);
    __syncwarp();
  }
  uint32_t lph = 0;
#pragma unroll 1
  for (int s = -1; s < NSTEP - 1; s++) {
    if (w == 0) {
      if (late) flag_wait(g_fl.xn[1][(s + 1 - LAG) >> 2], 128, budget);
      if (single(s)) {
#pragma unroll 1
        for (int i = 0; i < 8; i++) {
          const int k = i < 5 ? (0x21430 >> (4 * i)) & 15 : i;
          const int sl = (SLOT1 >> (4 * k)) & 15;
          mbar_wait(sb + B_EMPTY + 8 * sl, (((USE1 >> (4 * k)) ^ (sl >> 1 == 1 ? flip(s) : 0)) & 1) ^ 1, budget);
          e_expect_tx(sb + B_FULL + 8 * sl, 8192);
          e_tma_3d(sb + RING + sl * 8192, mX + 1, 0, (s + 1 + (s < LAG ? 0 : NSTEP)) * 32, k * 2, sb + B_FULL + 8 * sl);
        }
      } else {
        int sl = 4, ph = 1;
#pragma unroll 1
        for (int i = 0; i < 16; i++) {
          mbar_wait(sb + B_EMPTY + 8 * sl, ph ^ (sl >> 1 & LAG & 1), budget);
          e_expect_tx(sb + B_FULL + 8 * sl, 8192);
          e_tma_3d(sb + RING + sl * 8192, mX, i * 64, (s + 1) * 32, 0, sb + B_FULL + 8 * sl);
          if (++sl == 5) { sl = 0; ph ^= 1; }
        }
      }
      nbar_arrive<NB_X, 128>();
      const int sn = s + 2 - LAG;
      late = (sn & 3) == 0 && (unsigned)sn < NSEG && ld_acquire(g_fl.xn[1][sn >> 2]) < 128;
      asm volatile("fence.proxy.async.global;" ::: "memory");
    }
    uint32_t t = gtime();
    if (s >= 0) {
      uint2 a;
      if (w == 2 && rank < 2) {
        nbar_sync<NB_S, 64>();
        e_expect_tx(sb + B_WA, 16384);
        e_tma_2d(sb + WA, mWo, (3 * JA + 1 + rank) * 64, h * DH, sb + B_WA);
        e_tma_2d(sb + WA + 8192, mWo, (3 * JA + 1 + rank) * 64, h * DH + 64, sb + B_WA);
        e_arrive_cl(mapr(h, sb + B_SDONE, rank ^ 1));
        stg_rlx32(&g_ann[s & 1][lane0][h * 2 + rank], (gtime() & ~31u) | ((s + 1) & 31));
        e_expect_tx(sb + B_QK, 10240);
      }
      if (w) nbar_sync<NB_G, 128>();
      do { a = ldg_rlx64(&g_ann[s & 1][h][lane0 * 2]); } while (__any_sync(0xffffffffu, ((a.x ^ (s + 1)) | (a.y ^ (s + 1))) & 31) && --budget > 0);
      t += __reduce_max_sync(0xffffffffu, max((int)(a.x - t), (int)(a.y - t)));
      t = (t & ~31u) + (s >= NSEG - 1 ? TUN(6, 0) : 0);
      PROFW(1, 12);
      if (w == 1 && rank < 2) {
        nbar_sync<NB_TR, 160>();
        e_expect_tx(sb + B_PART, 16384);
        wait_time(t + (single(s) ? (rank ? TUN(11, 1500) : TUN(10, 1100)) : rank ? TUN(1, 1700) : TUN(0, 1300)), budget);
        e_bulk_g2s(sb + WA, (const char*)g_part + (rank * 32 + (h ^ 16)) * 16384, 16384, sb + B_PART);
        PROFW(1, 21);
      }
      t += s >= NSEG - 1 ? TUN(7, 0) : 0;
      t += single(s) ? (mq == 0 ? TUN(12, 1950) : mq == 1 ? TUN(13, 2100) : mq == 2 ? TUN(14, 2400) : TUN(15, 2600))
                     : (mq == 0 ? TUN(2, 2250) : mq == 1 ? TUN(3, 2400) : mq == 2 ? TUN(4, 2700) : TUN(5, 2950));
    }
    if (w) nbar_sync<NB_X, 128>();
    mbar_wait(sb + B_EMPTY + 8 * mq, mq >= 2 ? flip(s + 1) ^ 1 : 1, budget);
    PROFW(1, 9);
    uint32_t bar = sb + (P_SPEC && mq == 0 ? B_ML0 : B_MLAND + 8 * mq), redo = 0;
    e_expect_tx(bar, 8192);
    wait_time(t, budget);
    PROFW(1, 22); PROFW(3, 23);
    while (true) {
      e_bulk_g2s(sb + RING + mq * 8192, (const char*)g_mem + (s & 1) * 32768 + mq * 8192, 8192, bar);
      const uint32_t a = sb + RING + mq * 8192 + lane0 * 32 + (lane0 >> 2) * 4;
      if (bar == sb + B_ML0) mbar_wait(bar, (s + 1) & 1, budget);
      else { mbar_wait(bar, lph, budget); lph ^= 1; }
      PROFW(1, 24);
      uint32_t mn = 0xffffffffu;
#pragma unroll
      for (int i = 0; i < 8; i++) mn = min(mn, lds32v(a + i * 1024));
      if (!__any_sync(0xffffffffu, mn == 0) || --budget <= 0) break;
      bar = sb + B_MLAND + 8 * mq; redo = 1;
      e_expect_tx(bar, 8192);
    }
    if (mq == 0) sts32v(sb + REDO, redo);
    e_arrive(sb + B_FULL + 8 * mq);
    PROFW(1, 10); PROFW(2, 13); PROFW(3, 14); PROFW(0, 15);
  }
}

DEVI void ln_row(const uint4* u, bf16* dst, int lane) {
  const uint32_t* x = (const uint32_t*)u;
  float mean = 0, q = 0;
#pragma unroll
  for (int i = 0; i < 16; i++) mean += bf_lo(x[i]) + bf_hi(x[i]);
  mean *= 1.f / 32;
#pragma unroll
  for (int i = 0; i < 16; i++) { const float a = bf_lo(x[i]) - mean, b = bf_hi(x[i]) - mean; q = fmaf(a, a, fmaf(b, b, q)); }
#pragma unroll
  for (int o = 1; o < 32; o *= 2) {
    const float m2 = __shfl_xor_sync(0xffffffffu, mean, o), q2 = __shfl_xor_sync(0xffffffffu, q, o), dl = m2 - mean;
    q = fmaf(dl * dl, 16.f * o, q + q2);
    mean = 0.5f * (mean + m2);
  }
  const float rs = rsqrtf(q * (1.f / DM) + 1e-5f), mr = -mean * rs;
#pragma unroll
  for (int i = 0; i < 4; i++) {
    uint32_t y[4];
#pragma unroll
    for (int k = 0; k < 4; k++) y[k] = pack_bf16(fmaf(bf_lo(x[4*i+k]), rs, mr), fmaf(bf_hi(x[4*i+k]), rs, mr));
    stg128((uint4*)dst + i * 32 + lane, y[0], y[1], y[2], y[3]);
  }
}

struct RecMaps { CUtensorMap w[3], wo, x[2]; };
__global__ void __cluster_dims__(R_CL, 1, 1) __launch_bounds__(512, 1)
rec_kernel(const __grid_constant__ RecMaps M, const bf16* __restrict__ Wo, const bf16* __restrict__ mem0, const bf16* __restrict__ x, uint32_t zero) {
  using namespace rec;
  extern __shared__ __align__(1024) uint8_t smem[];
  const uint32_t sb = smem_u32(smem);
  const int tid = threadIdx.x, warp = __shfl_sync(0xffffffffu, tid >> 5, 0), wg = warp >> 2, lane = tid & 31;
  const int h = blockIdx.x / 3, rank = blockIdx.x % 3;
  if (warp >= 4) {
    const bool ln = warp >= 5 && blockIdx.x * 11 + warp - 5 < SEQ / 2;
    const size_t lo = (size_t)(blockIdx.x * 11 + warp - 5) * (2 * DM);
    uint4 u[8];
    if (ln) {
#pragma unroll
      for (int i = 0; i < 8; i++) u[i] = ldg_rlx128((const uint4*)(x + lo) + i * 32 + lane);
    }
    const uint4 z = make_uint4(0, 0, 0, 0);
    const int t = blockIdx.x * 384 + tid - 128;
    constexpr int N = (sizeof(Flags) - sizeof(g_fl.xn)) / 16;
    g_part[t] = z;
    if (t < 28672) g_part[96 * 384 + t] = z;
    else if (t < 32768) g_mem[0][t - 28672] = ((uint4*)g_stat[4])[t - 28672] = z;
    else if (t < 33792) ((uint4*)g_ann)[t - 32768] = z;
    else if (t < 33792 + N) ((uint4*)g_fl.dep)[t - 33792] = z;
    __syncwarp();
    if (ln) { ln_row(u, g_xn[0] + lo, lane); ln_row(u + 4, g_xn[0] + lo + DM, lane); }
    nbar_sync<NB_WO, 384>();
    if (warp == 4) {
      e_flag_add(g_fl.xn[0][0]);
      asm volatile("griddepcontrol.launch_dependents;" ::: "memory");
    }
  } else {
    if (warp == 0) {
      if (lane < 20) mbar_init(sb + BARS + 8 * lane, (lane >= 5 && lane < 10) || lane == 19 ? 2 : lane == 14 ? 9 : lane == 16 && rank < 2 ? 5 : 1);
      else if (lane < 23) mbar_init(sb + B_W1 + 8 * (lane - 20), 1);
      else if (lane < 25) mbar_init(sb + B_PART + 8 * (lane - 23), 1);
      fence_mbar_init();
      __syncwarp();
      e_expect_tx(sb + B_W1, NRS * 4096); e_expect_tx(sb + B_W2, NSS * 4096);
      e_expect_tx(sb + B_QK, 10240); e_expect_tx(sb + B_V, 10240); e_expect_tx(sb + B_OM, rank < 2 ? 2048 : 4096);
    }
    nbar_sync<NB_ST, 128>();
    if (!is_ss(tid >> 1)) tma_load_2d(sb + stage_at(tid & 1, reg_idx(tid >> 1)), &M.w[rank], h * DH + (tid & 1) * 64, (tid >> 1) * 16, sb + B_W1);
    __syncwarp();
  }
  __syncthreads();
  if (warp < 4) {
    const int j = tid >> 1, t = tid & 1;
    if (!is_ss(j)) {}
    else if (ss_before(j) < NSS - RB) tma_load_2d(sb + WS + (t * NSS + ss_before(j)) * 2048, &M.w[rank], h * DH + t * 64, j * 16, sb + B_W2);
    else tma_prefetch_2d(&M.w[rank], h * DH + t * 64, j * 16);
    __syncwarp();
  }
  if (wg == 3) {
    reg_dec<24>();
    rec_load(sb, h, rank, warp & 3, M.x, &M.wo);
    cluster_sync();
  } else if (wg == 2) {
    reg_dec<72>();
    if (rank < 2) rec_attn<true>(sb, h, rank, warp & 3, Wo, mem0);
    else rec_attn<false>(sb, h, rank, warp & 3, Wo, mem0);
  } else {
    reg_inc<208>();
    rec_proj(sb, h, rank, warp, &M.w[rank], zero);
    cluster_sync();
  }
}

namespace gm {
constexpr int STAGES = 6, STAGE_BYTES = 32768;
constexpr uint32_t SO = STAGES * STAGE_BYTES, B_FULL = SO + 32768, B_TRIG = B_FULL + 56, B_EMPTY = B_FULL + 64, B_JOB = B_FULL + 128,
                   B_MSG = B_FULL + 144, B_XF = B_FULL + 160, B_SF = B_FULL + 176, JOB = B_FULL + 192, MSG = JOB + 8, SMEM = B_FULL + 256;
constexpr int T_O = 0, T_GU = 1, T_D = 2, T_END = 3;
#define G_LOOK 8
#define G_FILL 7
#define G_SLEEP 100
#define G_SLEEP2 500
#define G_SLEEP3 100
#define G_DF 2
#define G_FL 12
#define G_DE 0
#define G_BOOT 3
#define G_O0 4
#define G_O1 12
#define G_DS 14
DEVI bool is_split(int ty, int l, int cb) { return ty == T_O ? !l || cb < G_O0 || cb >= G_O1 : ty == T_D && (!l || cb >= G_DS); }
#define G_ROLES 16, 17, 8, 9, 10, 0, 1, 2, 3, 4, 5, 6, 7, 11, 12, 13, 14, 15
constexpr uint64_t pack_roles(int i0, int i1) { constexpr int r[18] = {G_ROLES}; uint64_t v = 0; for (int i = i0; i < i1; i++) v |= (uint64_t)r[i] << (5 * (i - i0)); return v; }
constexpr uint64_t ROLE0 = pack_roles(0, 12), ROLE1 = pack_roles(12, 18);
static_assert(G_FL >= G_O1 && G_FL >= 8, "fused layernorm: split jobs, 8 slots");
struct Pipe { int s, ph; DEVI void next() { if (++s == STAGES) { s = 0; ph ^= 1; } } };
}
struct GemmMaps { CUtensorMap o, oh, wo, x, x1, x1s, xm, xms, xn, wg, wu, h, hs, wd, x2, x2s, out, outs; };

DEVI float geglu(float g, float u) {
  const float z = g * (0.7978845608028654f + 0.035677408136300125f * g * g);
  float t; asm("tanh.approx.f32 %0, %1;" : "=f"(t) : "f"(z));
  const float hg = 0.5f * g;
  return fmaf(hg, t, hg) * u;
}
DEVI int h_ready(int v) { const int t = v ^ 0x10141014; return t & 0xff0000ff ? 0 : t & 0xff00 ? 20 : t ? 36 : 56; }
DEVI int a_ready(int ty, int l, int cb) {
  int v;
  asm volatile("ld.acquire.gpu.global.s32 %0, [%1];" : "=r"(v) : "l"(g_fl.dep + grp(ty, l, cb) + (threadIdx.x & 1)) : "memory");
  v = __shfl_sync(0xffffffffu, v, 0);
  asm volatile("fence.proxy.async.global;" ::: "memory");
  return ty == gm::T_D ? h_ready(v) : v >= (ty == gm::T_O && l ? 256 : 128) ? 64 : 0;
}

__global__ void __cluster_dims__(2, 1, 1) __launch_bounds__(512, 1) gemm_kernel(const __grid_constant__ GemmMaps M) {
  using namespace gm;
  extern __shared__ __align__(1024) uint8_t smem[];
  const uint32_t sb = smem_u32(smem);
  const int tid = threadIdx.x, wid = __shfl_sync(0xffffffffu, tid >> 5, 0), wg = wid >> 2, warp = wid & 3;
  int budget = SPIN_BUDGET;
  const int rank = blockIdx.x & 1;
  const uint32_t peer = mapa(sb, rank ^ 1);
  if (tid < 24) mbar_init(sb + B_FULL + 8 * tid, tid >> 3 == 1 ? 2 : 1);
  fence_mbar_init();
  if (wid == 1 && tid < 32 + sizeof(GemmMaps) / 128) asm volatile("prefetch.tensormap [%0];" :: "l"(&M.o + (tid - 32)) : "memory");
  __syncthreads();
  cluster_sync();
  const int cta = blockIdx.x, lane = lane_reg();
  if (wg >= 2) {
    reg_dec<72>();
    if (wid == 8 || wid == 10) {
      Pipe p; p.s = 0; p.ph = 1;
      for (int n = 0; ; n++) {
        if (wid == 8) e_expect_tx(sb + B_MSG + 8 * (n & 1), 4);
        mbar_wait(sb + B_MSG + 8 * (n & 1), (n >> 1) & 1, budget);
        const int msg = __shfl_sync(0xffffffffu, lds32v(sb + MSG + 4 * (n & 1)), 0);
        const int ty = (msg >> 11) & 3, l = (msg >> 10) & 1;
        const bool shb = ty == T_GU && l, spl = is_split(ty, l, (msg >> 6) & 15);
        const int cb = ((msg >> 6) & 15) + (shb ? rank : 0), j = (msg & 63) + (ty == T_END || shb ? 0 : rank);
        const int ke = ty == T_O ? 64 : ty == T_GU ? 16 : 56, k0 = spl ? rank : 0, dk = spl ? 2 : 1;
        const int c0 = ty == T_GU ? j * 64 : spl ? (j >> 1) * 128 : j * 128, c1 = ty == T_GU ? c0 : c0 + 64;
        mbar_wait(sb + B_EMPTY + 8 * p.s, p.ph, budget);
        trap_if_spent(budget);
        auto stages = [&](auto f) {
#pragma unroll 1
          for (int k = k0; k < ke; k += dk) {
            mbar_wait(sb + B_EMPTY + 8 * p.s, p.ph, budget);
            f(k, sb + p.s * STAGE_BYTES, sb + B_FULL + 8 * p.s);
            p.next();
          }
        };
        if (wid == 8) {
          const int job = ty << 11 | l << 10 | cb << 6 | j;
          sts32v(sb + JOB + 4 * (n & 1), job | p.s << 16 | (p.ph ^ 1) << 20);
          e_arrive(sb + B_JOB + 8 * (n & 1));
          if (ty == T_END) break;
          if (ty != T_GU) { e_expect_tx(sb + B_FULL + 8 * p.s, spl ? 16384 : STAGE_BYTES); p.next(); }
          const CUtensorMap* const m0 = ty == T_D ? &M.wd : shb && rank ? &M.wu : &M.wg, * const m1 = ty == T_D ? &M.wd : &M.wu;
          if (ty == T_O) stages([&](int k, uint32_t a, uint32_t fb) { e_expect_tx(fb, STAGE_BYTES); e_tma_5d(a + 16384, &M.wo, c0, k * 2, fb); e_tma_5d(a + 24576, &M.wo, c1, k * 2, fb); });
          else if (shb) stages([&](int k, uint32_t a, uint32_t fb) { e_expect_tx(fb, STAGE_BYTES); e_tma_2d_mc(a + 16384 + rank * 8192, m0, c0, k * 64, fb); });
          else stages([&](int k, uint32_t a, uint32_t fb) { e_expect_tx(fb, STAGE_BYTES); e_tma_2d(a + 16384, m0, c0, k * 64, fb); e_tma_2d(a + 24576, m1, c1, k * 64, fb); });
        } else {
          if (ty == T_END) break;
          const int row = l * SEQ + cb * 128, kt = ke + k0 - G_LOOK * dk;
          const uint64_t polA = ty != T_GU ? EVICT_FIRST : EVICT_NORMAL;
          int rdy = msg >> 16;
          auto need = [&](int k) {
            if (k == kt) e_arrive(sb + B_TRIG);
            while (k >= rdy && k >= (rdy = a_ready(ty, l, cb))) { __nanosleep(G_SLEEP); trap_if_spent(--budget); }
          };
          if (ty != T_GU) {
            need(0);
            const uint32_t a = sb + p.s * STAGE_BYTES, fb = sb + B_FULL + 8 * p.s;
            const CUtensorMap* const m = ty == T_D ? (spl ? &M.x1 : &M.x1s) : l ? (spl ? &M.x2 : &M.x2s) : &M.x;
            const int r = (ty == T_D ? row : cb * 128) + (spl ? rank * 64 : 0);
            e_tma_2d(a, m, c0, r, fb, polA); e_tma_2d(a + 16384, m, c1, r, fb, polA);
            p.next();
          }
          if (shb || spl) {
            const CUtensorMap* const ma = ty == T_O ? &M.o : ty == T_GU ? &M.xms : &M.hs;
            stages([&](int k, uint32_t a, uint32_t fb) { need(k); e_tma_2d(a, ma, k * 64, row, fb, polA); });
          } else {
            const CUtensorMap* const ma = ty == T_O ? &M.oh : ty == T_GU ? &M.xm : &M.h;
            stages([&](int k, uint32_t a, uint32_t fb) { need(k); e_tma_2d_mc(a + rank * 8192, ma, k * 64, row + rank * 64, fb, polA); });
          }
        }
      }
    } else if (wid == 9 && rank == 0) {
      uint32_t sm; asm volatile("mov.u32 %0, %%smid;" : "=r"(sm));
      const bool crowd = sm >= 124 || sm < 50;
      int d0, d1, t0, t1, pair = e_ticket(g_fl.ticket, crowd ? 1 : 256);
      auto peek = [&]() {
        d0 = ld_relaxed(g_fl.dep + lane); d1 = ld_relaxed(g_fl.dep + 32 + lane);
        t0 = ld_relaxed(g_fl.taken + lane); t1 = ld_relaxed(g_fl.taken + 32 + lane);
      };
      peek();
      {
        const int t = bcast(pair), a = t & 255, b = t >> 8, i = crowd ? a : 17 - b;
        pair = a + b >= 18 ? a + b : (int)((i < 12 ? ROLE0 >> (5 * i) : ROLE1 >> (5 * i - 60)) & 31);
      }
      int k1 = pair < 18 ? 0 : 48, skip = pair - 18;
      bool late = false;
      uint32_t wait1 = 0, wait2 = 0;
      for (int n = 0, ty = 0; ty != T_END; n++) {
        mbar_wait(sb + B_TRIG, (n & 1) ^ 1, budget);
        int l, cb, j, rdy = 64;
        while (true) {
          const int ph = k1 % 3;
          const bool gap = pair < 8 ? ph == 1 : pair >= 16 && ph == 2;
          if (k1 < 48) {
            cb = k1++ / 3;
            if (gap && (late || !(G_FILL & (pair < 8 ? 1 : 2)))) continue;
            if (!gap) {
              l = 0;
              ty = pair < 8 ? (ph ? T_GU : T_O) : ph == 2 ? T_D : T_GU;
              j = 2 * (pair < 8 ? (ph ? pair + 10 : pair) : ph == 1 ? pair + 10 : pair - 8);
              rdy = a_ready(ty, 0, cb);
              if (ph == 0) late = rdy != 0;
              break;
            }
          }
          if (skip < 0) peek();
          const bool l0 = t0 < (lane < 16 ? (is_split(T_O, 1, lane) ? 8 : 4) : lane & 1 ? 0 : 56), l1 = lane < 16 && t1 < (lane < G_DS ? 4 : 8);
          const uint32_t rd = __ballot_sync(0xffffffffu, d0 >= (lane < 16 ? 256 : 128));
          uint32_t ok0 = __ballot_sync(0xffffffffu, l0) & rd & (rd >> 1 | 0xffff), ok1 = __ballot_sync(0xffffffffu, l1 && h_ready(d1) > 0);
          if (gap) { ok1 = 0; ok0 &= 0xffff0000u | (pair < 16 ? G_BOOT : (1u << G_O0) - 1); }
          ok0 &= ~wait2;
          ty = T_END; l = 1; cb = j = 0;
          if (!gap && !__any_sync(0xffffffffu, l0 || l1)) break;
          if (ok1 & ((1u << G_DS) - 1)) ok1 &= (1u << G_DS) - 1;
          const uint32_t dfirst = ok1 & __ballot_sync(0xffffffffu, lane < G_DF && d1 == 0x10141014);
          if (dfirst && !(ok0 & 0xffff)) { ok0 = 0; ok1 = dfirst; }
          else if (__any_sync(0xffffffffu, l0)) ok1 &= (1u << G_DE) - 1;
          else if (!ok1 && !gap) ok1 = __ballot_sync(0xffffffffu, l1);
          uint32_t m = ok0 ? ok0 : ok1;
          if (!m && !gap) __nanosleep(100);
          while (m) {
            const int nth = ok0 ? 0 : pair % __popc(m);
            const int b = __ffs(__ballot_sync(0xffffffffu, __popc(m << (31 - lane)) > nth)) - 1, gn = b + (ok0 ? 0 : 32);
            const int sz = gn >> 4 == T_GU ? 56 : is_split(gn >> 4, 1, gn & 15) ? 8 : 4;
            m &= ~(1u << b);
            if (skip >= 0 && m && (skip -= sz - __shfl_sync(0xffffffffu, ok0 ? t0 : t1, b)) >= 0) continue;
            int t = e_ticket(g_fl.taken + gn);
            rdy = a_ready(gn >> 4, 1, gn & 15);
            t = bcast(t);
            if (t < sz) { ty = gn >> 4; cb = gn & 15; j = sz == 56 ? t : 2 * t; break; }
          }
          skip = -1;
          if (ty != T_END) break;
          trap_if_spent(--budget);
        }
        wait2 = wait1;
        wait1 = ty == T_O && l && cb >= G_FL ? (2u << cb) - (1u << G_FL) : 0;
        const int msg = rdy << 16 | ty << 11 | l << 10 | cb << 6 | j;
        e_st_async32(peer + MSG + 4 * (n & 1), msg, peer + B_MSG + 8 * (n & 1));
        e_st_async32(sb + MSG + 4 * (n & 1), msg, sb + B_MSG + 8 * (n & 1));
      }
    } else if (wg == 3) {
      bool open = lane < G_FL && ld_relaxed(g_fl.rows + lane) < 128;
      while (__any_sync(0xffffffffu, open)) {
        int v = 0;
        if (open) asm volatile("ld.acquire.gpu.global.s32 %0, [%1];" : "=r"(v) : "l"(g_fl.part + lane) : "memory");
        const uint32_t ok = __ballot_sync(0xffffffffu, open && v >= 128);
        if (!ok) {
          if (--budget <= 0) break;
          __nanosleep(G_SLEEP2);
          continue;
        }
        const int cb = __ffs(__ballot_sync(0xffffffffu, __popc(ok << (31 - lane)) > (cta >> 5) % __popc(ok))) - 1;
        const int r = bcast(e_ticket(g_fl.rows + cb));
        if (r >= 128) { open = open && lane != cb; continue; }
        uint4 u[4];
#pragma unroll
        for (int i = 0; i < 4; i++) u[i] = ldg_rlx128((const uint4*)(g_x1[1] + (size_t)(cb * 128 + r) * DM) + i * 32 + lane);
        ln_row(u, g_xm[1] + (size_t)(cb * 128 + r) * DM, lane);
        __syncwarp();
        e_flag_add(g_fl.dep + grp(T_GU, 1, cb));
      }
      if (cta == 0 && wid == 12) {
        asm volatile("griddepcontrol.wait;" ::: "memory");
        g_fl.xn[lane >> 4][lane & 15][0] = 0;
      }
    }
    cluster_sync();
  } else {
    reg_inc<184>();
    const bool lead = warp == 0;
    const uint32_t eb = (warp == 1 ? peer : sb) + B_EMPTY;
    const int rl = warp < 2 ? 0 : -1;
    const uint32_t so = sb + SO + wg * 16384;
    const int r0 = warp * 16 + (lane & 7) + ((lane >> 3) & 1) * 8;
    const uint32_t sw = r0 * 128 + (((lane >> 4) ^ (r0 & 7)) << 4);
    int xph = 0;
    for (int n = wg; ; n += 2) {
      float d0[64], d1[64];
      mbar_wait(sb + B_JOB + 8 * wg, (n >> 1) & 1, budget);
      fault_if_spent(budget);
      const int job = __shfl_sync(0xffffffffu, lds32v(sb + JOB + 4 * wg), 0);
      const int ty = (job >> 11) & 3, l = (job >> 10) & 1, cb = (job >> 6) & 15, j = job & 63;
      if (ty == T_END) {
        if (n > 0) nbar_sync_r(1 + wg, 256);
        if (lead && !(job & 1)) { sts32v(sb + JOB + 4 * (wg ^ 1), job | 1); e_arrive(sb + B_JOB + 8 * (wg ^ 1)); }
        if (!(job & 1)) nbar_arrive_r(1 + (wg ^ 1), 256);
        break;
      }
      Pipe q; q.s = (job >> 16) & 15; q.ph = job >> 20;
      const bool spl = is_split(ty, l, cb);
      if (ty != T_GU) mbar_wait(sb + B_FULL + 8 * q.s, q.ph, budget);
#pragma unroll
      for (int m = 0; m < 2; m++) {
        float* d = m ? d1 : d0;
        if (ty != T_GU && !(m && spl)) {
#pragma unroll
          for (int c = 0; c < 8; c++) {
            uint32_t r[4];
            ldsm4(sb + q.s * STAGE_BYTES + (c >> 2) * 16384 + m * 8192 + (sw ^ ((c & 3) << 5)), r[0], r[1], r[2], r[3]);
#pragma unroll
            for (int i = 0; i < 4; i++) { d[8*c+2*i] = bf_lo(r[i]); d[8*c+2*i+1] = bf_hi(r[i]); }
          }
        } else {
#pragma unroll
          for (int i = 0; i < 64; i++) d[i] = 0.f;
        }
      }
      if (ty != T_GU) {
        fence_proxy_async();
        nbar_sync_r(3 + wg, 128);
        arrive_cl_if_eq(eb + 8 * q.s, lane, rl);
        q.next();
      }
      pin<64>(d0); pin<64>(d1);
      if (n > 0) nbar_sync_r(1 + wg, 256);
      const int nk = (ty == T_O ? 64 : ty == T_GU ? 16 : 56) >> spl;
      const uint32_t ro = spl ? rank * 512 : 0;
      int prev = 0;
      for (int i = 0; i < nk; i++) {
        mbar_wait(sb + B_FULL + 8 * q.s, q.ph, budget);
        const uint32_t da = desc_base(sb) + q.s * (STAGE_BYTES / 16);
        wg_fence();
        sfor<0, 4>([&](auto K) {
          constexpr int k = K;
          typedef Op<16384 + k * 2048, 8192, 1024, 1, 1> OB;
          wg_ss128<1, Op<k * 32, 16, 1024, 1, 0>, OB>(d0, da + ro, da);
          wg_ss128<1, Op<8192 + k * 32, 16, 1024, 1, 0>, OB>(d1, da - ro, da);
        });
        wg_commit();
        wg_wait<1>();
        arrive_cl_if_eq(eb + 8 * prev, lane, i ? rl : -1);
        prev = q.s;
        q.next();
      }
      nbar_arrive_r(1 + (wg ^ 1), 256);
      wg_wait<0>();
      pin<64>(d0); pin<64>(d1);
      arrive_cl_if_eq(eb + 8 * prev, lane, rl);
      if (spl) {
        const uint32_t xa = SO + wg * 16384 + warp * 512 + lane * 16;
        if (lead) e_expect_tx(sb + B_XF + 8 * wg, 16384);
        mbar_wait(sb + B_SF + 8 * wg, ((n >> 1) & 1) ^ 1, budget);
#pragma unroll
        for (int i = 0; i < 8; i++) {
          const float* d = d1 + 8 * i;
          st_async128(peer + xa + i * 2048, pack_bf16(d[0], d[1]), pack_bf16(d[2], d[3]), pack_bf16(d[4], d[5]), pack_bf16(d[6], d[7]), peer + B_XF + 8 * wg);
        }
        mbar_wait(sb + B_XF + 8 * wg, xph, budget);
        xph ^= 1;
        uint32_t y[32];
#pragma unroll
        for (int i = 0; i < 8; i++) {
          const float* d = d0 + 8 * i;
          const uint4 v = lds128(sb + xa + i * 2048);
          y[4*i] = pack_bf16(d[0] + bf_lo(v.x), d[1] + bf_hi(v.x)); y[4*i+1] = pack_bf16(d[2] + bf_lo(v.y), d[3] + bf_hi(v.y));
          y[4*i+2] = pack_bf16(d[4] + bf_lo(v.z), d[5] + bf_hi(v.z)); y[4*i+3] = pack_bf16(d[6] + bf_lo(v.w), d[7] + bf_hi(v.w));
        }
        const bool fuse = !l || (ty == T_O && cb >= G_FL);
        float2* const st = &g_stat[l ? 4 + (cb & 7) : ty + (cb & 1)][0][rank * 64 + warp * 16 + (lane >> 2) * 2];
        if (fuse) {
          float mn[2], sq[2];
#pragma unroll
          for (int z = 0; z < 2; z++) {
            float m = 0, s2 = 0;
#pragma unroll
            for (int i = 0; i < 16; i++) m += bf_lo(y[2*i+z]) + bf_hi(y[2*i+z]);
            m += __shfl_xor_sync(0xffffffffu, m, 1); m += __shfl_xor_sync(0xffffffffu, m, 2);
            m *= 1.f / 128;
#pragma unroll
            for (int i = 0; i < 16; i++) { const float a = bf_lo(y[2*i+z]) - m, b = bf_hi(y[2*i+z]) - m; s2 = fmaf(a, a, fmaf(b, b, s2)); }
            s2 += __shfl_xor_sync(0xffffffffu, s2, 1); s2 += __shfl_xor_sync(0xffffffffu, s2, 2);
            mn[z] = m; sq[z] = s2;
          }
          if ((lane & 3) == 0) stg_rlx128(st + (j >> 1) * 128, __float_as_uint(mn[0]), (__float_as_uint(sq[0]) & ~31u) | (cb + 1), __float_as_uint(mn[1]), __float_as_uint(sq[1]));
          __syncwarp();
        }
        const int row = (ty == T_O ? l * SEQ : 0) + cb * 128 + rank * 64;
        auto put = [&](const CUtensorMap* mo, auto f) {
          nbar_sync_r(3 + wg, 128);
#pragma unroll
          for (int c = 0; c < 8; c++) stsm4(so + (c >> 2) * 8192 + (sw ^ ((c & 3) << 5)), f(4*c), f(4*c+1), f(4*c+2), f(4*c+3));
          fence_proxy_async();
          nbar_sync_r(3 + wg, 128);
          if (lead) { e_tma_store_2d(mo, so, (j >> 1) * 128, row); e_tma_store_2d(mo, so + 8192, (j >> 1) * 128 + 64, row); bulk_commit(); }
        };
        if (fuse) {
          uint4 u[2];
          while (true) {
            __nanosleep(G_SLEEP3);
            u[0] = ldg_rlx128(st + (lane & 3) * 256); u[1] = ldg_rlx128(st + (lane & 3) * 256 + 128);
            if (!__any_sync(0xffffffffu, ((u[0].y ^ (cb + 1)) | (u[1].y ^ (cb + 1))) & 31) || --budget <= 0) break;
          }
          float rs[2], mr[2];
#pragma unroll
          for (int z = 0; z < 2; z++) {
            const float ma = __uint_as_float(z ? u[0].z : u[0].x), mb = __uint_as_float(z ? u[1].z : u[1].x);
            float m = ma + mb;
            m += __shfl_xor_sync(0xffffffffu, m, 1); m += __shfl_xor_sync(0xffffffffu, m, 2);
            m *= 0.125f;
            float s2 = __uint_as_float(z ? u[0].w : u[0].y & ~31u) + __uint_as_float(z ? u[1].w : u[1].y & ~31u) + 128.f * ((ma - m) * (ma - m) + (mb - m) * (mb - m));
            s2 += __shfl_xor_sync(0xffffffffu, s2, 1); s2 += __shfl_xor_sync(0xffffffffu, s2, 2);
            rs[z] = rsqrtf(s2 * (1.f / DM) + 1e-5f); mr[z] = -m * rs[z];
          }
          put(ty == T_O ? &M.xm : &M.xn, [&](int i) { return pack_bf16(fmaf(bf_lo(y[i]), rs[i & 1], mr[i & 1]), fmaf(bf_hi(y[i]), rs[i & 1], mr[i & 1])); });
          if (lead) {
            bulk_wait<0>();
            e_flag_add_bulk(ty == T_D ? g_fl.xn[1][cb] : g_fl.dep + grp(T_GU, l, cb), 8);
          }
        }
        put(ty == T_O ? &M.x1 : l ? &M.out : &M.x2, [&](int i) { return y[i]; });
      } else {
        if (ty == T_GU) {
#pragma unroll
          for (int i = 0; i < 32; i++) { d0[i] = geglu(d0[i], d0[32 + i]); d1[i] = geglu(d1[i], d1[32 + i]); }
        }
#pragma unroll
        for (int hf = 0; hf < 2; hf++) {
          if (hf) {
            if (ty == T_GU) break;
            if (lead) bulk_wait_read<0>();
            nbar_sync_r(3 + wg, 128);
          }
#pragma unroll
          for (int m = 0; m < 2; m++)
#pragma unroll
            for (int c = 0; c < 4; c++) {
              const float* d = (m ? d1 : d0) + 32 * hf + 8 * c;
              stsm4(so + m * 8192 + (sw ^ (c << 5)), pack_bf16(d[0], d[1]), pack_bf16(d[2], d[3]), pack_bf16(d[4], d[5]), pack_bf16(d[6], d[7]));
            }
          fence_proxy_async();
          nbar_sync_r(3 + wg, 128);
          if (lead) {
            if (ty == T_GU) e_tma_store_2d(&M.hs, so, j * 64, l * SEQ + cb * 128); else e_tma_store_2d(ty == T_O ? &M.x1s : &M.outs, so, j * 128 + hf * 64, (ty == T_O ? SEQ : 0) + cb * 128);
            bulk_commit();
          }
        }
      }
      if (lead) {
        bulk_wait<0>();
        e_arrive_cl(peer + B_SF + 8 * wg);
        if (ty == T_GU) e_flag_add_bulk(g_fl.dep + grp(T_D, l, cb), j < 20 ? 1 : j < 36 ? 1 << 8 : 1 << 16);
        else if (ty == T_O) { e_flag_add_bulk(g_fl.dep + grp(T_D, l, cb), (2 << 24) >> spl); if (l && cb < G_FL) e_flag_add_bulk(g_fl.part + cb, 16 >> spl); }
        else if (!l) e_flag_add_bulk(g_fl.dep + grp(T_O, 1, cb), 8);
      }
    }
    cluster_sync();
  }
}

typedef CUresult (*PFN_encodeTiled)(CUtensorMap*, CUtensorMapDataType, cuuint32_t, void*, const cuuint64_t*, const cuuint64_t*,
                                    const cuuint32_t*, const cuuint32_t*, CUtensorMapInterleave, CUtensorMapSwizzle,
                                    CUtensorMapL2promotion, CUtensorMapFloatOOBfill);
static PFN_encodeTiled g_encode = nullptr;
static int g_sms = 0;
static CUtensorMap encode(const void* ptr, int rank, const cuuint64_t* dims, const cuuint64_t* strides, const cuuint32_t* box) {
  CUtensorMap m;
  const cuuint32_t es[5] = {1, 1, 1, 1, 1};
  g_encode(&m, CU_TENSOR_MAP_DATA_TYPE_BFLOAT16, rank, (void*)ptr, dims, strides, box, es, CU_TENSOR_MAP_INTERLEAVE_NONE,
           CU_TENSOR_MAP_SWIZZLE_128B, CU_TENSOR_MAP_L2_PROMOTION_L2_256B, CU_TENSOR_MAP_FLOAT_OOB_FILL_NONE);
  return m;
}
static CUtensorMap make_map(const void* ptr, uint64_t rows, uint64_t cols, uint32_t box_rows) {
  const cuuint64_t dims[2] = {cols, rows}, strides[1] = {cols * 2};
  const cuuint32_t box[2] = {64, box_rows};
  return encode(ptr, 2, dims, strides, box);
}
static CUtensorMap make_map_x(const void* ptr) {
  const cuuint64_t dims[3] = {DM, NSTEP * 32, 2}, strides[2] = {DM * 2, (cuuint64_t)NSTEP * 32 * DM * 2};
  const cuuint32_t box[3] = {64, 32, 2};
  return encode(ptr, 3, dims, strides, box);
}
static CUtensorMap make_map_x1(const void* ptr) {
  const cuuint64_t dims[3] = {64, 2 * NSTEP * 32, DM / 64}, strides[2] = {DM * 2, 128};
  const cuuint32_t box[3] = {64, 32, 2};
  return encode(ptr, 3, dims, strides, box);
}
static CUtensorMap make_map_wo(const void* ptr) {
  const cuuint64_t dims[5] = {DM, 2, 4, 4, NH * DH / 32}, strides[4] = {DM * 2, 8 * DM * 2, 2 * DM * 2, 32 * DM * 2};
  const cuuint32_t box[5] = {64, 2, 4, 4, 2};
  return encode(ptr, 5, dims, strides, box);
}

extern "C" void kernel_launch(void* const* d_in, const int* in_sizes, int n_in, void* d_out, int out_size) {
  const bf16 *x = (const bf16*)d_in[0], *mem0 = (const bf16*)d_in[1], *Wo = (const bf16*)d_in[5];
  if (!g_encode) {
    void* p = nullptr; cudaDriverEntryPointQueryResult q;
    cudaGetDriverEntryPoint("cuTensorMapEncodeTiled", &p, cudaEnableDefault, &q);
    g_encode = (PFN_encodeTiled)p;
    int dev = 0;
    cudaGetDevice(&dev);
    cudaDeviceGetAttribute(&g_sms, cudaDevAttrMultiProcessorCount, dev);
    cudaFuncSetAttribute(rec_kernel, cudaFuncAttributeMaxDynamicSharedMemorySize, rec::SMEM);
    cudaFuncSetAttribute(gemm_kernel, cudaFuncAttributeMaxDynamicSharedMemorySize, gm::SMEM);
  }
  void *xn, *o, *x1, *xm, *x2, *hh;
  cudaGetSymbolAddress(&xn, g_xn); cudaGetSymbolAddress(&o, g_o); cudaGetSymbolAddress(&x1, g_x1);
  cudaGetSymbolAddress(&xm, g_xm); cudaGetSymbolAddress(&x2, g_x2); cudaGetSymbolAddress(&hh, g_h);
  RecMaps R;
  for (int i = 0; i < 3; i++) R.w[i] = make_map(d_in[2 + i], DM, NH * DH, 16);
  R.wo = make_map(Wo, NH * DH, DM, 64); R.x[0] = make_map_x(xn); R.x[1] = make_map_x1(xn);
  rec_kernel<<<96, 512, rec::SMEM>>>(R, Wo, mem0, x, 0);
  GemmMaps G;
  G.o = make_map(o, 2 * SEQ, NH * DH, 128); G.oh = make_map(o, 2 * SEQ, NH * DH, 64); G.wo = make_map_wo(Wo);
  G.x1 = make_map(x1, 2 * SEQ, DM, 64); G.x1s = make_map(x1, 2 * SEQ, DM, 128);
  G.xn = make_map((bf16*)xn + (NSTEP + LAG) * 32 * DM, SEQ, DM, 64);
  G.xm = make_map(xm, 2 * SEQ, DM, 64); G.xms = make_map(xm, 2 * SEQ, DM, 128);
  G.wg = make_map(d_in[8], DM, DF, 64); G.wu = make_map(d_in[9], DM, DF, 64); G.wd = make_map(d_in[10], DF, DM, 64);
  G.h = make_map(hh, 2 * SEQ, DF, 64); G.hs = make_map(hh, 2 * SEQ, DF, 128);
  G.x = make_map(x, SEQ, DM, 64); G.x2 = make_map(x2, SEQ, DM, 64); G.x2s = make_map(x2, SEQ, DM, 128);
  G.out = make_map(d_out, SEQ, DM, 64); G.outs = make_map(d_out, SEQ, DM, 128);
  cudaLaunchConfig_t cfg = {};
  cfg.gridDim = dim3(g_sms & ~1); cfg.blockDim = dim3(512); cfg.dynamicSmemBytes = gm::SMEM; cfg.stream = cudaStreamPerThread;
  cudaLaunchAttribute at;
  at.id = cudaLaunchAttributeProgrammaticStreamSerialization; at.val.programmaticStreamSerializationAllowed = 1;
  cfg.attrs = &at; cfg.numAttrs = 1;
  cudaLaunchKernelEx(&cfg, gemm_kernel, G);
}
```

```cpp
#include <cuda_runtime.h>
#include <cuda_bf16.h>
#include <cuda.h>
#include <stdint.h>

#define DEVI __device__ __forceinline__
typedef __nv_bfloat16 bf16;

#define LAG 14
constexpr int SEQ = 2048, DM = 1024, NH = 32, DH = 128, DF = 3584, NSEG = 64, NSTEP = NSEG + LAG;

__device__ __align__(1024) bf16 g_xn[2][NSTEP * 32 * DM];
__device__ __align__(1024) bf16 g_o[2][SEQ * NH * DH];
__device__ __align__(1024) bf16 g_x1[2][SEQ * DM];
__device__ __align__(1024) bf16 g_xm[2][SEQ * DM];
__device__ __align__(1024) bf16 g_x2[SEQ * DM];
__device__ __align__(1024) bf16 g_h[2][SEQ * DF];
__device__ __align__(1024) uint4 g_part[256 * 32 * 8];
__device__ __align__(1024) uint32_t g_ann[2][32][64];
__device__ __align__(1024) uint4 g_mem[2][2048];
__device__ __align__(128) float2 g_stat[12][8][128];
__host__ __device__ constexpr int grp(int type, int layer, int blk) { return layer ? 16 * type + blk : 64 + (16 * type + blk) * 32; }
struct Flags {
  int xn[2][16][32];
  int dep[64 + 48 * 32];
  int taken[64];
  int rows[32];
  int part[32];
  int ticket[32];
};
__device__ __align__(128) Flags g_fl;

DEVI uint32_t smem_u32(const void* p) { return (uint32_t)__cvta_generic_to_shared(p); }
DEVI void mbar_init(uint32_t bar, uint32_t cnt) { asm volatile("mbarrier.init.shared::cta.b64 [%0], %1;" :: "r"(bar), "r"(cnt) : "memory"); }
DEVI void mbar_arrive(uint32_t bar) { asm volatile("mbarrier.arrive.shared::cta.b64 _, [%0];" :: "r"(bar) : "memory"); }
DEVI bool mbar_try(uint32_t bar, uint32_t parity) {
  uint32_t p;
  asm volatile("{.reg .pred p; mbarrier.try_wait.parity.shared::cta.b64 p, [%1], %2; selp.u32 %0, 1, 0, p;}" : "=r"(p) : "r"(bar), "r"(parity) : "memory");
  return p;
}
constexpr int SPIN_BUDGET = 1 << 20;
DEVI void mbar_wait(uint32_t bar, uint32_t parity, int& budget) {
  while (!mbar_try(bar, parity)) { if (--budget < 0) break; }
}
DEVI void trap_if_spent(int budget) { asm volatile("{.reg .pred p; setp.le.s32 p, %0, 0; @p trap;}" :: "r"(budget) : "memory"); }
DEVI void fault_if_spent(int budget) { asm volatile("{.reg .pred p; setp.le.s32 p, %0, 0; @p st.global.u32 [%1], 0;}" :: "r"(budget), "l"(0ull) : "memory"); }
DEVI uint32_t mapa(uint32_t addr, uint32_t rank) { uint32_t r; asm("mapa.shared::cluster.u32 %0, %1, %2;" : "=r"(r) : "r"(addr), "r"(rank)); return r; }
DEVI void cluster_sync() { asm volatile("barrier.cluster.arrive.relaxed.aligned; barrier.cluster.wait.aligned;" ::: "memory"); }
DEVI void fence_mbar_init() { asm volatile("fence.mbarrier_init.release.cluster;" ::: "memory"); }
DEVI void fence_proxy_async() { asm volatile("fence.proxy.async.shared::cta;" ::: "memory"); }
DEVI void tma_load_2d(uint32_t dst, const CUtensorMap* m, int c0, int c1, uint32_t bar) {
  asm volatile("cp.async.bulk.tensor.2d.shared::cluster.global.mbarrier::complete_tx::bytes [%0], [%1, {%3, %4}], [%2];"
    :: "r"(dst), "l"(m), "r"(bar), "r"(c0), "r"(c1) : "memory");
}
DEVI void tma_prefetch_2d(const CUtensorMap* m, int c0, int c1) {
  asm volatile("cp.async.bulk.prefetch.tensor.2d.L2.global [%0, {%1, %2}];" :: "l"(m), "r"(c0), "r"(c1) : "memory");
}
#define ELECT "{.reg .pred p; elect.sync _|p, 0xffffffff;\n @p "
DEVI void e_expect_tx(uint32_t bar, uint32_t bytes) { asm volatile(ELECT "mbarrier.arrive.expect_tx.shared::cta.b64 _, [%0], %1;}" :: "r"(bar), "r"(bytes) : "memory"); }
DEVI void e_arrive(uint32_t bar) { asm volatile(ELECT "mbarrier.arrive.shared::cta.b64 _, [%0];}" :: "r"(bar) : "memory"); }
DEVI void e_arrive_cl(uint32_t bar) { asm volatile(ELECT "mbarrier.arrive.shared::cluster.b64 _, [%0];}" :: "r"(bar) : "memory"); }
constexpr uint64_t EVICT_NORMAL = 0x1000000000000000ull, EVICT_FIRST = 0x12F0000000000000ull;
DEVI void e_tma_2d(uint32_t dst, const CUtensorMap* m, int c0, int c1, uint32_t bar, uint64_t pol = EVICT_NORMAL) {
  asm volatile(ELECT "cp.async.bulk.tensor.2d.shared::cluster.global.mbarrier::complete_tx::bytes.L2::cache_hint [%0], [%1, {%3, %4}], [%2], %5;}"
    :: "r"(dst), "l"(m), "r"(bar), "r"(c0), "r"(c1), "l"(pol) : "memory");
}
DEVI void e_tma_2d_mc(uint32_t dst, const CUtensorMap* m, int c0, int c1, uint32_t bar, uint64_t pol = EVICT_NORMAL) {
  asm volatile(ELECT "cp.async.bulk.tensor.2d.shared::cluster.global.mbarrier::complete_tx::bytes.multicast::cluster.L2::cache_hint [%0], [%1, {%3, %4}], [%2], %5, %6;}"
    :: "r"(dst), "l"(m), "r"(bar), "r"(c0), "r"(c1), "h"((unsigned short)3), "l"(pol) : "memory");
}
DEVI void e_st_async32(uint32_t a, uint32_t x, uint32_t bar) {
  asm volatile(ELECT "st.async.weak.shared::cluster.mbarrier::complete_tx::bytes.b32 [%0], %1, [%2];}" :: "r"(a), "r"(x), "r"(bar) : "memory");
}
DEVI void e_tma_store_2d(const CUtensorMap* m, uint32_t src, int c0, int c1) {
  asm volatile(ELECT "cp.async.bulk.tensor.2d.global.shared::cta.bulk_group [%0, {%2, %3}], [%1];}" :: "l"(m), "r"(src), "r"(c0), "r"(c1) : "memory");
}
DEVI void e_flag_add(int* p, int v = 1) {
  asm volatile("{.reg .pred p; elect.sync _|p, 0xffffffff;\n fence.proxy.async.global; @p red.release.gpu.global.add.s32 [%0], %1;}" :: "l"(p), "r"(v) : "memory");
}
DEVI void e_flag_add_bulk(int* p, int v) {
  asm volatile(ELECT "red.relaxed.gpu.global.add.s32 [%0], %1;}" :: "l"(p), "r"(v) : "memory");
}
DEVI int e_ticket(int* p, int n = 1) { int v = 0; asm volatile(ELECT "atom.relaxed.gpu.global.add.s32 %0, [%1], %2;}" : "+r"(v) : "l"(p), "r"(n) : "memory"); __syncwarp(); return v; }
DEVI int bcast(int v) { return __reduce_max_sync(0xffffffffu, v); }
DEVI int ld_relaxed(const int* p) { int v; asm volatile("ld.relaxed.gpu.global.s32 %0, [%1];" : "=r"(v) : "l"(p) : "memory"); return v; }
DEVI int ld_acquire(const int* p) { int v; asm volatile("ld.acquire.gpu.global.s32 %0, [%1];" : "=r"(v) : "l"(p) : "memory"); return __shfl_sync(0xffffffffu, v, 0); }
DEVI void e_tma_3d(uint32_t dst, const CUtensorMap* m, int c0, int c1, int c2, uint32_t bar) {
  asm volatile(ELECT "cp.async.bulk.tensor.3d.shared::cluster.global.mbarrier::complete_tx::bytes [%0], [%1, {%3, %4, %5}], [%2];}"
    :: "r"(dst), "l"(m), "r"(bar), "r"(c0), "r"(c1), "r"(c2) : "memory");
}
DEVI void e_tma_5d(uint32_t dst, const CUtensorMap* m, int c0, int c4, uint32_t bar) {
  asm volatile(ELECT "cp.async.bulk.tensor.5d.shared::cluster.global.mbarrier::complete_tx::bytes [%0], [%1, {%3, %5, %5, %5, %4}], [%2];}"
    :: "r"(dst), "l"(m), "r"(bar), "r"(c0), "r"(c4), "r"(0) : "memory");
}
DEVI void e_bulk_g2s(uint32_t dst, const void* src, uint32_t bytes, uint32_t bar) {
  asm volatile(ELECT "cp.async.bulk.shared::cluster.global.mbarrier::complete_tx::bytes [%0], [%1], %2, [%3];}" :: "r"(dst), "l"(src), "r"(bytes), "r"(bar) : "memory");
}
DEVI void e_prefetch(const void* src, uint32_t bytes) {
  asm volatile(ELECT "cp.async.bulk.prefetch.L2.global [%0], %1;}" :: "l"(src), "r"(bytes) : "memory");
}
DEVI void bulk_commit() { asm volatile("cp.async.bulk.commit_group;" ::: "memory"); }
template<int N> DEVI void bulk_wait_read() { asm volatile("cp.async.bulk.wait_group.read %0;" :: "n"(N) : "memory"); }
template<int N> DEVI void bulk_wait() { asm volatile("cp.async.bulk.wait_group %0;" :: "n"(N) : "memory"); }
template<int ID, int N> DEVI void nbar_sync() { asm volatile("bar.sync %0, %1;" :: "n"(ID), "n"(N) : "memory"); }
template<int ID, int N> DEVI void nbar_arrive() { asm volatile("bar.arrive %0, %1;" :: "n"(ID), "n"(N) : "memory"); }
DEVI void nbar_sync_r(int id, int n) { asm volatile("bar.sync %0, %1;" :: "r"(id), "r"(n) : "memory"); }
DEVI void nbar_arrive_r(int id, int n) { asm volatile("bar.arrive %0, %1;" :: "r"(id), "r"(n) : "memory"); }
template<int R> DEVI void reg_inc() { asm volatile("setmaxnreg.inc.sync.aligned.u32 %0;" :: "n"(R)); }
template<int R> DEVI void reg_dec() { asm volatile("setmaxnreg.dec.sync.aligned.u32 %0;" :: "n"(R)); }
DEVI void wg_fence() { asm volatile("wgmma.fence.sync.aligned;" ::: "memory"); }
DEVI void wg_commit() { asm volatile("wgmma.commit_group.sync.aligned;" ::: "memory"); }
template<int N> DEVI void wg_wait() { asm volatile("wgmma.wait_group.sync.aligned %0;" :: "n"(N) : "memory"); }
DEVI uint32_t pack_bf16(float lo, float hi) { uint32_t r; asm("cvt.rn.bf16x2.f32 %0, %1, %2;" : "=r"(r) : "f"(hi), "f"(lo)); return r; }
DEVI float bf_lo(uint32_t v) { return __uint_as_float(v << 16); }
DEVI float bf_hi(uint32_t v) { return __uint_as_float(v & 0xffff0000u); }
DEVI void ldsm4(uint32_t addr, uint32_t& r0, uint32_t& r1, uint32_t& r2, uint32_t& r3) {
  asm volatile("ldmatrix.sync.aligned.m8n8.x4.shared.b16 {%0,%1,%2,%3}, [%4];" : "=r"(r0), "=r"(r1), "=r"(r2), "=r"(r3) : "r"(addr) : "memory");
}
DEVI void ldsm4t(uint32_t addr, uint32_t& r0, uint32_t& r1, uint32_t& r2, uint32_t& r3) {
  asm volatile("ldmatrix.sync.aligned.m8n8.x4.trans.shared.b16 {%0,%1,%2,%3}, [%4];" : "=r"(r0), "=r"(r1), "=r"(r2), "=r"(r3) : "r"(addr) : "memory");
}
DEVI void stsm4(uint32_t addr, uint32_t r0, uint32_t r1, uint32_t r2, uint32_t r3) {
  asm volatile("stmatrix.sync.aligned.m8n8.x4.shared.b16 [%0], {%1,%2,%3,%4};" :: "r"(addr), "r"(r0), "r"(r1), "r"(r2), "r"(r3) : "memory");
}
DEVI uint4 lds128(uint32_t a) { uint4 v; asm volatile("ld.shared.v4.u32 {%0,%1,%2,%3}, [%4];" : "=r"(v.x), "=r"(v.y), "=r"(v.z), "=r"(v.w) : "r"(a) : "memory"); return v; }
DEVI uint32_t lds32v(uint32_t a) { uint32_t v; asm volatile("ld.volatile.shared.u32 %0, [%1];" : "=r"(v) : "r"(a) : "memory"); return v; }
DEVI void sts32v(uint32_t a, uint32_t v) { asm volatile("st.volatile.shared.u32 [%0], %1;" :: "r"(a), "r"(v) : "memory"); }
DEVI void st_async128(uint32_t a, uint32_t x, uint32_t y, uint32_t z, uint32_t w, uint32_t bar) {
  asm volatile("st.async.weak.shared::cluster.mbarrier::complete_tx::bytes.v4.b32 [%0], {%1,%2,%3,%4}, [%5];" :: "r"(a), "r"(x), "r"(y), "r"(z), "r"(w), "r"(bar) : "memory");
}
DEVI void st_async32(uint32_t a, uint32_t x, uint32_t bar) {
  asm volatile("st.async.weak.shared::cluster.mbarrier::complete_tx::bytes.b32 [%0], %1, [%2];" :: "r"(a), "r"(x), "r"(bar) : "memory");
}
DEVI void st_cl128(bool own, uint32_t a, uint32_t x, uint32_t y, uint32_t z, uint32_t w, uint32_t bar) {
  asm volatile("{.reg .pred p; setp.ne.u32 p, %6, 0; @p st.shared.v4.b32 [%0], {%1,%2,%3,%4};\n"
               "@!p st.async.weak.shared::cluster.mbarrier::complete_tx::bytes.v4.b32 [%0], {%1,%2,%3,%4}, [%5];}"
               :: "r"(a), "r"(x), "r"(y), "r"(z), "r"(w), "r"(bar), "r"((uint32_t)own) : "memory");
}
DEVI uint4 ldg_rlx128(const void* p) {
  uint4 v;
  asm volatile("ld.relaxed.gpu.global.v4.b32 {%0,%1,%2,%3}, [%4];" : "=r"(v.x), "=r"(v.y), "=r"(v.z), "=r"(v.w) : "l"(p) : "memory");
  return v;
}
DEVI void stg_rlx128(void* p, uint32_t x, uint32_t y, uint32_t z, uint32_t w) {
  asm volatile("st.relaxed.gpu.global.v4.b32 [%0], {%1,%2,%3,%4};" :: "l"(p), "r"(x), "r"(y), "r"(z), "r"(w) : "memory");
}
DEVI void stg128(void* p, uint32_t x, uint32_t y, uint32_t z, uint32_t w) {
  asm volatile("st.global.v4.b32 [%0], {%1,%2,%3,%4};" :: "l"(p), "r"(x), "r"(y), "r"(z), "r"(w) : "memory");
}
DEVI void stg_rlx32(void* p, uint32_t x) { asm volatile("st.relaxed.gpu.global.b32 [%0], %1;" :: "l"(p), "r"(x) : "memory"); }
DEVI uint32_t clock32() { uint32_t c; asm volatile("mov.u32 %0, %%clock;" : "=r"(c) :: "memory"); return c; }
DEVI uint32_t gtime() { uint32_t c; asm volatile("mov.u32 %0, %%globaltimer_lo;" : "=r"(c) :: "memory"); return c; }
DEVI void wait_time(uint32_t t, int& budget) { while ((int)(gtime() - t) < 0 && --budget > 0) {} }
DEVI uint2 ldg_rlx64(const void* p) { uint2 v; asm volatile("ld.relaxed.gpu.global.v2.b32 {%0,%1}, [%2];" : "=r"(v.x), "=r"(v.y) : "l"(p) : "memory"); return v; }
DEVI void sts16(uint32_t a, uint32_t x) { asm volatile("st.shared.b16 [%0], %1;" :: "r"(a), "h"((unsigned short)x) : "memory"); }
DEVI void sts128(uint32_t a, uint32_t x) { asm volatile("st.shared.v4.b32 [%0], {%1,%1,%1,%1};" :: "r"(a), "r"(x) : "memory"); }
DEVI void arrive_if_eq(uint32_t bar, int a, int b) { asm volatile("{.reg .pred p; setp.eq.s32 p, %1, %2; @p mbarrier.arrive.shared::cta.b64 _, [%0];}" :: "r"(bar), "r"(a), "r"(b) : "memory"); }
DEVI void arrive_cl_if_eq(uint32_t bar, int a, int b) { asm volatile("{.reg .pred p; setp.eq.s32 p, %1, %2; @p mbarrier.arrive.shared::cluster.b64 _, [%0];}" :: "r"(bar), "r"(a), "r"(b) : "memory"); }
DEVI void spin_until(uint32_t t0, int d) { while ((int)(clock32() - t0) < d) {} }
DEVI void flag_wait(const int* p, int n, int& budget) {
  while (ld_acquire(p) < n && --budget > 0) __nanosleep(128);
  asm volatile("fence.proxy.async.global;" ::: "memory");
}

#define F4(C, o)  C(d[o+0]), C(d[o+1]), C(d[o+2]), C(d[o+3])
#define F8(C, o)  F4(C, o), F4(C, o+4)
#define F32(C, o) F8(C, o), F8(C, o+8), F8(C, o+16), F8(C, o+24)
#define R4  "{%0,%1,%2,%3}"
#define R8  "{%0,%1,%2,%3,%4,%5,%6,%7}"
#define R16 "{%0,%1,%2,%3,%4,%5,%6,%7,%8,%9,%10,%11,%12,%13,%14,%15}"
#define R20 "{%0,%1,%2,%3,%4,%5,%6,%7,%8,%9,%10,%11,%12,%13,%14,%15,%16,%17,%18,%19}"
#define R32 "{%0,%1,%2,%3,%4,%5,%6,%7,%8,%9,%10,%11,%12,%13,%14,%15,%16,%17,%18,%19,%20,%21,%22,%23,%24,%25,%26,%27,%28,%29,%30,%31}"
#define R64 "{%0,%1,%2,%3,%4,%5,%6,%7,%8,%9,%10,%11,%12,%13,%14,%15,%16,%17,%18,%19,%20,%21,%22,%23,%24,%25,%26,%27,%28,%29,%30,%31," \
  "%32,%33,%34,%35,%36,%37,%38,%39,%40,%41,%42,%43,%44,%45,%46,%47,%48,%49,%50,%51,%52,%53,%54,%55,%56,%57,%58,%59,%60,%61,%62,%63}"
template<uint32_t OFF, uint32_t LBO, uint32_t SBO, uint32_t SW, int T> struct Op {
  static constexpr uint32_t lo = (OFF >> 4) | ((LBO >> 4) << 16), hi = (SBO >> 4) | (SW << 30);
  static constexpr int t = T;
};
DEVI uint32_t desc_base(uint32_t addr) { return (addr & 0x3FFFF) >> 4; }
#define RS_ASM(SHAPE, REGS, A0, A1, A2, A3, B, LO, HI, T, SD) \
  "{.reg .b64 tb; .reg .b32 lb; add.u32 lb, " B ", " LO "; mov.b64 tb, {lb, " HI "};\n" \
  "wgmma.mma_async.sync.aligned." SHAPE ".f32.bf16.bf16 " REGS ", {" A0 "," A1 "," A2 "," A3 "}, tb, " SD ", 1, 1, " T ";}"
#define WG_RS(NAME, SHAPE, REGS, LIST, ...) \
  template<int ACC, class OB> DEVI void NAME(float* d, const uint32_t* a, uint32_t b) { \
    if (ACC) asm volatile(RS_ASM(SHAPE, REGS, __VA_ARGS__) \
      : LIST("+f") : "r"(a[0]), "r"(a[1]), "r"(a[2]), "r"(a[3]), "r"(b), "n"(OB::lo), "n"(OB::hi), "n"(OB::t), "n"(ACC & 1)); \
    else asm volatile(RS_ASM(SHAPE, REGS, __VA_ARGS__) \
      : LIST("=f") : "r"(a[0]), "r"(a[1]), "r"(a[2]), "r"(a[3]), "r"(b), "n"(OB::lo), "n"(OB::hi), "n"(OB::t), "n"(0)); \
  }
#define SS_ASM(SHAPE, REGS, A, B, LA, HA, TA, LB, HB, TB, SD) \
  "{.reg .b64 ta, tb; .reg .b32 la, lb; add.u32 la, " A ", " LA "; mov.b64 ta, {la, " HA "}; add.u32 lb, " B ", " LB "; mov.b64 tb, {lb, " HB "};\n" \
  "wgmma.mma_async.sync.aligned." SHAPE ".f32.bf16.bf16 " REGS ", ta, tb, " SD ", 1, 1, " TA ", " TB ";}"
#define WG_SS(NAME, SHAPE, REGS, LIST, ...) \
  template<int ACC, class OA, class OB> DEVI void NAME(float* d, uint32_t a, uint32_t b) { \
    if (ACC) asm volatile(SS_ASM(SHAPE, REGS, __VA_ARGS__) \
      : LIST("+f") : "r"(a), "r"(b), "n"(OA::lo), "n"(OA::hi), "n"(OA::t), "n"(OB::lo), "n"(OB::hi), "n"(OB::t), "n"(ACC & 1)); \
    else asm volatile(SS_ASM(SHAPE, REGS, __VA_ARGS__) \
      : LIST("=f") : "r"(a), "r"(b), "n"(OA::lo), "n"(OA::hi), "n"(OA::t), "n"(OB::lo), "n"(OB::hi), "n"(OB::t), "n"(0)); \
  }
#define L4(C)  F4(C, 0)
#define L8(C)  F8(C, 0)
#define L16(C) F8(C, 0), F8(C, 8)
#define L20(C) F8(C, 0), F8(C, 8), F4(C, 16)
#define L32(C) F32(C, 0)
WG_RS(wg_rs8, "m64n8k16", R4, L4, "%4", "%5", "%6", "%7", "%8", "%9", "%10", "%11", "%12")
WG_RS(wg_rs16, "m64n16k16", R8, L8, "%8", "%9", "%10", "%11", "%12", "%13", "%14", "%15", "%16")
WG_RS(wg_rs32, "m64n32k16", R16, L16, "%16", "%17", "%18", "%19", "%20", "%21", "%22", "%23", "%24")
WG_SS(wg_ss32, "m64n32k16", R16, L16, "%16", "%17", "%18", "%19", "%20", "%21", "%22", "%23", "%24")
WG_RS(wg_rs64, "m64n64k16", R32, L32, "%32", "%33", "%34", "%35", "%36", "%37", "%38", "%39", "%40")
WG_SS(wg_ss8, "m64n8k16", R4, L4, "%4", "%5", "%6", "%7", "%8", "%9", "%10", "%11", "%12")
WG_SS(wg_ss16, "m64n16k16", R8, L8, "%8", "%9", "%10", "%11", "%12", "%13", "%14", "%15", "%16")
WG_SS(wg_ss40, "m64n40k16", R20, L20, "%20", "%21", "%22", "%23", "%24", "%25", "%26", "%27", "%28")
WG_SS(wg_ss64, "m64n64k16", R32, L32, "%32", "%33", "%34", "%35", "%36", "%37", "%38", "%39", "%40")
#define L64(C) F32(C, 0), F32(C, 32)
WG_SS(wg_ss128, "m64n128k16", R64, L64, "%64", "%65", "%66", "%67", "%68", "%69", "%70", "%71", "%72")
template<int I> struct IC { __host__ __device__ constexpr operator int() const { return I; } };
template<int I, int N, class F> DEVI void sfor(F&& f) {
  if constexpr (I < N) { f(IC<I>{}); sfor<I + 1, N>(f); }
}

namespace rec {
constexpr int NHI = 36, NLO = 5, NRS = NHI + NLO, NSS = 64 - NRS;
constexpr uint32_t WS = 0;
constexpr uint32_t WO = 2 * NSS * 2048;
constexpr uint32_t RING = WO + 65536;
constexpr uint32_t QB = RING + 40960, RG = 2080, POSQ = 0x64210, POSK = 0xB9753, POSV = 0xEDCA8;
constexpr int JA = 2;
constexpr uint32_t WA = QB;
constexpr uint32_t OM = QB + 9 * RG, OMS = 2 * RG;
constexpr uint32_t OM2 = QB + 16384, OM2S = 2048;
constexpr uint32_t WH = QB + 20480;
constexpr uint32_t B_PART = QB + 15 * RG - 32, B_ML0 = B_PART + 8, REDO = B_PART + 16;
constexpr uint32_t PM0 = QB + 16384, PM1 = QB + 15 * RG, PM2 = PM1 + 256;
constexpr uint32_t BARS = PM2 + 128;
constexpr uint32_t B_FULL = BARS, B_EMPTY = BARS + 40, B_MLAND = BARS + 80, B_QK = BARS + 112, B_V = BARS + 120, B_OM = BARS + 128,
                   B_WA = BARS + 136, B_SDONE = BARS + 144, B_BFREE = BARS + 152, B_W1 = PM1, B_W2 = PM1 + 8, B_WO = PM1 + 16;
constexpr uint32_t SMEM = BARS + 160;
static_assert(SMEM <= 232448 && QB % 1024 == 0, "smem map");
constexpr int R1 = (PM1 - WO) / 4096, RB = NRS - R1;
__host__ __device__ constexpr uint32_t stage_at(int t, int r) { return r < R1 ? WO + (t * R1 + r) * 2048 : WS + (t * NSS + NSS - RB + r - R1) * 2048; }
constexpr int NB_WO = 1, NB_ST = 2, NB_P = 3, NB_TR = 4, NB_X = 5, NB_G = 6, NB_G1 = 7, NB_G2 = 8, NB_G4 = 9, NB_S = 10;
__host__ __device__ constexpr bool is_lo(int j) { return j % 12 == 8; }
__host__ __device__ constexpr int lo_before(int j) { return (j + 3) / 12; }
__host__ __device__ constexpr int ss_before(int j) { return (j - lo_before(j)) * NSS / (64 - NLO); }
__host__ __device__ constexpr bool is_ss(int j) { return ss_before(j + 1) != ss_before(j); }
__host__ __device__ constexpr int reg_idx(int j) { return is_lo(j) ? NHI + lo_before(j) : j - ss_before(j) - lo_before(j); }
template<int j> using OpW = Op<WS + ss_before(j) * 2048, 16, 1024, 1, 1>;
#define P_G1 1
#define P_G2 3
#define P_NA 6
#define P_G4 10
#define P_G5 12
#define P_SEND 0xff3210ffu
#define P_S1 0
#define P_S2 0
#define P_S0 2
#define P_S4 5
#define P_S5 8
constexpr uint32_t SLOT1 = 0x32410324, USE1 = 0x22111110;
DEVI bool single(int s) { return s < LAG - 1 || s >= NSEG - 1; }
DEVI uint32_t flip(int s) { return (s < LAG - 1 ? s + 1 : s < NSEG - 1 ? LAG : LAG + s + 1) & 1; }
}
DEVI uint32_t mapr(int h, uint32_t addr, int rank) { return mapa(addr, rank + (h & 1) * 3); }
template<int N> DEVI void pin(float* d) {
#pragma unroll
  for (int i = 0; i < N; i++) asm volatile("" : "+f"(d[i]) :: "memory");
}
DEVI void keep(const void* a) { asm volatile("{.reg .pred p; setp.eq.u64 p, %0, 0; vote.sync.any.pred p, p, 0xffffffff; @p exit;}" :: "l"(a) : "memory"); }
DEVI int lane_reg() { return __shfl_sync(0xffffffffu, threadIdx.x & 31, threadIdx.x & 31); }
#define LANE_NOW [[maybe_unused]] const int lane = lane0 + ((uint32_t)budget >> 30), g = lane >> 2, c = lane & 3

DEVI void rec_proj(const uint32_t sb, const int h, const int rank, const int w, const CUtensorMap* mW, const uint32_t zero) {
  using namespace rec;
  const int lane0 = lane_reg(), wg = w >> 2, ww = w & 3;
  int budget = SPIN_BUDGET;
  uint32_t wr[NRS * 4];
  {
    LANE_NOW;
    const uint32_t wsw = ((lane & 7) + (lane >> 4) * 8) * 128 + (((ww * 2 + ((lane >> 3) & 1)) ^ (lane & 7)) << 4);
    mbar_wait(sb + B_W1, 0, budget);

#pragma unroll
    for (int r = 0; r < NRS; r++) ldsm4t(sb + stage_at(wg, r) + wsw, wr[4*r], wr[4*r+1], wr[4*r+2], wr[4*r+3]);
    fence_proxy_async();
    nbar_sync<NB_ST, 256>();
    if (w < 4) {
      const int j = w * 16 + (lane >> 1), t = lane & 1;
      if (is_ss(j) && ss_before(j) >= NSS - RB) tma_load_2d(sb + WS + (t * NSS + ss_before(j)) * 2048, mW, h * DH + t * 64, j * 16, sb + B_W2);
    }
    __syncwarp();
    cluster_sync();
  }
  const uint32_t d0 = desc_base(sb), da = d0 + wg * (NSS * 128);
  const uint32_t pos = rank == 0 ? POSQ : rank == 1 ? POSK : POSV, bar = rank == 2 ? B_V : B_QK;
  uint32_t stg[2][4] = {}, pk[16] = {};
  auto stage = [&](uint32_t* t, int r) {
#pragma unroll
    for (int i = 0; i < 4; i++) asm volatile("xor.b32 %0, %1, %2;" : "+r"(t[i]) : "r"(wr[4 * r + i]), "r"(zero));
  };
#pragma unroll 1
  for (int s = -1; s < NSTEP; s++) {
    const uint32_t fl = flip(s);
    if (s >= 0) {
      float d[8];
      auto steps = [&](auto J0, auto J1, auto A0) {
        wg_fence();
        sfor<J0, J1>([&](auto J) {
          constexpr int j = J, acc = j ? 1 : A0;
          typedef Op<RING + j * 512, 256, 128, 0, 1> OB;
          if constexpr (is_ss(j)) wg_ss16<acc, OpW<j>, OB>(d, da, d0);
          else wg_rs16<acc, OB>(d, is_lo(j) ? stg[lo_before(j) & 1] : wr + 4 * reg_idx(j), d0);
        });
        wg_commit();
      };
      stage(stg[0], NHI);
      mbar_wait(sb + B_ML0, s & 1, budget);

      sfor<0, 8>([&](auto E) {
        constexpr int e = E, q = e >> 1;
        steps(IC<8 * e>{}, IC<8 * e + 8>{}, IC<0>{});
        if constexpr (e == 1) {
          mbar_wait(sb + B_FULL, 0, budget);
          if (__any_sync(0xffffffffu, lds32v(sb + REDO))) { wg_wait<0>(); steps(IC<0>{}, IC<16>{}, IC<2>{}); }
        }
        if constexpr (((P_SEND >> (4 * e)) & 15) == 0) { if (s > 0) mbar_wait(sb + B_BFREE, (s & 1) ^ 1, budget); }
        if constexpr (e > 0 && !(e & 1)) {
          wg_wait<1>();
          arrive_if_eq(sb + B_EMPTY + 8 * (q - 1), lane0, ww * 32);
        }
        if constexpr (!(e & 1)) stage(stg[(q + 1) & 1], NHI + q + 1);
        if constexpr (e < 6 && (e & 1)) mbar_wait(sb + B_FULL + 8 * (q + 1), q ? fl : 0, budget);
        if constexpr (((P_SEND >> (4 * e)) & 15) < 4) {
          constexpr int n = (P_SEND >> (4 * e)) & 15;
          LANE_NOW;
          const uint32_t r = mapr(h, sb, n >> 1);
          uint32_t t[4];
#pragma unroll
          for (int i = 0; i < 4; i++) { if (n == 0) t[i] = pk[i]; else asm volatile("xor.b32 %0, %1, %2;" : "=r"(t[i]) : "r"(pk[4*n+i]), "r"(zero)); }
          st_cl128(rank == n >> 1, r + QB + ((pos >> (4 + 4 * c)) & 15) * RG + w * 256 + (n & 1) * 128 + g * 16, t[0], t[1], t[2], t[3], r + bar);
        }
      });
      LANE_NOW;
      const uint32_t dst = QB + (pos & 15) * RG + w * 256 + lane * 4;
      wg_wait<0>();
      pin<8>(d);
      {
        const uint32_t x0 = pack_bf16(d[0], d[1]), x1 = pack_bf16(d[2], d[3]), y0 = pack_bf16(d[4], d[5]), y1 = pack_bf16(d[6], d[7]);
        const uint32_t r = mapr(h, sb, rank == 0);
        if (rank < 2) { sts32v(sb + dst, rank ? y0 : x0); sts32v(sb + dst + 128, rank ? y1 : x1); fence_proxy_async(); }
        st_async32(r + dst, rank ? x0 : y0, r + bar); st_async32(r + dst + 128, rank ? x1 : y1, r + bar);
        if (rank < 2) e_arrive(sb + B_QK);
        else { const uint32_t r1 = mapr(h, sb, 1); st_async32(r1 + dst, y0, r1 + bar); st_async32(r1 + dst + 128, y1, r1 + bar); }
      }
      if (s == NSTEP - 1) break;
      arrive_if_eq(sb + B_EMPTY + 24, lane0, ww * 32);
    } else {
      e_arrive(sb + B_EMPTY + 8 * ww);
      mbar_wait(sb + B_W2, 0, budget);
    }
    const bool gate = rank < 2 && s >= 0;
    if (single(s)) {
      float d[16];
      sfor<0, 8>([&](auto C) {
        constexpr int cc = C, sl = (SLOT1 >> (4 * cc)) & 15;
        if constexpr (cc == 0) mbar_wait(sb + B_FULL + 8 * sl, 0, budget);
        if constexpr (cc == P_S1) { if (gate) nbar_sync<NB_G1, 384>(); }
        if constexpr (cc == P_S2) { if (gate) nbar_sync<NB_G2, 384>(); }
        if constexpr (cc == P_S0) nbar_sync<NB_WO, 384>();
        if constexpr (cc == P_S4 || cc == P_S5) { if (gate && cc == (rank ? P_S5 : P_S4)) nbar_sync<NB_G4, 384>(); }
        if constexpr (lo_before(cc * 8 + 8) != lo_before(cc * 8)) stage(stg[0], NHI + lo_before(cc * 8));
        wg_fence();
        sfor<0, 8>([&](auto I) {
          constexpr int i = I, j = cc * 8 + i;
          typedef Op<RING + sl * 8192 + (i >> 2) * 4096 + (i & 3) * 32, 16, 1024, 1, 0> OB;
          if constexpr (is_ss(j)) wg_ss32<j != 0, OpW<j>, OB>(d, da, d0);
          else wg_rs32<j != 0, OB>(d, is_lo(j) ? stg[0] : wr + 4 * reg_idx(j), d0);
        });
        wg_commit();
        if constexpr (cc < 7) {
          constexpr int sn = (SLOT1 >> (4 * cc + 4)) & 15;
          mbar_wait(sb + B_FULL + 8 * sn, ((USE1 >> (4 * cc + 4)) & 1) ^ (sn >> 1 == 1 ? fl : 0), budget);
        }
        wg_wait<0>();
        arrive_if_eq(sb + B_EMPTY + 8 * sl, lane0, ww * 32);
      });
      pin<16>(d);
      if (gate && (rank ? P_S5 : P_S4) == 8) nbar_arrive<NB_G4, 384>();

#pragma unroll
      for (int i = 0; i < 8; i++) pk[i] = pk[8 + i] = pack_bf16(d[4 * (i & 3) + ((i >> 1) & 2)], d[4 * (i & 3) + ((i >> 1) & 2) + 1]);
      continue;
    }
    float d[32];
    sfor<0, 16>([&](auto C) {
      constexpr int cc = C, sl = (cc + 4) % 5;
      if constexpr (cc == 0) mbar_wait(sb + B_FULL + 8 * sl, 0, budget);
      if constexpr (cc == P_G1) { if (gate) nbar_sync<NB_G1, 384>(); }
      if constexpr (cc == P_G2) { if (gate) nbar_sync<NB_G2, 384>(); }
      if constexpr (cc == P_NA) {
        nbar_sync<NB_WO, 384>();
      }
      if constexpr (cc == P_G4 || cc == P_G5) { if (gate && cc == (rank ? P_G5 : P_G4)) nbar_sync<NB_G4, 384>(); }
      wg_fence();
      sfor<0, 4>([&](auto I) {
        constexpr int i = I, j = cc * 4 + i;
        typedef Op<RING + sl * 8192 + i * 32, 16, 1024, 1, 0> OB;
        if constexpr (is_ss(j)) wg_ss64<j != 0, OpW<j>, OB>(d, da, d0);
        else wg_rs64<j != 0, OB>(d, is_lo(j) ? stg[0] : wr + 4 * reg_idx(j), d0);
      });
      wg_commit();
      if constexpr (cc < 15) {
        if constexpr (is_lo(cc * 4 + 4)) stage(stg[0], reg_idx(cc * 4 + 4));
        mbar_wait(sb + B_FULL + 8 * ((sl + 1) % 5), ((cc + 5) / 5 + (sl == 1 || sl == 2 ? LAG : 0)) & 1, budget);
      }
      wg_wait<0>();
      arrive_if_eq(sb + B_EMPTY + 8 * sl, lane0, ww * 32);
    });
    pin<32>(d);
    if (gate && (rank ? P_G5 : P_G4) == 16) nbar_arrive<NB_G4, 384>();

#pragma unroll
    for (int i = 0; i < 16; i++) pk[i] = pack_bf16(d[16 * (i >> 3) + 4 * (i & 3) + ((i >> 1) & 2)], d[16 * (i >> 3) + 4 * (i & 3) + ((i >> 1) & 2) + 1]);
  }
}

DEVI float softmax_row(float* v, uint32_t* p) {
  constexpr float SC = 0.08838834764831845f * 1.4426950408889634f;
  float m = fmaxf(fmaxf(fmaxf(fmaxf(v[0], v[1]), fmaxf(v[2], v[3])), fmaxf(fmaxf(v[4], v[5]), fmaxf(v[6], v[7]))), fmaxf(v[8], v[9]));
  m = fmaxf(m, __shfl_xor_sync(0xffffffffu, m, 1));
  m = fmaxf(m, __shfl_xor_sync(0xffffffffu, m, 2));
  const float ms = -m * SC, mh = fmaf(m, -SC, -1.f);
#pragma unroll
  for (int i = 0; i < 10; i++) asm("ex2.approx.ftz.f32 %0, %1;" : "=f"(v[i]) : "f"(fmaf(v[i], SC, i < 8 ? ms : mh)));
#pragma unroll
  for (int n = 0; n < 5; n++) p[n] = pack_bf16(v[2*n], v[2*n+1]);
  return fmaf(v[8] + v[9], 2.f, ((v[0] + v[1]) + (v[2] + v[3])) + ((v[4] + v[5]) + (v[6] + v[7])));
}

template<bool ATT>
DEVI void rec_attn(const uint32_t sb, int h, int rank, int w, const bf16* __restrict__ Wo, const bf16* __restrict__ mem0) {
  using namespace rec;
  const int lane0 = lane_reg();
  int budget = SPIN_BUDGET;
  constexpr int NT = ATT ? 5 : 6;
  uint32_t wl[16];
  if (!ATT) {
    LANE_NOW;
#pragma unroll
    for (int i = 0; i < 16; i++) {
      const int dh = 8 * (i >> 1) + 2 * c;
      const unsigned short* p = (const unsigned short*)Wo + (size_t)(h * DH + dh) * DM + 15 * 64 + 16 * w + 8 * (i & 1) + g;
      wl[i] = p[0] | (uint32_t)p[DM] << 16;
    }
  }
  cluster_sync();
  const uint32_t d0 = desc_base(sb);
  uint32_t pph = 0;
#pragma unroll 1
  for (int s = -1; s < NSTEP; s++) {
    asm volatile("" : "+r"(h), "+r"(rank), "+r"(w));
    const uint32_t sp = s & 1;
    const int t0 = ATT ? rank + 1 : 0;
    const bool more = s + 1 < NSTEP;
    if (s == 0) mbar_wait(sb + B_WO, 0, budget);
    float hold[10] = {0, 0, 0, 0, 0, 0, 0, 0, 0, 0};
    if (ATT && s >= 0) {
      float sc[20];
      LANE_NOW;
      mbar_wait(sb + B_QK, sp, budget);
      fence_proxy_async();
      wg_fence();
      sfor<0, 8>([&](auto K) { constexpr int k = K; wg_ss40<k != 0, Op<QB + k * 256, 128, RG, 0, 1>, Op<QB + 3 * RG + k * 256, 128, 2 * RG, 0, 1>>(sc, d0, d0); });
      wg_commit();
      if (more) nbar_arrive<NB_G1, 384>();
      wg_wait<0>();
      pin<20>(sc);
      if (w == 3 && more) nbar_arrive<NB_S, 64>();
      if (w == 0) {
        uint32_t p[5];
        float v[10];
#pragma unroll
        for (int i = 0; i < 10; i++) v[i] = sc[4 * (i >> 1) + (i & 1)];
        softmax_row(v, p);
        const uint32_t a = sb + lane * 4;
        sts32v(a + PM0, p[0]); sts32v(a + PM0 + 128, p[1]); sts32v(a + PM1, p[2]); sts32v(a + PM1 + 128, p[3]); sts32v(a + PM2, p[4]);
      }
      if (w || !more) mbar_wait(sb + B_V, sp, budget);
      if (w == 1 && more) e_expect_tx(sb + B_V, 10240);
      if (more) {
        float rs[4], ot[2][4];
        uint32_t one[4];
#pragma unroll
        for (int i = 0; i < 4; i++) one[i] = 0x3F803F80u + ((uint32_t)budget >> (31 - i));
        typedef Op<PM0, 128, 128, 0, 0> P0; typedef Op<PM1, 128, 128, 0, 0> P1; typedef Op<PM2, 0, 128, 0, 0> P2;
        fence_proxy_async();
        nbar_sync<NB_P, 128>();
        wg_fence();
        wg_rs8<0, P0>(rs, one, d0); wg_rs8<1, P1>(rs, one, d0); wg_rs8<1, P2>(rs, one, d0);
        wg_commit();
        sfor<0, 2>([&](auto T) {
          constexpr int t = T;
          wg_ss8<0, Op<QB + 8 * RG + t * 1024, 2 * RG, 128, 0, 0>, P0>(ot[t], d0, d0);
          wg_ss8<1, Op<QB + 12 * RG + t * 1024, RG, 128, 0, 0>, P1>(ot[t], d0, d0);
          wg_ss8<1, Op<QB + 14 * RG + t * 1024, 0, 128, 0, 0>, P2>(ot[t], d0, d0);
        });
        wg_commit();
        nbar_arrive<NB_G2, 384>();
        const uint32_t oa = w * 256 + lane * 4, r1 = mapr(h, sb, rank ^ 1), r2 = mapr(h, sb, 2);
        mbar_wait(sb + B_SDONE, sp, budget);
        wg_wait<1>();
        pin<4>(rs);
        float i0, i1;
        asm volatile("rcp.approx.ftz.f32 %0, %1;" : "=f"(i0) : "f"(rs[0]));
        asm volatile("rcp.approx.ftz.f32 %0, %1;" : "=f"(i1) : "f"(rs[1]));
        wg_wait<0>();
        pin<4>(ot[0]); pin<4>(ot[1]);
        uint32_t x[4];
#pragma unroll
        for (int j = 0; j < 4; j++) {
          x[j] = pack_bf16(ot[j >> 1][2 * (j & 1)] * i0, ot[j >> 1][2 * (j & 1) + 1] * i1);
          sts32v(sb + OM + rank * OMS + oa + (j >> 1) * 1024 + (j & 1) * 128, x[j]);
        }
        fence_proxy_async();
#pragma unroll
        for (int j = 0; j < 8; j++) {
          const int i = j >> 1;
          if (j & 1) st_async32(r1 + OM + rank * OMS + oa + (i >> 1) * 1024 + (i & 1) * 128, x[i], r1 + B_OM);
          else st_async32(r2 + OM2 + rank * OM2S + oa + (i >> 1) * 1024 + (i & 1) * 128, x[i], r2 + B_OM);
        }
        e_arrive(sb + B_OM);
      }
#pragma unroll
      for (int i = 0; i < 10; i++) hold[i] = w ? sc[4 * (i >> 1) + (i & 1)] : sc[4 * (i >> 1) + 2 + (i & 1)];
    }
    if (more && s >= 0) {
      LANE_NOW;
      char* const pw = (char*)g_part + (uint32_t)((t0 * 16 + w * 4 + (lane >> 3)) * 4096 + h * 128 + ((lane ^ h) & 7) * 16);
      mbar_wait(sb + B_OM, sp, budget);
      if (w == 0) nbar_arrive<NB_G, 128>();
      if (!ATT) fence_proxy_async();
      float acc[3][8];
      auto store = [&](auto J) {
        constexpr int j = J;
        float* d = acc[j % 3];
        pin<8>(d);
        uint32_t x[4];
#pragma unroll
        for (int i = 0; i < 4; i++) { const uint32_t m = (h >> 3) == i; x[i] = (pack_bf16(d[2*i], d[2*i+1]) & ~m) | (m & ~sp); }
        stg_rlx128(pw + j * (48 * 4096), x[0], x[1], x[2], x[3]);
        if constexpr (ATT && j == JA) nbar_arrive<NB_TR, 160>();
      };
      sfor<0, NT>([&](auto J) {
        constexpr int j = J;
        if constexpr (ATT && j == JA) { mbar_wait(sb + B_WA, sp, budget); }
        wg_fence();
        sfor<0, 8>([&](auto K) {
          constexpr int k = K;
          typedef Op<(ATT ? OM : OM2) + k * 256, 128, ATT ? OMS : OM2S, 0, 1> OB;
          if constexpr (j == 5 && k < 4) wg_rs16<k ? 1 : 2, OB>(acc[j % 3], wl + 4 * k, d0);
          else wg_ss16<k ? 1 : j < 3 ? 0 : 2, Op<(j == JA ? WA : j < 5 ? WO + (j - (j > JA)) * 16384 : WH - 8192) + k * 2048, 16, 1024, 1, 1>, OB>(acc[j % 3], d0, d0);
        });
        wg_commit();
        if constexpr (j == 0) { if (w == 3) e_expect_tx(sb + B_OM, ATT ? 2048 : 4096); }
        if constexpr (j == NT - 1) nbar_arrive<NB_WO, 384>();
        if constexpr (j > 0 && j != JA + 1) { wg_wait<1>(); store(IC<j - 1>{}); }
        if constexpr (j == JA || j == NT - 1) { wg_wait<0>(); store(IC<j>{}); }
        if constexpr (j == JA) {
          const uint32_t t = clock32();
          if (ATT) {
            if (w == 3 && lane < 14) sts128(sb + PM1 + lane * 16, (lane >> 1) == 3 ? 0x3F803F80u : 0);
            if (w == 3) fence_proxy_async();
            nbar_sync<NB_P, 128>();
          }
          spin_until(t, 100);
        }
      });
    } else if (more) nbar_arrive<NB_WO, 384>();
    asm volatile("" : "+r"(h), "+r"(rank), "+r"(w));
#pragma unroll 1
    for (int pass = 0; ATT && pass < 2; pass++)
    if (pass != rank) {
      LANE_NOW;
      const int lim = 8 * (g >> 1) + (g & 1) + 2 * w - 8 * c;
      uint32_t p[5];
#pragma unroll
      for (int i = 0; i < 8; i++) hold[2+i] = i <= lim ? hold[2+i] : -INFINITY;
      const float psum = softmax_row(hold, p);
#pragma unroll
      for (int i = 0; i < 5; i++) hold[i] = __uint_as_float(p[i]);
      hold[5] = psum;
    } else if (more) {
      LANE_NOW;
      const int blk = rank * 32 + (h ^ 16);
      char* const mw = (char*)g_mem + (uint32_t)(sp * 32768 + blk * 512 + w * 128 + lane * 4);
      uint32_t v0 = 0;
      if (s == -1 || (s == LAG - 1 && (w & 1))) {
        const unsigned short* q = (const unsigned short*)mem0 + c * 2 * DM + blk * 16 + (w >> 1) * 8 + g;
        v0 = q[0] | (uint32_t)q[DM] << 16;
        if (v0 == 0) v0 = 0x8000u;
      }
      keep(mw);
      if (s >= 0) {
        const uint32_t ca = sb + WA + lane * 128 + (((2 * w) ^ lane) & 7) * 16 + (lane >> 3) * 4;
        const uint32_t sa = sb + OM + (((g >> 1) & 1) * 2 + (g >> 2)) * 128 + (2 * c + (w >> 1)) * 16 + (w & 1) * 8 + (g & 1) * 2;
        const bool g4l = single(s);
        for (bool first = true; ; first = false) {
          float r[4];
          mbar_wait(sb + B_PART, pph, budget);
          pph ^= 1;
          wg_fence();
          sfor<0, 8>([&](auto K) { constexpr int k = K; wg_ss8<k != 0, Op<WA + k * 2048, 16, 1024, 1, 1>, Op<PM1 + (6 - (k & 6)) * 16, 0, 128, 0, 0>>(r, d0, d0); });
          wg_commit();
          if (!g4l && first) nbar_arrive<NB_G4, 384>();
          const uint32_t x0 = lds32v(ca), x1 = lds32v(ca + 4096), x2 = lds32v(ca + 8192), x3 = lds32v(ca + 12288);
          bool bad = __any_sync(0xffffffffu, (sp ? x0 | x1 | x2 | x3 : ~(x0 & x1 & x2 & x3)) & 1) && budget > 0;
          wg_wait<0>();
          pin<4>(r);
          uint32_t y = pack_bf16(r[0], r[2]);
          y |= (y & 0xffffu) ? 0 : 0x8000u;
          y |= (y >> 16) ? 0 : 0x80000000u;
          if (bad) y = 0;
          sts16(sa, y); sts16(sa + 4, y >> 16);
          nbar_sync<NB_P, 128>();
          y = lds32v(sb + OM + w * 128 + lane * 4);
          const bool ok = !__any_sync(0xffffffffu, y == 0);
          if (ok) stg_rlx32(mw, v0 ? v0 : y);
          if (g4l && first) nbar_arrive<NB_G4, 384>();
          if (ok) break;
          nbar_sync<NB_P, 128>();
          budget--;
          if (w == 0) { e_expect_tx(sb + B_PART, 16384); e_bulk_g2s(sb + WA, (const char*)g_part + blk * 16384, 16384, sb + B_PART); }
          __syncwarp();
        }
        nbar_sync<NB_P, 128>();
        if (w < 2) e_arrive_cl(mapr(h, sb + B_BFREE, w));
      } else stg_rlx32(mw, v0);
      stg_rlx32(mw + (sp ? -32768 : 32768), 0);
    }
    if (ATT && s >= 0) {
      const int seg = s - (rank ? LAG : 0);
      const bool act = (unsigned)seg < NSEG;
      LANE_NOW;
      uint32_t a[12];
#pragma unroll
      for (int i = 0; i < 12; i++) a[i] = __float_as_uint(hold[i < 10 ? i >> 1 : 4]) + ((uint32_t)budget >> (31 - (i & 3)));
      float o[32], inv, psum = hold[5];
      char* const ob = (char*)g_o[rank] + ((size_t)(seg * 32 + 8 * (g >> 1) + (g & 1) + 2 * w) * (NH * DH) + h * DH + c * 8) * 2;
      sfor<0, 2>([&](auto HF) {
        constexpr int hf = HF;
        wg_fence();
        wg_rs64<hf * 2, Op<QB + 8 * RG + hf * 1024, 2 * RG, 128, 0, 0>>(o, a, d0);
        wg_rs64<1, Op<QB + 12 * RG + hf * 1024, RG, 128, 0, 0>>(o, a + 4, d0);
        wg_rs64<1, Op<QB + 14 * RG + hf * 1024, 0, 128, 0, 0>>(o, a + 8, d0);
        wg_commit();
        if constexpr (hf == 0) {
          psum += __shfl_xor_sync(0xffffffffu, psum, 1);
          psum += __shfl_xor_sync(0xffffffffu, psum, 2);
          asm("rcp.approx.ftz.f32 %0, %1;" : "=f"(inv) : "f"(psum));
        }
        wg_wait<0>();
        pin<32>(o);
        if constexpr (hf == 1) { if (w == 2 && more) e_arrive_cl(mapr(h, sb + B_BFREE, 2)); }
        if (act) {
#pragma unroll
          for (int i = 0; i < 2; i++)
            stg128(ob + (hf * 2 + i) * 64, pack_bf16(o[16*i] * inv, o[16*i+1] * inv), pack_bf16(o[16*i+4] * inv, o[16*i+5] * inv),
                   pack_bf16(o[16*i+8] * inv, o[16*i+9] * inv), pack_bf16(o[16*i+12] * inv, o[16*i+13] * inv));
        }
      });
      if (act && (seg & 3) == 3) {
        nbar_sync<NB_P, 128>();
        if (w == 0) e_flag_add(g_fl.dep + grp(0, rank, seg >> 2), 4);
      }
    } else if (!ATT && w == 3) {
      if (s + 4 < NSEG) e_prefetch(g_xn[0] + (size_t)((s + 4) * 32 + h) * DM, 2048);
    }
  }
  cluster_sync();
}

DEVI void rec_load(const uint32_t sb, const int h, const int rank, const int w, const CUtensorMap* mX, const CUtensorMap* mWo) {
  using namespace rec;
  const int lane0 = lane_reg(), mq = (w + 3) & 3;
  int budget = SPIN_BUDGET;
  if (w == 0) flag_wait(g_fl.xn[0][0], 96, budget);

  bool late = false;
  cluster_sync();
  if (w == 0) { if (lane0 < 4) mbar_arrive(sb + B_FULL + 8 * lane0); __syncwarp(); }
  if (w == 3) {
    mbar_wait(sb + B_W2, 0, budget);
    e_expect_tx(sb + B_WO, rank == 2 ? 65536 + 16384 + 8192 : 65536);
    const int t0 = (rank + 1) % 3;
    if (lane0 < 8) tma_load_2d(sb + WO + lane0 * 8192, mWo, (3 * ((lane0 >> 1) + (lane0 >> 1 >= JA)) + t0) * 64, h * DH + (lane0 & 1) * 64, sb + B_WO);
    else if (rank < 2 && lane0 < 10) tma_prefetch_2d(mWo, (3 * JA + t0) * 64, h * DH + (lane0 & 1) * 64);
    else if (rank == 2 && lane0 < 11) tma_load_2d(lane0 < 10 ? sb + WA + (lane0 - 8) * 8192 : sb + WH, mWo, lane0 < 10 ? 3 * JA * 64 : 15 * 64, h * DH + (lane0 > 8) * 64, sb + B_WO);
    __syncwarp();
  }
  uint32_t lph = 0;
#pragma unroll 1
  for (int s = -1; s < NSTEP - 1; s++) {
    if (w == 0) {
      if (late) flag_wait(g_fl.xn[1][(s + 1 - LAG) >> 2], 128, budget);
      if (single(s)) {
#pragma unroll 1
        for (int i = 0; i < 8; i++) {
          const int k = i < 5 ? (0x21430 >> (4 * i)) & 15 : i;
          const int sl = (SLOT1 >> (4 * k)) & 15;
          mbar_wait(sb + B_EMPTY + 8 * sl, (((USE1 >> (4 * k)) ^ (sl >> 1 == 1 ? flip(s) : 0)) & 1) ^ 1, budget);
          e_expect_tx(sb + B_FULL + 8 * sl, 8192);
          e_tma_3d(sb + RING + sl * 8192, mX + 1, 0, (s + 1 + (s < LAG ? 0 : NSTEP)) * 32, k * 2, sb + B_FULL + 8 * sl);
        }
      } else {
        int sl = 4, ph = 1;
#pragma unroll 1
        for (int i = 0; i < 16; i++) {
          mbar_wait(sb + B_EMPTY + 8 * sl, ph ^ (sl >> 1 & LAG & 1), budget);
          e_expect_tx(sb + B_FULL + 8 * sl, 8192);
          e_tma_3d(sb + RING + sl * 8192, mX, i * 64, (s + 1) * 32, 0, sb + B_FULL + 8 * sl);
          if (++sl == 5) { sl = 0; ph ^= 1; }
        }
      }
      nbar_arrive<NB_X, 128>();
      const int sn = s + 2 - LAG;
      late = (sn & 3) == 0 && (unsigned)sn < NSEG && ld_acquire(g_fl.xn[1][sn >> 2]) < 128;
      asm volatile("fence.proxy.async.global;" ::: "memory");
    }
    uint32_t t = gtime();
    if (s >= 0) {
      uint2 a;
      if (w == 2 && rank < 2) {
        nbar_sync<NB_S, 64>();
        e_expect_tx(sb + B_WA, 16384);
        e_tma_2d(sb + WA, mWo, (3 * JA + 1 + rank) * 64, h * DH, sb + B_WA);
        e_tma_2d(sb + WA + 8192, mWo, (3 * JA + 1 + rank) * 64, h * DH + 64, sb + B_WA);
        e_arrive_cl(mapr(h, sb + B_SDONE, rank ^ 1));
        stg_rlx32(&g_ann[s & 1][lane0][h * 2 + rank], (gtime() & ~31u) | ((s + 1) & 31));
        e_expect_tx(sb + B_QK, 10240);
      }
      if (w) nbar_sync<NB_G, 128>();
      do { a = ldg_rlx64(&g_ann[s & 1][h][lane0 * 2]); } while (__any_sync(0xffffffffu, ((a.x ^ (s + 1)) | (a.y ^ (s + 1))) & 31) && --budget > 0);
      t += __reduce_max_sync(0xffffffffu, max((int)(a.x - t), (int)(a.y - t)));
      t &= ~31u;
      if (w == 1 && rank < 2) {
        nbar_sync<NB_TR, 160>();
        e_expect_tx(sb + B_PART, 16384);
        wait_time(t + (single(s) ? (rank ? 1500 : 1100) : rank ? 1700 : 1300), budget);
        e_bulk_g2s(sb + WA, (const char*)g_part + (rank * 32 + (h ^ 16)) * 16384, 16384, sb + B_PART);
      }
      t += single(s) ? (mq == 0 ? 1950 : mq == 1 ? 2100 : mq == 2 ? 2400 : 2600)
                     : (mq == 0 ? 2250 : mq == 1 ? 2400 : mq == 2 ? 2700 : 2950);
    }
    if (w) nbar_sync<NB_X, 128>();
    mbar_wait(sb + B_EMPTY + 8 * mq, mq >= 2 ? flip(s + 1) ^ 1 : 1, budget);
    uint32_t bar = sb + (mq == 0 ? B_ML0 : B_MLAND + 8 * mq), redo = 0;
    e_expect_tx(bar, 8192);
    wait_time(t, budget);
    while (true) {
      e_bulk_g2s(sb + RING + mq * 8192, (const char*)g_mem + (s & 1) * 32768 + mq * 8192, 8192, bar);
      const uint32_t a = sb + RING + mq * 8192 + lane0 * 32 + (lane0 >> 2) * 4;
      if (bar == sb + B_ML0) mbar_wait(bar, (s + 1) & 1, budget);
      else { mbar_wait(bar, lph, budget); lph ^= 1; }
      uint32_t mn = 0xffffffffu;
#pragma unroll
      for (int i = 0; i < 8; i++) mn = min(mn, lds32v(a + i * 1024));
      if (!__any_sync(0xffffffffu, mn == 0) || --budget <= 0) break;
      bar = sb + B_MLAND + 8 * mq; redo = 1;
      e_expect_tx(bar, 8192);
    }
    if (mq == 0) sts32v(sb + REDO, redo);
    e_arrive(sb + B_FULL + 8 * mq);
  }
}

DEVI void ln_row(const uint4* u, bf16* dst, int lane) {
  const uint32_t* x = (const uint32_t*)u;
  float mean = 0, q = 0;
#pragma unroll
  for (int i = 0; i < 16; i++) mean += bf_lo(x[i]) + bf_hi(x[i]);
  mean *= 1.f / 32;
#pragma unroll
  for (int i = 0; i < 16; i++) { const float a = bf_lo(x[i]) - mean, b = bf_hi(x[i]) - mean; q = fmaf(a, a, fmaf(b, b, q)); }
#pragma unroll
  for (int o = 1; o < 32; o *= 2) {
    const float m2 = __shfl_xor_sync(0xffffffffu, mean, o), q2 = __shfl_xor_sync(0xffffffffu, q, o), dl = m2 - mean;
    q = fmaf(dl * dl, 16.f * o, q + q2);
    mean = 0.5f * (mean + m2);
  }
  const float rs = rsqrtf(q * (1.f / DM) + 1e-5f), mr = -mean * rs;
#pragma unroll
  for (int i = 0; i < 4; i++) {
    uint32_t y[4];
#pragma unroll
    for (int k = 0; k < 4; k++) y[k] = pack_bf16(fmaf(bf_lo(x[4*i+k]), rs, mr), fmaf(bf_hi(x[4*i+k]), rs, mr));
    stg128((uint4*)dst + i * 32 + lane, y[0], y[1], y[2], y[3]);
  }
}

struct RecMaps { CUtensorMap w[3], wo, x[2]; };
__global__ void __cluster_dims__(6, 1, 1) __launch_bounds__(512, 1)
rec_kernel(const __grid_constant__ RecMaps M, const bf16* __restrict__ Wo, const bf16* __restrict__ mem0, const bf16* __restrict__ x, uint32_t zero) {
  using namespace rec;
  extern __shared__ __align__(1024) uint8_t smem[];
  const uint32_t sb = smem_u32(smem);
  const int tid = threadIdx.x, warp = __shfl_sync(0xffffffffu, tid >> 5, 0), wg = warp >> 2, lane = tid & 31;
  const int h = blockIdx.x / 3, rank = blockIdx.x % 3;
  if (warp >= 4) {
    const bool ln = warp >= 5 && blockIdx.x * 11 + warp - 5 < SEQ / 2;
    const size_t lo = (size_t)(blockIdx.x * 11 + warp - 5) * (2 * DM);
    uint4 u[8];
    if (ln) {
#pragma unroll
      for (int i = 0; i < 8; i++) u[i] = ldg_rlx128((const uint4*)(x + lo) + i * 32 + lane);
    }
    const uint4 z = make_uint4(0, 0, 0, 0);
    const int t = blockIdx.x * 384 + tid - 128;
    constexpr int N = (sizeof(Flags) - sizeof(g_fl.xn)) / 16;
    g_part[t] = z;
    if (t < 28672) g_part[96 * 384 + t] = z;
    else if (t < 32768) g_mem[0][t - 28672] = ((uint4*)g_stat[4])[t - 28672] = z;
    else if (t < 33792) ((uint4*)g_ann)[t - 32768] = z;
    else if (t < 33792 + N) ((uint4*)g_fl.dep)[t - 33792] = z;
    __syncwarp();
    if (ln) { ln_row(u, g_xn[0] + lo, lane); ln_row(u + 4, g_xn[0] + lo + DM, lane); }
    nbar_sync<NB_WO, 384>();
    if (warp == 4) {
      e_flag_add(g_fl.xn[0][0]);
      asm volatile("griddepcontrol.launch_dependents;" ::: "memory");
    }
  } else {
    if (warp == 0) {
      if (lane < 20) mbar_init(sb + BARS + 8 * lane, (lane >= 5 && lane < 10) || lane == 19 ? 2 : lane == 14 ? 9 : lane == 16 && rank < 2 ? 5 : 1);
      else if (lane < 23) mbar_init(sb + B_W1 + 8 * (lane - 20), 1);
      else if (lane < 25) mbar_init(sb + B_PART + 8 * (lane - 23), 1);
      fence_mbar_init();
      __syncwarp();
      e_expect_tx(sb + B_W1, NRS * 4096); e_expect_tx(sb + B_W2, NSS * 4096);
      e_expect_tx(sb + B_QK, 10240); e_expect_tx(sb + B_V, 10240); e_expect_tx(sb + B_OM, rank < 2 ? 2048 : 4096);
    }
    nbar_sync<NB_ST, 128>();
    if (!is_ss(tid >> 1)) tma_load_2d(sb + stage_at(tid & 1, reg_idx(tid >> 1)), &M.w[rank], h * DH + (tid & 1) * 64, (tid >> 1) * 16, sb + B_W1);
    __syncwarp();
  }
  __syncthreads();
  if (warp < 4) {
    const int j = tid >> 1, t = tid & 1;
    if (!is_ss(j)) {}
    else if (ss_before(j) < NSS - RB) tma_load_2d(sb + WS + (t * NSS + ss_before(j)) * 2048, &M.w[rank], h * DH + t * 64, j * 16, sb + B_W2);
    else tma_prefetch_2d(&M.w[rank], h * DH + t * 64, j * 16);
    __syncwarp();
  }
  if (wg == 3) {
    reg_dec<24>();
    rec_load(sb, h, rank, warp & 3, M.x, &M.wo);
    cluster_sync();
  } else if (wg == 2) {
    reg_dec<72>();
    if (rank < 2) rec_attn<true>(sb, h, rank, warp & 3, Wo, mem0);
    else rec_attn<false>(sb, h, rank, warp & 3, Wo, mem0);
  } else {
    reg_inc<208>();
    rec_proj(sb, h, rank, warp, &M.w[rank], zero);
    cluster_sync();
  }
}

namespace gm {
constexpr int STAGES = 6, STAGE_BYTES = 32768;
constexpr uint32_t SO = STAGES * STAGE_BYTES, B_FULL = SO + 32768, B_TRIG = B_FULL + 56, B_EMPTY = B_FULL + 64, B_JOB = B_FULL + 128,
                   B_MSG = B_FULL + 144, B_XF = B_FULL + 160, B_SF = B_FULL + 176, JOB = B_FULL + 192, MSG = JOB + 8, SMEM = B_FULL + 256;
constexpr int T_O = 0, T_GU = 1, T_D = 2, T_END = 3;
#define G_LOOK 8
#define G_DF 2
#define G_FL 12
#define G_BOOT 3
#define G_O0 4
#define G_O1 12
#define G_DS 14
DEVI bool is_split(int ty, int l, int cb) { return ty == T_O ? !l || cb < G_O0 || cb >= G_O1 : ty == T_D && (!l || cb >= G_DS); }
#define G_ROLES 16, 17, 8, 9, 10, 0, 1, 2, 3, 4, 5, 6, 7, 11, 12, 13, 14, 15
constexpr uint64_t pack_roles(int i0, int i1) { constexpr int r[18] = {G_ROLES}; uint64_t v = 0; for (int i = i0; i < i1; i++) v |= (uint64_t)r[i] << (5 * (i - i0)); return v; }
constexpr uint64_t ROLE0 = pack_roles(0, 12), ROLE1 = pack_roles(12, 18);
static_assert(G_FL >= G_O1 && G_FL >= 8, "fused layernorm: split jobs, 8 slots");
struct Pipe { int s, ph; DEVI void next() { if (++s == STAGES) { s = 0; ph ^= 1; } } };
}
struct GemmMaps { CUtensorMap o, oh, wo, x, x1, x1s, xm, xms, xn, wg, wu, h, hs, wd, x2, x2s, out, outs; };

DEVI float geglu(float g, float u) {
  const float z = g * (0.7978845608028654f + 0.035677408136300125f * g * g);
  float t; asm("tanh.approx.f32 %0, %1;" : "=f"(t) : "f"(z));
  const float hg = 0.5f * g;
  return fmaf(hg, t, hg) * u;
}
DEVI int h_ready(int v) { const int t = v ^ 0x10141014; return t & 0xff0000ff ? 0 : t & 0xff00 ? 20 : t ? 36 : 56; }
DEVI int a_ready(int ty, int l, int cb) {
  int v;
  asm volatile("ld.acquire.gpu.global.s32 %0, [%1];" : "=r"(v) : "l"(g_fl.dep + grp(ty, l, cb) + (threadIdx.x & 1)) : "memory");
  v = __shfl_sync(0xffffffffu, v, 0);
  asm volatile("fence.proxy.async.global;" ::: "memory");
  return ty == gm::T_D ? h_ready(v) : v >= (ty == gm::T_O && l ? 256 : 128) ? 64 : 0;
}

__global__ void __cluster_dims__(2, 1, 1) __launch_bounds__(512, 1) gemm_kernel(const __grid_constant__ GemmMaps M) {
  using namespace gm;
  extern __shared__ __align__(1024) uint8_t smem[];
  const uint32_t sb = smem_u32(smem);
  const int tid = threadIdx.x, wid = __shfl_sync(0xffffffffu, tid >> 5, 0), wg = wid >> 2, warp = wid & 3;
  int budget = SPIN_BUDGET;
  const int rank = blockIdx.x & 1;
  const uint32_t peer = mapa(sb, rank ^ 1);
  if (tid < 24) mbar_init(sb + B_FULL + 8 * tid, tid >> 3 == 1 ? 2 : 1);
  fence_mbar_init();
  if (wid == 1 && tid < 32 + sizeof(GemmMaps) / 128) asm volatile("prefetch.tensormap [%0];" :: "l"(&M.o + (tid - 32)) : "memory");
  __syncthreads();
  cluster_sync();
  const int cta = blockIdx.x, lane = lane_reg();
  if (wg >= 2) {
    reg_dec<72>();
    if (wid == 8 || wid == 10) {
      Pipe p; p.s = 0; p.ph = 1;
      for (int n = 0; ; n++) {
        if (wid == 8) e_expect_tx(sb + B_MSG + 8 * (n & 1), 4);
        mbar_wait(sb + B_MSG + 8 * (n & 1), (n >> 1) & 1, budget);
        const int msg = __shfl_sync(0xffffffffu, lds32v(sb + MSG + 4 * (n & 1)), 0);
        const int ty = (msg >> 11) & 3, l = (msg >> 10) & 1;
        const bool shb = ty == T_GU && l, spl = is_split(ty, l, (msg >> 6) & 15);
        const int cb = ((msg >> 6) & 15) + (shb ? rank : 0), j = (msg & 63) + (ty == T_END || shb ? 0 : rank);
        const int ke = ty == T_O ? 64 : ty == T_GU ? 16 : 56, k0 = spl ? rank : 0, dk = spl ? 2 : 1;
        const int c0 = ty == T_GU ? j * 64 : spl ? (j >> 1) * 128 : j * 128, c1 = ty == T_GU ? c0 : c0 + 64;
        mbar_wait(sb + B_EMPTY + 8 * p.s, p.ph, budget);
        trap_if_spent(budget);
        auto stages = [&](auto f) {
#pragma unroll 1
          for (int k = k0; k < ke; k += dk) {
            mbar_wait(sb + B_EMPTY + 8 * p.s, p.ph, budget);
            f(k, sb + p.s * STAGE_BYTES, sb + B_FULL + 8 * p.s);
            p.next();
          }
        };
        if (wid == 8) {
          const int job = ty << 11 | l << 10 | cb << 6 | j;
          sts32v(sb + JOB + 4 * (n & 1), job | p.s << 16 | (p.ph ^ 1) << 20);
          e_arrive(sb + B_JOB + 8 * (n & 1));
          if (ty == T_END) break;
          if (ty != T_GU) { e_expect_tx(sb + B_FULL + 8 * p.s, spl ? 16384 : STAGE_BYTES); p.next(); }
          const CUtensorMap* const m0 = ty == T_D ? &M.wd : shb && rank ? &M.wu : &M.wg, * const m1 = ty == T_D ? &M.wd : &M.wu;
          if (ty == T_O) stages([&](int k, uint32_t a, uint32_t fb) { e_expect_tx(fb, STAGE_BYTES); e_tma_5d(a + 16384, &M.wo, c0, k * 2, fb); e_tma_5d(a + 24576, &M.wo, c1, k * 2, fb); });
          else if (shb) stages([&](int k, uint32_t a, uint32_t fb) { e_expect_tx(fb, STAGE_BYTES); e_tma_2d_mc(a + 16384 + rank * 8192, m0, c0, k * 64, fb); });
          else stages([&](int k, uint32_t a, uint32_t fb) { e_expect_tx(fb, STAGE_BYTES); e_tma_2d(a + 16384, m0, c0, k * 64, fb); e_tma_2d(a + 24576, m1, c1, k * 64, fb); });
        } else {
          if (ty == T_END) break;
          const int row = l * SEQ + cb * 128, kt = ke + k0 - G_LOOK * dk;
          const uint64_t polA = ty != T_GU ? EVICT_FIRST : EVICT_NORMAL;
          int rdy = msg >> 16;
          auto need = [&](int k) {
            if (k == kt) e_arrive(sb + B_TRIG);
            while (k >= rdy && k >= (rdy = a_ready(ty, l, cb))) { __nanosleep(100); trap_if_spent(--budget); }
          };
          if (ty != T_GU) {
            need(0);
            const uint32_t a = sb + p.s * STAGE_BYTES, fb = sb + B_FULL + 8 * p.s;
            const CUtensorMap* const m = ty == T_D ? (spl ? &M.x1 : &M.x1s) : l ? (spl ? &M.x2 : &M.x2s) : &M.x;
            const int r = (ty == T_D ? row : cb * 128) + (spl ? rank * 64 : 0);
            e_tma_2d(a, m, c0, r, fb, polA); e_tma_2d(a + 16384, m, c1, r, fb, polA);
            p.next();
          }
          if (shb || spl) {
            const CUtensorMap* const ma = ty == T_O ? &M.o : ty == T_GU ? &M.xms : &M.hs;
            stages([&](int k, uint32_t a, uint32_t fb) { need(k); e_tma_2d(a, ma, k * 64, row, fb, polA); });
          } else {
            const CUtensorMap* const ma = ty == T_O ? &M.oh : ty == T_GU ? &M.xm : &M.h;
            stages([&](int k, uint32_t a, uint32_t fb) { need(k); e_tma_2d_mc(a + rank * 8192, ma, k * 64, row + rank * 64, fb, polA); });
          }
        }
      }
    } else if (wid == 9 && rank == 0) {
      uint32_t sm; asm volatile("mov.u32 %0, %%smid;" : "=r"(sm));
      const bool crowd = sm >= 124 || sm < 50;
      int d0, d1, t0, t1, pair = e_ticket(g_fl.ticket, crowd ? 1 : 256);
      auto peek = [&]() {
        d0 = ld_relaxed(g_fl.dep + lane); d1 = ld_relaxed(g_fl.dep + 32 + lane);
        t0 = ld_relaxed(g_fl.taken + lane); t1 = ld_relaxed(g_fl.taken + 32 + lane);
      };
      peek();
      {
        const int t = bcast(pair), a = t & 255, b = t >> 8, i = crowd ? a : 17 - b;
        pair = a + b >= 18 ? a + b : (int)((i < 12 ? ROLE0 >> (5 * i) : ROLE1 >> (5 * i - 60)) & 31);
      }
      int k1 = pair < 18 ? 0 : 48, skip = pair - 18;
      bool late = false;
      uint32_t wait1 = 0, wait2 = 0;
      for (int n = 0, ty = 0; ty != T_END; n++) {
        mbar_wait(sb + B_TRIG, (n & 1) ^ 1, budget);
        int l, cb, j, rdy = 64;
        while (true) {
          const int ph = k1 % 3;
          const bool gap = pair < 8 ? ph == 1 : pair >= 16 && ph == 2;
          if (k1 < 48) {
            cb = k1++ / 3;
            if (gap && late) continue;
            if (!gap) {
              l = 0;
              ty = pair < 8 ? (ph ? T_GU : T_O) : ph == 2 ? T_D : T_GU;
              j = 2 * (pair < 8 ? (ph ? pair + 10 : pair) : ph == 1 ? pair + 10 : pair - 8);
              rdy = a_ready(ty, 0, cb);
              if (ph == 0) late = rdy != 0;
              break;
            }
          }
          if (skip < 0) peek();
          const bool l0 = t0 < (lane < 16 ? (is_split(T_O, 1, lane) ? 8 : 4) : lane & 1 ? 0 : 56), l1 = lane < 16 && t1 < (lane < G_DS ? 4 : 8);
          const uint32_t rd = __ballot_sync(0xffffffffu, d0 >= (lane < 16 ? 256 : 128));
          uint32_t ok0 = __ballot_sync(0xffffffffu, l0) & rd & (rd >> 1 | 0xffff), ok1 = __ballot_sync(0xffffffffu, l1 && h_ready(d1) > 0);
          if (gap) { ok1 = 0; ok0 &= 0xffff0000u | (pair < 16 ? G_BOOT : (1u << G_O0) - 1); }
          ok0 &= ~wait2;
          ty = T_END; l = 1; cb = j = 0;
          if (!gap && !__any_sync(0xffffffffu, l0 || l1)) break;
          if (ok1 & ((1u << G_DS) - 1)) ok1 &= (1u << G_DS) - 1;
          const uint32_t dfirst = ok1 & __ballot_sync(0xffffffffu, lane < G_DF && d1 == 0x10141014);
          if (dfirst && !(ok0 & 0xffff)) { ok0 = 0; ok1 = dfirst; }
          else if (__any_sync(0xffffffffu, l0)) ok1 = 0;
          else if (!ok1 && !gap) ok1 = __ballot_sync(0xffffffffu, l1);
          uint32_t m = ok0 ? ok0 : ok1;
          if (!m && !gap) __nanosleep(100);
          while (m) {
            const int nth = ok0 ? 0 : pair % __popc(m);
            const int b = __ffs(__ballot_sync(0xffffffffu, __popc(m << (31 - lane)) > nth)) - 1, gn = b + (ok0 ? 0 : 32);
            const int sz = gn >> 4 == T_GU ? 56 : is_split(gn >> 4, 1, gn & 15) ? 8 : 4;
            m &= ~(1u << b);
            if (skip >= 0 && m && (skip -= sz - __shfl_sync(0xffffffffu, ok0 ? t0 : t1, b)) >= 0) continue;
            int t = e_ticket(g_fl.taken + gn);
            rdy = a_ready(gn >> 4, 1, gn & 15);
            t = bcast(t);
            if (t < sz) { ty = gn >> 4; cb = gn & 15; j = sz == 56 ? t : 2 * t; break; }
          }
          skip = -1;
          if (ty != T_END) break;
          trap_if_spent(--budget);
        }
        wait2 = wait1;
        wait1 = ty == T_O && l && cb >= G_FL ? (2u << cb) - (1u << G_FL) : 0;
        const int msg = rdy << 16 | ty << 11 | l << 10 | cb << 6 | j;
        e_st_async32(peer + MSG + 4 * (n & 1), msg, peer + B_MSG + 8 * (n & 1));
        e_st_async32(sb + MSG + 4 * (n & 1), msg, sb + B_MSG + 8 * (n & 1));
      }
    } else if (wg == 3) {
      bool open = lane < G_FL && ld_relaxed(g_fl.rows + lane) < 128;
      while (__any_sync(0xffffffffu, open)) {
        int v = 0;
        if (open) asm volatile("ld.acquire.gpu.global.s32 %0, [%1];" : "=r"(v) : "l"(g_fl.part + lane) : "memory");
        const uint32_t ok = __ballot_sync(0xffffffffu, open && v >= 128);
        if (!ok) {
          if (--budget <= 0) break;
          __nanosleep(500);
          continue;
        }
        const int cb = __ffs(__ballot_sync(0xffffffffu, __popc(ok << (31 - lane)) > (cta >> 5) % __popc(ok))) - 1;
        const int r = bcast(e_ticket(g_fl.rows + cb));
        if (r >= 128) { open = open && lane != cb; continue; }
        uint4 u[4];
#pragma unroll
        for (int i = 0; i < 4; i++) u[i] = ldg_rlx128((const uint4*)(g_x1[1] + (size_t)(cb * 128 + r) * DM) + i * 32 + lane);
        ln_row(u, g_xm[1] + (size_t)(cb * 128 + r) * DM, lane);
        __syncwarp();
        e_flag_add(g_fl.dep + grp(T_GU, 1, cb));
      }
      if (cta == 0 && wid == 12) {
        asm volatile("griddepcontrol.wait;" ::: "memory");
        g_fl.xn[lane >> 4][lane & 15][0] = 0;
      }
    }
    cluster_sync();
  } else {
    reg_inc<184>();
    const bool lead = warp == 0;
    const uint32_t eb = (warp == 1 ? peer : sb) + B_EMPTY;
    const int rl = warp < 2 ? 0 : -1;
    const uint32_t so = sb + SO + wg * 16384;
    const int r0 = warp * 16 + (lane & 7) + ((lane >> 3) & 1) * 8;
    const uint32_t sw = r0 * 128 + (((lane >> 4) ^ (r0 & 7)) << 4);
    int xph = 0;
    for (int n = wg; ; n += 2) {
      float d0[64], d1[64];
      mbar_wait(sb + B_JOB + 8 * wg, (n >> 1) & 1, budget);
      fault_if_spent(budget);
      const int job = __shfl_sync(0xffffffffu, lds32v(sb + JOB + 4 * wg), 0);
      const int ty = (job >> 11) & 3, l = (job >> 10) & 1, cb = (job >> 6) & 15, j = job & 63;
      if (ty == T_END) {
        if (n > 0) nbar_sync_r(1 + wg, 256);
        if (lead && !(job & 1)) { sts32v(sb + JOB + 4 * (wg ^ 1), job | 1); e_arrive(sb + B_JOB + 8 * (wg ^ 1)); }
        if (!(job & 1)) nbar_arrive_r(1 + (wg ^ 1), 256);
        break;
      }
      Pipe q; q.s = (job >> 16) & 15; q.ph = job >> 20;
      const bool spl = is_split(ty, l, cb);
      if (ty != T_GU) mbar_wait(sb + B_FULL + 8 * q.s, q.ph, budget);
#pragma unroll
      for (int m = 0; m < 2; m++) {
        float* d = m ? d1 : d0;
        if (ty != T_GU && !(m && spl)) {
#pragma unroll
          for (int c = 0; c < 8; c++) {
            uint32_t r[4];
            ldsm4(sb + q.s * STAGE_BYTES + (c >> 2) * 16384 + m * 8192 + (sw ^ ((c & 3) << 5)), r[0], r[1], r[2], r[3]);
#pragma unroll
            for (int i = 0; i < 4; i++) { d[8*c+2*i] = bf_lo(r[i]); d[8*c+2*i+1] = bf_hi(r[i]); }
          }
        } else {
#pragma unroll
          for (int i = 0; i < 64; i++) d[i] = 0.f;
        }
      }
      if (ty != T_GU) {
        fence_proxy_async();
        nbar_sync_r(3 + wg, 128);
        arrive_cl_if_eq(eb + 8 * q.s, lane, rl);
        q.next();
      }
      pin<64>(d0); pin<64>(d1);
      if (n > 0) nbar_sync_r(1 + wg, 256);
      const int nk = (ty == T_O ? 64 : ty == T_GU ? 16 : 56) >> spl;
      const uint32_t ro = spl ? rank * 512 : 0;
      int prev = 0;
      for (int i = 0; i < nk; i++) {
        mbar_wait(sb + B_FULL + 8 * q.s, q.ph, budget);
        const uint32_t da = desc_base(sb) + q.s * (STAGE_BYTES / 16);
        wg_fence();
        sfor<0, 4>([&](auto K) {
          constexpr int k = K;
          typedef Op<16384 + k * 2048, 8192, 1024, 1, 1> OB;
          wg_ss128<1, Op<k * 32, 16, 1024, 1, 0>, OB>(d0, da + ro, da);
          wg_ss128<1, Op<8192 + k * 32, 16, 1024, 1, 0>, OB>(d1, da - ro, da);
        });
        wg_commit();
        wg_wait<1>();
        arrive_cl_if_eq(eb + 8 * prev, lane, i ? rl : -1);
        prev = q.s;
        q.next();
      }
      nbar_arrive_r(1 + (wg ^ 1), 256);
      wg_wait<0>();
      pin<64>(d0); pin<64>(d1);
      arrive_cl_if_eq(eb + 8 * prev, lane, rl);
      if (spl) {
        const uint32_t xa = SO + wg * 16384 + warp * 512 + lane * 16;
        if (lead) e_expect_tx(sb + B_XF + 8 * wg, 16384);
        mbar_wait(sb + B_SF + 8 * wg, ((n >> 1) & 1) ^ 1, budget);
#pragma unroll
        for (int i = 0; i < 8; i++) {
          const float* d = d1 + 8 * i;
          st_async128(peer + xa + i * 2048, pack_bf16(d[0], d[1]), pack_bf16(d[2], d[3]), pack_bf16(d[4], d[5]), pack_bf16(d[6], d[7]), peer + B_XF + 8 * wg);
        }
        mbar_wait(sb + B_XF + 8 * wg, xph, budget);
        xph ^= 1;
        uint32_t y[32];
#pragma unroll
        for (int i = 0; i < 8; i++) {
          const float* d = d0 + 8 * i;
          const uint4 v = lds128(sb + xa + i * 2048);
          y[4*i] = pack_bf16(d[0] + bf_lo(v.x), d[1] + bf_hi(v.x)); y[4*i+1] = pack_bf16(d[2] + bf_lo(v.y), d[3] + bf_hi(v.y));
          y[4*i+2] = pack_bf16(d[4] + bf_lo(v.z), d[5] + bf_hi(v.z)); y[4*i+3] = pack_bf16(d[6] + bf_lo(v.w), d[7] + bf_hi(v.w));
        }
        const bool fuse = !l || (ty == T_O && cb >= G_FL);
        float2* const st = &g_stat[l ? 4 + (cb & 7) : ty + (cb & 1)][0][rank * 64 + warp * 16 + (lane >> 2) * 2];
        if (fuse) {
          float mn[2], sq[2];
#pragma unroll
          for (int z = 0; z < 2; z++) {
            float m = 0, s2 = 0;
#pragma unroll
            for (int i = 0; i < 16; i++) m += bf_lo(y[2*i+z]) + bf_hi(y[2*i+z]);
            m += __shfl_xor_sync(0xffffffffu, m, 1); m += __shfl_xor_sync(0xffffffffu, m, 2);
            m *= 1.f / 128;
#pragma unroll
            for (int i = 0; i < 16; i++) { const float a = bf_lo(y[2*i+z]) - m, b = bf_hi(y[2*i+z]) - m; s2 = fmaf(a, a, fmaf(b, b, s2)); }
            s2 += __shfl_xor_sync(0xffffffffu, s2, 1); s2 += __shfl_xor_sync(0xffffffffu, s2, 2);
            mn[z] = m; sq[z] = s2;
          }
          if ((lane & 3) == 0) stg_rlx128(st + (j >> 1) * 128, __float_as_uint(mn[0]), (__float_as_uint(sq[0]) & ~31u) | (cb + 1), __float_as_uint(mn[1]), __float_as_uint(sq[1]));
          __syncwarp();
        }
        const int row = (ty == T_O ? l * SEQ : 0) + cb * 128 + rank * 64;
        auto put = [&](const CUtensorMap* mo, auto f) {
          nbar_sync_r(3 + wg, 128);
#pragma unroll
          for (int c = 0; c < 8; c++) stsm4(so + (c >> 2) * 8192 + (sw ^ ((c & 3) << 5)), f(4*c), f(4*c+1), f(4*c+2), f(4*c+3));
          fence_proxy_async();
          nbar_sync_r(3 + wg, 128);
          if (lead) { e_tma_store_2d(mo, so, (j >> 1) * 128, row); e_tma_store_2d(mo, so + 8192, (j >> 1) * 128 + 64, row); bulk_commit(); }
        };
        if (fuse) {
          uint4 u[2];
          while (true) {
            __nanosleep(100);
            u[0] = ldg_rlx128(st + (lane & 3) * 256); u[1] = ldg_rlx128(st + (lane & 3) * 256 + 128);
            if (!__any_sync(0xffffffffu, ((u[0].y ^ (cb + 1)) | (u[1].y ^ (cb + 1))) & 31) || --budget <= 0) break;
          }
          float rs[2], mr[2];
#pragma unroll
          for (int z = 0; z < 2; z++) {
            const float ma = __uint_as_float(z ? u[0].z : u[0].x), mb = __uint_as_float(z ? u[1].z : u[1].x);
            float m = ma + mb;
            m += __shfl_xor_sync(0xffffffffu, m, 1); m += __shfl_xor_sync(0xffffffffu, m, 2);
            m *= 0.125f;
            float s2 = __uint_as_float(z ? u[0].w : u[0].y & ~31u) + __uint_as_float(z ? u[1].w : u[1].y & ~31u) + 128.f * ((ma - m) * (ma - m) + (mb - m) * (mb - m));
            s2 += __shfl_xor_sync(0xffffffffu, s2, 1); s2 += __shfl_xor_sync(0xffffffffu, s2, 2);
            rs[z] = rsqrtf(s2 * (1.f / DM) + 1e-5f); mr[z] = -m * rs[z];
          }
          put(ty == T_O ? &M.xm : &M.xn, [&](int i) { return pack_bf16(fmaf(bf_lo(y[i]), rs[i & 1], mr[i & 1]), fmaf(bf_hi(y[i]), rs[i & 1], mr[i & 1])); });
          if (lead) {
            bulk_wait<0>();
            e_flag_add_bulk(ty == T_D ? g_fl.xn[1][cb] : g_fl.dep + grp(T_GU, l, cb), 8);
          }
        }
        put(ty == T_O ? &M.x1 : l ? &M.out : &M.x2, [&](int i) { return y[i]; });
      } else {
        if (ty == T_GU) {
#pragma unroll
          for (int i = 0; i < 32; i++) { d0[i] = geglu(d0[i], d0[32 + i]); d1[i] = geglu(d1[i], d1[32 + i]); }
        }
#pragma unroll
        for (int hf = 0; hf < 2; hf++) {
          if (hf) {
            if (ty == T_GU) break;
            if (lead) bulk_wait_read<0>();
            nbar_sync_r(3 + wg, 128);
          }
#pragma unroll
          for (int m = 0; m < 2; m++)
#pragma unroll
            for (int c = 0; c < 4; c++) {
              const float* d = (m ? d1 : d0) + 32 * hf + 8 * c;
              stsm4(so + m * 8192 + (sw ^ (c << 5)), pack_bf16(d[0], d[1]), pack_bf16(d[2], d[3]), pack_bf16(d[4], d[5]), pack_bf16(d[6], d[7]));
            }
          fence_proxy_async();
          nbar_sync_r(3 + wg, 128);
          if (lead) {
            if (ty == T_GU) e_tma_store_2d(&M.hs, so, j * 64, l * SEQ + cb * 128); else e_tma_store_2d(ty == T_O ? &M.x1s : &M.outs, so, j * 128 + hf * 64, (ty == T_O ? SEQ : 0) + cb * 128);
            bulk_commit();
          }
        }
      }
      if (lead) {
        bulk_wait<0>();
        e_arrive_cl(peer + B_SF + 8 * wg);
        if (ty == T_GU) e_flag_add_bulk(g_fl.dep + grp(T_D, l, cb), j < 20 ? 1 : j < 36 ? 1 << 8 : 1 << 16);
        else if (ty == T_O) { e_flag_add_bulk(g_fl.dep + grp(T_D, l, cb), (2 << 24) >> spl); if (l && cb < G_FL) e_flag_add_bulk(g_fl.part + cb, 16 >> spl); }
        else if (!l) e_flag_add_bulk(g_fl.dep + grp(T_O, 1, cb), 8);
      }
    }
    cluster_sync();
  }
}

typedef CUresult (*PFN_encodeTiled)(CUtensorMap*, CUtensorMapDataType, cuuint32_t, void*, const cuuint64_t*, const cuuint64_t*,
                                    const cuuint32_t*, const cuuint32_t*, CUtensorMapInterleave, CUtensorMapSwizzle,
                                    CUtensorMapL2promotion, CUtensorMapFloatOOBfill);
static PFN_encodeTiled g_encode = nullptr;
static int g_sms = 0;
static CUtensorMap encode(const void* ptr, int rank, const cuuint64_t* dims, const cuuint64_t* strides, const cuuint32_t* box) {
  CUtensorMap m;
  const cuuint32_t es[5] = {1, 1, 1, 1, 1};
  g_encode(&m, CU_TENSOR_MAP_DATA_TYPE_BFLOAT16, rank, (void*)ptr, dims, strides, box, es, CU_TENSOR_MAP_INTERLEAVE_NONE,
           CU_TENSOR_MAP_SWIZZLE_128B, CU_TENSOR_MAP_L2_PROMOTION_NONE, CU_TENSOR_MAP_FLOAT_OOB_FILL_NONE);
  return m;
}
static CUtensorMap make_map(const void* ptr, uint64_t rows, uint64_t cols, uint32_t box_rows) {
  const cuuint64_t dims[2] = {cols, rows}, strides[1] = {cols * 2};
  const cuuint32_t box[2] = {64, box_rows};
  return encode(ptr, 2, dims, strides, box);
}
static CUtensorMap make_map_x(const void* ptr) {
  const cuuint64_t dims[3] = {DM, NSTEP * 32, 2}, strides[2] = {DM * 2, (cuuint64_t)NSTEP * 32 * DM * 2};
  const cuuint32_t box[3] = {64, 32, 2};
  return encode(ptr, 3, dims, strides, box);
}
static CUtensorMap make_map_x1(const void* ptr) {
  const cuuint64_t dims[3] = {64, 2 * NSTEP * 32, DM / 64}, strides[2] = {DM * 2, 128};
  const cuuint32_t box[3] = {64, 32, 2};
  return encode(ptr, 3, dims, strides, box);
}
static CUtensorMap make_map_wo(const void* ptr) {
  const cuuint64_t dims[5] = {DM, 2, 4, 4, NH * DH / 32}, strides[4] = {DM * 2, 8 * DM * 2, 2 * DM * 2, 32 * DM * 2};
  const cuuint32_t box[5] = {64, 2, 4, 4, 2};
  return encode(ptr, 5, dims, strides, box);
}

extern "C" void kernel_launch(void* const* d_in, const int* in_sizes, int n_in, void* d_out, int out_size) {
  const bf16 *x = (const bf16*)d_in[0], *mem0 = (const bf16*)d_in[1], *Wo = (const bf16*)d_in[5];
  if (!g_encode) {
    void* p = nullptr; cudaDriverEntryPointQueryResult q;
    cudaGetDriverEntryPoint("cuTensorMapEncodeTiled", &p, cudaEnableDefault, &q);
    g_encode = (PFN_encodeTiled)p;
    int dev = 0;
    cudaGetDevice(&dev);
    cudaDeviceGetAttribute(&g_sms, cudaDevAttrMultiProcessorCount, dev);
    cudaFuncSetAttribute(rec_kernel, cudaFuncAttributeMaxDynamicSharedMemorySize, rec::SMEM);
    cudaFuncSetAttribute(gemm_kernel, cudaFuncAttributeMaxDynamicSharedMemorySize, gm::SMEM);
  }
  void *xn, *o, *x1, *xm, *x2, *hh;
  cudaGetSymbolAddress(&xn, g_xn); cudaGetSymbolAddress(&o, g_o); cudaGetSymbolAddress(&x1, g_x1);
  cudaGetSymbolAddress(&xm, g_xm); cudaGetSymbolAddress(&x2, g_x2); cudaGetSymbolAddress(&hh, g_h);
  RecMaps R;
  for (int i = 0; i < 3; i++) R.w[i] = make_map(d_in[2 + i], DM, NH * DH, 16);
  R.wo = make_map(Wo, NH * DH, DM, 64); R.x[0] = make_map_x(xn); R.x[1] = make_map_x1(xn);
  rec_kernel<<<96, 512, rec::SMEM>>>(R, Wo, mem0, x, 0);
  GemmMaps G;
  G.o = make_map(o, 2 * SEQ, NH * DH, 128); G.oh = make_map(o, 2 * SEQ, NH * DH, 64); G.wo = make_map_wo(Wo);
  G.x1 = make_map(x1, 2 * SEQ, DM, 64); G.x1s = make_map(x1, 2 * SEQ, DM, 128);
  G.xn = make_map((bf16*)xn + (NSTEP + LAG) * 32 * DM, SEQ, DM, 64);
  G.xm = make_map(xm, 2 * SEQ, DM, 64); G.xms = make_map(xm, 2 * SEQ, DM, 128);
  G.wg = make_map(d_in[8], DM, DF, 64); G.wu = make_map(d_in[9], DM, DF, 64); G.wd = make_map(d_in[10], DF, DM, 64);
  G.h = make_map(hh, 2 * SEQ, DF, 64); G.hs = make_map(hh, 2 * SEQ, DF, 128);
  G.x = make_map(x, SEQ, DM, 64); G.x2 = make_map(x2, SEQ, DM, 64); G.x2s = make_map(x2, SEQ, DM, 128);
  G.out = make_map(d_out, SEQ, DM, 64); G.outs = make_map(d_out, SEQ, DM, 128);
  cudaLaunchConfig_t cfg = {};
  cfg.gridDim = dim3(g_sms & ~1); cfg.blockDim = dim3(512); cfg.dynamicSmemBytes = gm::SMEM; cfg.stream = cudaStreamPerThread;
  cudaLaunchAttribute at;
  at.id = cudaLaunchAttributeProgrammaticStreamSerialization; at.val.programmaticStreamSerializationAllowed = 1;
  cfg.attrs = &at; cfg.numAttrs = 1;
  cudaLaunchKernelEx(&cfg, gemm_kernel, G);
}
```
